```python
import torch

def _softmax(x, axis=-1):
    return torch.softmax(x, dim=axis)
def _gelu(x):
    return torch.nn.functional.gelu(x, approximate="tanh")
def _silu(x):
    return torch.nn.functional.silu(x)
def _sigmoid(x):
    return torch.sigmoid(x)
def _layernorm(x, axis=-1, eps=1e-5):
    m = x.mean(dim=axis, keepdim=True)
    v = x.var(dim=axis, keepdim=True, unbiased=False)
    return (x - m) / torch.sqrt(v + eps)
def _scatter_add(tgt, idx, src, axis=0):
    return tgt.clone().index_add_(axis, idx, src)
def _segment_sum(src, seg, n):
    out = torch.zeros((n,) + src.shape[1:], dtype=src.dtype)
    return out.index_add_(0, seg, src)
def _pad(x, pw):
    flat = tuple(v for pair in reversed(pw) for v in pair)
    return torch.nn.functional.pad(x, flat)

kernel_name = 'interleave_layers__sliding_local_dilated__dense_activation_squared_relu__prompt'

def setup_inputs():

    _w = (lambda a: (lambda t: t.to(torch.bfloat16) if t.is_floating_point() else t)(torch.as_tensor(a)))
    def _A_setup():
        B, S, D = 1, 2048, 1024
        return {
            "x": _w((lambda *s: torch.randn(*s, dtype=torch.bfloat16) * 0.05)(B, S, D)),
            "wqkv": _w((lambda *s: torch.randn(*s, dtype=torch.bfloat16) * 0.05)(D, 3 * D)),
            "wo": _w((lambda *s: torch.randn(*s, dtype=torch.bfloat16) * 0.05)(D, D)),
        }
    _A_in = _A_setup()

    def _B_setup():
        B, S, D, F = 1, 2048, 1024, 3584
        return {
            "x": _w((lambda *s: torch.randn(*s, dtype=torch.bfloat16) * 0.05)(B, S, D)),
            "w1": _w((lambda *s: torch.randn(*s, dtype=torch.bfloat16) * 0.05)(D, F)),
            "b1": _w((lambda *s: torch.randn(*s, dtype=torch.bfloat16) * 0.2)(F)),
            "w2": _w((lambda *s: torch.randn(*s, dtype=torch.bfloat16) * 0.05)(F, D)),
            "b2": _w((lambda *s: torch.randn(*s, dtype=torch.bfloat16) * 1.6)(D)),
        }
    _B_in = _B_setup()

    return {
        "A_x": _A_in["x"],
        "A_wqkv": _A_in["wqkv"],
        "A_wo": _A_in["wo"],
        "B_x": _B_in["x"],
        "B_w1": _B_in["w1"],
        "B_b1": _B_in["b1"],
        "B_w2": _B_in["w2"],
        "B_b2": _B_in["b2"],
    }

def reference(A_x, A_wqkv, A_wo, B_x, B_w1, B_b1, B_w2, B_b2):
    def _A_ref(x, wqkv, wo):
        B, S, D = x.shape
        H = 32; Dh = D // H
        W, dil = 8, 2
        qkv = (lambda x, *d: x.permute(*d))((x @ wqkv).reshape(B, S, 3, H, Dh), 2, 0, 3, 1, 4)
        q, k, v = qkv[0], qkv[1], qkv[2]
        scale = Dh ** -0.5
        pos = torch.arange(S)
        off = torch.arange(W) * dil
        idx = pos[:, None] - off[None, :]
        mask = idx >= 0
        idx_c = torch.where(mask, idx, 0).reshape(-1)
        kg = k[:, :, idx_c, :].reshape(B, H, S, W, Dh)
        vg = v[:, :, idx_c, :].reshape(B, H, S, W, Dh)
        logits = torch.einsum("bhsd,bhswd->bhsw", q, kg) * scale
        logits = torch.where(mask[None, None, :, :], logits, -1e9)
        attn = _softmax(logits, axis=-1)
        o = torch.einsum("bhsw,bhswd->bhsd", attn, vg)
        return (lambda x, *d: x.permute(*d))(o, 0, 2, 1, 3).reshape(B, S, D) @ wo

    def _B_ref(x, w1, b1, w2, b2):
        h = torch.einsum("bsd,df->bsf", x, w1) + b1
        zero = torch.zeros_like(h)
        r = torch.where(h > zero, h, zero)
        h = r * r
        out = torch.einsum("bsf,fd->bsd", h, w2) + b2
        return out

    x = A_x
    x = x + _A_ref(_layernorm(x, axis=-1), A_wqkv, A_wo)
    x = x + _B_ref(_layernorm(x, axis=-1), B_w1, B_b1, B_w2, B_b2)
    x = x + _A_ref(_layernorm(x, axis=-1), A_wqkv, A_wo)
    x = x + _B_ref(_layernorm(x, axis=-1), B_w1, B_b1, B_w2, B_b2)
    return x
```

```cpp
#include <cuda_runtime.h>
#include <cuda_bf16.h>
#include <cuda.h>
#include <stdint.h>

#define LEAD0 2
#define LEAD1 2
#define LEAD2 3
#define LEAD3 1
#define LEAD4 1
#define LEAD5 4
#define WPROMO CU_TENSOR_MAP_L2_PROMOTION_L2_256B
#define Q1 20
#define Q2 24
#define Q3 28
#define PACE2 0x1a
#define ST2 14
#define STB 3
#define PROBE 4
#define D0 2
#define NPRO 4
#define XPROMO CU_TENSOR_MAP_L2_PROMOTION_L2_256B
#define IPRE 7
#define FILLT 1
#define EARLYC 1
#define OWNDLY 0
#define STARTC 6500
#define PRE5 0
#define PRE2 0
#define FUN 4
#define XEF 0
#define BEF 0xff8
#define AEF 0xdb6
#define SEF 0
#define NPREPX 0
#define NPREPO 0
#define SDELAYO SDELAY
#define SDELAY 300
#define HDELAY 600
#define NH1 6
#define NH2 4
namespace {

constexpr int NMAIN = 128, NAUX = 4, NTHREADS = 384;
constexpr uint32_t OFF_B = 0;
constexpr uint32_t OFF_A = 131072;
constexpr uint32_t OFF_VEC = 229376;
constexpr uint32_t OFF_BAR = 231424;
constexpr uint32_t OFF_RSTD = OFF_VEC + 512, OFF_MEAN = OFF_VEC + 1088, OFF_HOLD = OFF_VEC + 2032;
constexpr uint32_t SMEM_BYTES = OFF_BAR + 960;
constexpr uint32_t BAR_FULLA = OFF_BAR, BAR_FULLB = OFF_BAR + 96, BAR_EMPTYB = OFF_BAR + 160, BAR_EMPTYA = OFF_BAR + 224,
                   BAR_STG = OFF_BAR + 320, BAR_OWN = OFF_BAR + 336, BAR_SRV = OFF_BAR + 352, BAR_STAT = OFF_BAR + 392, BAR_LEAD = OFF_BAR + 408, BAR_DUMMY = OFF_BAR + 416, BAR_HALO = OFF_BAR + 424, BAR_AUG = OFF_BAR + 440,
                   BAR_SPEC = OFF_BAR + 448, BAR_STG2 = OFF_BAR + 544, BAR_DUMMY3 = OFF_BAR + 384;
constexpr int NA = 6;
constexpr uint32_t SB = 1024;
constexpr uint32_t SPIN_LIMIT = 1u << 22;

enum { TM_XIN = 0, TM_X, TM_XA, TM_O, TM_H, TM_WQKV, TM_WO, TM_W1A, TM_W1B, TM_W2, TM_X16, TM_XA16, TM_O16, TM_COUNT };

struct Scratch;
struct Params {
  Scratch* s;
  __nv_bfloat16* out;
  const __nv_bfloat16* b1;
  const __nv_bfloat16* b2;
  CUtensorMap tm[TM_COUNT];
};

constexpr int NSTEP = 280;
enum : uint32_t { F_STAMP = 1u << 14, F_GATH = 1u << 15, F_NEW = 1u << 16, F_AUG = 1u << 17, F_NOA = 1u << 18, E_HAND = 1u << 19, E_ATTN = 1u << 20, E_XPUB0 = 1u << 21,
                  E_WAIT = 1u << 22, E_REL = 1u << 23, E_KEEP = 1u << 24, E_PART1 = 1u << 25, E_HALO = 1u << 26,
                  E_SIG = 1u << 27, E_RARE = F_NEW | E_KEEP | (0xfu << 20) | (3u << 26) };
struct Sched { uint32_t v[8][NSTEP + 8]; };
constexpr Sched make_sched() {
  Sched T{};
  for (int j = 0; j < 8; j++) {
    int owner[16] = {};
    for (int i = 0; i < 16; i++) owner[i] = -100;
    int p = 0, g = 0;
    for (int t = 0; t < 12; t++) {
      const int kind = t % 6, ks = kind == 5 ? 56 : (kind == 2 ? 16 : 17);
      for (int i = 0; i < ks; i++) {
        const bool augs = ks == 17 && i == 16;
        const int na = (kind == 2 || kind == 5) ? 2 : (augs ? 1 : (kind == 4 ? 4 : 3));
        if (i == 0) p = (0x20cc63 >> (4 * kind)) & 15;
        if (augs) p = (0x0f0af >> (4 * kind)) & 15;
        if (p + na > 16) p = 0;
        int need = g - 8;
        for (int a = p; a < p + na; a++) { if (owner[a] > need) need = owner[a]; owner[a] = g; }
        uint32_t k = i, f = i == (t ? 0 : NPRO) ? F_NEW : 0;
        if (augs) { k = 0; f |= F_AUG; }
        else if (kind == 0 || kind == 3) {
          const int d = t ? 0 : D0, o = i < d ? i : i - 2;
          if (i >= d && i < d + 2) { k = 2 * j + i - d; if (t) f |= F_NOA | (i == 0 ? E_XPUB0 : 0); }
          else { const int half = o >= 7; int u = o - 7 * half; u += u >= j; k = 2 * u + half; if (t && i == 6) f |= E_REL; if (t && i < 2 + NPREPX) f |= F_NOA; }
          if (i == 11) f |= E_HAND;
          if (i == 11 + d) f |= E_SIG;
        } else if (kind == 1 || kind == 4) {
          if (kind == 1) f |= i == 3 ? E_HAND : (i == 8 ? E_HAND | E_KEEP : (i == 5 ? E_HALO : 0));
          if (kind == 1) f |= i == 13 ? E_REL : 0;
          else if (i == 4 || i == 7 || i == 10) f |= E_HAND;
        } else if (kind == 2) {
          f |= i == 0 ? E_WAIT : (i == 3 ? E_HAND : (i == 5 ? E_HALO : 0));
          if (i == 8) { k = 8 + j; f |= E_ATTN | E_KEEP | F_NOA; }
          if (i > 8) k = i - 1 + (i - 9 >= j);
          if (i > 8 && i < 9 + NPREPO) f |= F_NOA;
          if (i == 11) f |= E_REL;
        } else {
          k = i < 24 ? (i / 3) * 7 + i % 3 : ((i - 24) / 4) * 7 + 3 + (i - 24) % 4;
          if (i == 4 || i == 7 || i == 10 || i == 13) f |= E_HAND;
          f |= i == 0 ? E_WAIT : (i == 24 ? E_WAIT | E_PART1 : 0);
        }
        if ((kind == 2 || kind == 5) && t < 11 && i == ks - (kind == 2 ? 1 : STB)) f |= F_STAMP;
        if (((PACE2 >> kind) & 1) && i == ST2) f |= F_STAMP;
        if (i == 0 && t && ((PACE2 >> ((t - 1) % 6)) & 1)) f |= F_GATH;
        T.v[j][g] = p | ((g - need) << 4) | (k << 8) | f;
        p += na; g++;
      }
    }
    T.v[j][NSTEP] = F_NEW | F_NOA | E_XPUB0 | (2 * j << 8);
  }
  return T;
}
__constant__ Sched c_sched = make_sched();
__device__ __forceinline__ int sched_k(uint32_t e) { return (e >> 2) & 0xfc0; }

struct Scratch {
  __nv_bfloat16 x[2048 * 1024];
  __nv_bfloat16 h[2048 * 3584];
  uint32_t epoch[160];
  uint8_t flags[8][2][64];
  uint32_t pace[8][32];
  uint32_t aug[2][32][1024];
  uint4 stats[4][512][8][2];
  uint4 halo[4][256][136];
};
__device__ __align__(1024) Scratch g_s;
#define PROF_T(w, t, i)
#define LT(i)
#define CT(n)
#define ST(i)
#define AP(i)

__device__ __forceinline__ int work_id() {
  uint32_t smid, nsm;
  asm volatile("mov.u32 %0, %%smid;" : "=r"(smid));
  asm volatile("mov.u32 %0, %%nsmid;" : "=r"(nsm));
  const int t = smid >> 1, u = t - 32, d = (u * 37) >> 8;
  int id = (t & 7) * 16 + (t >> 3) * 2;
  if (t >= 32) id = (1 + u - 7 * d) * 16 + (4 + d) * 2;
  if (t >= 60) id = t < 62 ? t * 2 + 8 : t * 2 - 116;
  return nsm == NMAIN + NAUX ? id + (smid & 1) : blockIdx.x;
}

__device__ __forceinline__ uint32_t smem_u32(const void* p) { return (uint32_t)__cvta_generic_to_shared(p); }
__device__ __forceinline__ void mbar_init(uint32_t bar, int cnt) { asm volatile("mbarrier.init.shared::cta.b64 [%0], %1;" ::"r"(bar), "r"(cnt)); }
__device__ __forceinline__ void mbar_expect_tx(uint32_t bar, uint32_t bytes) { asm volatile("mbarrier.arrive.expect_tx.shared::cta.b64 _, [%0], %1;" ::"r"(bar), "r"(bytes) : "memory"); }
__device__ __forceinline__ void mbar_arrive(uint32_t bar, uint32_t cnt) { asm volatile("mbarrier.arrive.shared::cta.b64 _, [%0], %1;" ::"r"(bar), "r"(cnt) : "memory"); }
__device__ __forceinline__ void arrive_n(uint32_t bar, bool on) { if (on) asm volatile("mbarrier.arrive.shared::cta.b64 _, [%0];" ::"r"(bar) : "memory"); }
__device__ __forceinline__ void mbar_wait(uint32_t bar, uint32_t parity) {
  asm volatile(
      "{\n.reg .pred p;\n.reg .u32 c;\nmov.u32 c, 0;\n"
      "LAB_WAIT:\nmbarrier.try_wait.parity.shared::cta.b64 p, [%0], %1;\n@p bra.uni DONE;\n"
      "add.u32 c, c, 1;\nsetp.lt.u32 p, c, 4000000;\n@p bra.uni LAB_WAIT;\ntrap;\nDONE:\n}" ::"r"(bar), "r"(parity) : "memory");
}
__device__ __forceinline__ void mbar_spin(uint32_t bar, uint32_t parity) {
  asm volatile("{\n.reg .pred p;\nLAB_WAIT:\nmbarrier.try_wait.parity.shared::cta.b64 p, [%0], %1;\n@!p pmevent 7;\n@!p bra.uni LAB_WAIT;\n}" ::"r"(bar), "r"(parity) : "memory");
}
__device__ __forceinline__ bool elect_one() {
  uint32_t p;
  asm volatile("{\n.reg .pred P;\nelect.sync _|P, 0xffffffff;\nselp.u32 %0, 1, 0, P;\n}" : "=r"(p));
  return p != 0;
}
__device__ __forceinline__ bool mbar_test(uint32_t bar, uint32_t parity) {
  uint32_t ok;
  asm volatile("{\n.reg .pred p;\nmbarrier.test_wait.parity.shared::cta.b64 p, [%1], %2;\nselp.u32 %0, 1, 0, p;\n}" : "=r"(ok) : "r"(bar), "r"(parity) : "memory");
  return ok != 0;
}
__device__ __forceinline__ void tma_ld2(uint32_t dst, const CUtensorMap* tm, int c0, int c1, uint32_t bar) {
  asm volatile("cp.async.bulk.tensor.2d.shared::cluster.global.mbarrier::complete_tx::bytes [%0], [%1, {%3, %4}], [%2];" ::"r"(dst), "l"(tm), "r"(bar), "r"(c0), "r"(c1) : "memory");
}
__device__ __forceinline__ void tma_ld4(uint32_t dst, const CUtensorMap* tm, int c1, int c2, int c3, uint32_t bar, uint64_t pol = 0x1000000000000000ull) {
  asm volatile("cp.async.bulk.tensor.4d.shared::cluster.global.mbarrier::complete_tx::bytes.L2::cache_hint [%0], [%1, {%3, %4, %5, %6}], [%2], %7;" ::"r"(dst), "l"(tm), "r"(bar), "r"(0), "r"(c1), "r"(c2), "r"(c3), "l"(pol) : "memory");
}
__device__ __forceinline__ void tma_st2(const CUtensorMap* tm, int c0, int c1, uint32_t src) {
  asm volatile("cp.async.bulk.tensor.2d.global.shared::cta.bulk_group [%0, {%2, %3}], [%1];" ::"l"(tm), "r"(src), "r"(c0), "r"(c1) : "memory");
}
__device__ __forceinline__ void bulk_ld(uint32_t dst, const void* src, uint32_t bytes, uint32_t bar) {
  asm volatile("cp.async.bulk.shared::cluster.global.mbarrier::complete_tx::bytes [%0], [%1], %2, [%3];" ::"r"(dst), "l"(src), "r"(bytes), "r"(bar) : "memory");
}
__device__ __forceinline__ void e_arrive(uint32_t bar, uint32_t cnt) {
  if (cnt == 1) asm volatile("{\n.reg .pred p;\nelect.sync _|p, 0xffffffff;\n@p mbarrier.arrive.shared::cta.b64 _, [%0];\n}" ::"r"(bar) : "memory");
  else asm volatile("{\n.reg .pred p;\nelect.sync _|p, 0xffffffff;\n@p mbarrier.arrive.shared::cta.b64 _, [%0], %1;\n}" ::"r"(bar), "r"(cnt) : "memory");
}
template <int BYTES = 8192> __device__ __forceinline__ void e_load(uint32_t dst, const CUtensorMap* tm, int c0, int c1, uint32_t bar, uint64_t pol = 0x1000000000000000ull) {
  asm volatile("{\n.reg .pred p;\nelect.sync _|p, 0xffffffff;\n@p mbarrier.arrive.expect_tx.shared::cta.b64 _, [%2], %5;\n"
               "@p cp.async.bulk.tensor.2d.shared::cluster.global.mbarrier::complete_tx::bytes.L2::cache_hint [%0], [%1, {%3, %4}], [%2], %6;\n}"
               ::"r"(dst), "l"(tm), "r"(bar), "r"(c0), "r"(c1), "n"(BYTES), "l"(pol) : "memory");
}
__device__ __forceinline__ void e_store(const CUtensorMap* tm, int c0, int c1, uint32_t src) {
  asm volatile("{\n.reg .pred p;\nfence.proxy.async.shared::cta;\nelect.sync _|p, 0xffffffff;\n"
               "@p cp.async.bulk.tensor.2d.global.shared::cta.bulk_group [%0, {%2, %3}], [%1];\ncp.async.bulk.commit_group;\n}"
               ::"l"(tm), "r"(src), "r"(c0), "r"(c1) : "memory");
}
__device__ __forceinline__ void bulk_commit() { asm volatile("cp.async.bulk.commit_group;" ::: "memory"); }
template <int N> __device__ __forceinline__ void bulk_wait_read() { asm volatile("cp.async.bulk.wait_group.read %0;" ::"n"(N) : "memory"); }
__device__ __forceinline__ void bulk_wait_all() { asm volatile("cp.async.bulk.wait_group 0;" ::: "memory"); }
__device__ __forceinline__ void fence_async_smem() { asm volatile("fence.proxy.async.shared::cta;" ::: "memory"); }
__device__ __forceinline__ void wg_fence() { asm volatile("wgmma.fence.sync.aligned;" ::: "memory"); }
__device__ __forceinline__ void wg_commit() { asm volatile("wgmma.commit_group.sync.aligned;" ::: "memory"); }
template <int N> __device__ __forceinline__ void wg_wait() { asm volatile("wgmma.wait_group.sync.aligned %0;" ::"n"(N) : "memory"); }
__device__ __forceinline__ void wg_bar(int w) { asm volatile("bar.sync %0, 128;" ::"r"(w + 1) : "memory"); }
__device__ __forceinline__ uint32_t ld_acquire(const uint32_t* p) { uint32_t v; asm volatile("ld.acquire.gpu.global.u32 %0, [%1];" : "=r"(v) : "l"(p) : "memory"); return v; }
__device__ __forceinline__ uint4 ld_relaxed4(const uint32_t* p) {
  uint4 v; asm volatile("ld.relaxed.gpu.global.v4.u32 {%0,%1,%2,%3}, [%4];" : "=r"(v.x), "=r"(v.y), "=r"(v.z), "=r"(v.w) : "l"(p) : "memory"); return v;
}
__device__ __forceinline__ void st_release8(uint8_t* p, uint32_t v) { asm volatile("st.release.gpu.global.u8 [%0], %1;" ::"l"(p), "r"(v) : "memory"); }
__device__ __forceinline__ uint32_t ld_relaxed(const uint32_t* p) { uint32_t v; asm volatile("ld.relaxed.gpu.global.u32 %0, [%1];" : "=r"(v) : "l"(p) : "memory"); return v; }
__device__ __forceinline__ void st_release(uint32_t* p, uint32_t v) { asm volatile("st.release.gpu.global.u32 [%0], %1;" ::"l"(p), "r"(v) : "memory"); }
__device__ __forceinline__ void st_pkt(uint4* p, uint32_t a, uint32_t b, uint32_t c, uint32_t d) {
  asm volatile("{\n.reg .b64 lo, hi;\n.reg .b128 v;\nmov.b64 lo, {%1, %2};\nmov.b64 hi, {%3, %4};\nmov.b128 v, {lo, hi};\nst.relaxed.gpu.global.b128 [%0], v;\n}" ::"l"(p), "r"(a), "r"(b), "r"(c), "r"(d) : "memory");
}
__device__ __forceinline__ uint4 ld_pkt(const uint4* p) {
  uint4 r;
  asm volatile("{\n.reg .b64 lo, hi;\n.reg .b128 v;\nld.relaxed.gpu.global.b128 v, [%4];\nmov.b128 {lo, hi}, v;\nmov.b64 {%0, %1}, lo;\nmov.b64 {%2, %3}, hi;\n}" : "=r"(r.x), "=r"(r.y), "=r"(r.z), "=r"(r.w) : "l"(p) : "memory");
  return r;
}
__device__ __forceinline__ uint32_t pack_bf16(float lo, float hi) { uint32_t d; asm("cvt.rn.bf16x2.f32 %0, %1, %2;" : "=r"(d) : "f"(hi), "f"(lo)); return d; }
__device__ __forceinline__ float ex2(float x) { float y; asm("ex2.approx.ftz.f32 %0, %1;" : "=f"(y) : "f"(x)); return y; }
__device__ __forceinline__ float rsq(float x) { float y; asm("rsqrt.approx.ftz.f32 %0, %1;" : "=f"(y) : "f"(x)); return y; }
__device__ __forceinline__ float rcp(float x) { float y; asm("rcp.approx.ftz.f32 %0, %1;" : "=f"(y) : "f"(x)); return y; }
__device__ __forceinline__ float bf_lo(uint32_t v) { return __uint_as_float(v << 16); }
__device__ __forceinline__ float bf_hi(uint32_t v) { return __uint_as_float(v & 0xffff0000u); }
__device__ __forceinline__ void stsm4(uint32_t addr, uint32_t a, uint32_t b, uint32_t c, uint32_t d) {
  asm volatile("stmatrix.sync.aligned.m8n8.x4.shared.b16 [%0], {%1, %2, %3, %4};" ::"r"(addr), "r"(a), "r"(b), "r"(c), "r"(d) : "memory");
}
__device__ __forceinline__ uint32_t movm(uint32_t a) { uint32_t d; asm volatile("movmatrix.sync.aligned.m8n8.trans.b16 %0, %1;" : "=r"(d) : "r"(a)); return d; }
__device__ __forceinline__ void mma16(float (&c)[4], uint32_t a0, uint32_t a1, uint32_t a2, uint32_t a3, uint32_t b0, uint32_t b1) {
  asm volatile("mma.sync.aligned.m16n8k16.row.col.f32.bf16.bf16.f32 {%0,%1,%2,%3}, {%4,%5,%6,%7}, {%8,%9}, {%0,%1,%2,%3};"
               : "+f"(c[0]), "+f"(c[1]), "+f"(c[2]), "+f"(c[3]) : "r"(a0), "r"(a1), "r"(a2), "r"(a3), "r"(b0), "r"(b1));
}
__device__ __forceinline__ void mma8(float (&c)[4], uint32_t a0, uint32_t a1, uint32_t b0) {
  asm volatile("mma.sync.aligned.m16n8k8.row.col.f32.bf16.bf16.f32 {%0,%1,%2,%3}, {%4,%5}, {%6}, {%0,%1,%2,%3};"
               : "+f"(c[0]), "+f"(c[1]), "+f"(c[2]), "+f"(c[3]) : "r"(a0), "r"(a1), "r"(b0));
}
__device__ __forceinline__ void sts128(uint32_t a, uint32_t x, uint32_t y, uint32_t z, uint32_t w) {
  asm volatile("st.shared.v4.b32 [%0], {%1,%2,%3,%4};" ::"r"(a), "r"(x), "r"(y), "r"(z), "r"(w) : "memory");
}
__device__ __forceinline__ float2 lds64(uint32_t a) { float2 v; asm volatile("ld.shared.v2.f32 {%0,%1}, [%2];" : "=f"(v.x), "=f"(v.y) : "r"(a)); return v; }
__device__ __forceinline__ float4 lds128(uint32_t a) { float4 v; asm volatile("ld.shared.v4.f32 {%0,%1,%2,%3}, [%4];" : "=f"(v.x), "=f"(v.y), "=f"(v.z), "=f"(v.w) : "r"(a)); return v; }
__device__ __forceinline__ uint32_t lds32(uint32_t a) { uint32_t v; asm volatile("ld.shared.b32 %0, [%1];" : "=r"(v) : "r"(a)); return v; }
template <int S> __device__ __forceinline__ void wgmma_first128(float (&d)[S], uint32_t da, uint32_t db) {
  asm volatile("{\n.reg .b64 a, b;\n.reg .b32 t, u, h;\n.reg .pred p, q;\nmov.b32 h, 0x40000040;\nwgmma.fence.sync.aligned;\n"
    "add.u32 t, %64, 0;\nadd.u32 u, %65, 0;\nmov.b64 a, {t, h};\nmov.b64 b, {u, h};\n"
    "wgmma.mma_async.sync.aligned.m64n128k16.f32.bf16.bf16 "
    "{%0, %1, %2, %3, %4, %5, %6, %7, %8, %9, %10, %11, %12, %13, %14, %15, %16, %17, %18, %19, %20, %21, %22, %23, %24, %25, %26, %27, %28, %29, %30, %31, %32, %33, %34, %35, %36, %37, %38, %39, %40, %41, %42, %43, %44, %45, %46, %47, %48, %49, %50, %51, %52, %53, %54, %55, %56, %57, %58, %59, %60, %61, %62, %63}, "
    "a, b, 0, 1, 1, 0, 1;\n"
    "add.u32 t, %64, 2;\nadd.u32 u, %65, 128;\nmov.b64 a, {t, h};\nmov.b64 b, {u, h};\n"
    "wgmma.mma_async.sync.aligned.m64n128k16.f32.bf16.bf16 "
    "{%0, %1, %2, %3, %4, %5, %6, %7, %8, %9, %10, %11, %12, %13, %14, %15, %16, %17, %18, %19, %20, %21, %22, %23, %24, %25, %26, %27, %28, %29, %30, %31, %32, %33, %34, %35, %36, %37, %38, %39, %40, %41, %42, %43, %44, %45, %46, %47, %48, %49, %50, %51, %52, %53, %54, %55, %56, %57, %58, %59, %60, %61, %62, %63}, "
    "a, b, 1, 1, 1, 0, 1;\n"
    "add.u32 t, %64, 4;\nadd.u32 u, %65, 256;\nmov.b64 a, {t, h};\nmov.b64 b, {u, h};\n"
    "wgmma.mma_async.sync.aligned.m64n128k16.f32.bf16.bf16 "
    "{%0, %1, %2, %3, %4, %5, %6, %7, %8, %9, %10, %11, %12, %13, %14, %15, %16, %17, %18, %19, %20, %21, %22, %23, %24, %25, %26, %27, %28, %29, %30, %31, %32, %33, %34, %35, %36, %37, %38, %39, %40, %41, %42, %43, %44, %45, %46, %47, %48, %49, %50, %51, %52, %53, %54, %55, %56, %57, %58, %59, %60, %61, %62, %63}, "
    "a, b, 1, 1, 1, 0, 1;\n"
    "add.u32 t, %64, 6;\nadd.u32 u, %65, 384;\nmov.b64 a, {t, h};\nmov.b64 b, {u, h};\n"
    "wgmma.mma_async.sync.aligned.m64n128k16.f32.bf16.bf16 "
    "{%0, %1, %2, %3, %4, %5, %6, %7, %8, %9, %10, %11, %12, %13, %14, %15, %16, %17, %18, %19, %20, %21, %22, %23, %24, %25, %26, %27, %28, %29, %30, %31, %32, %33, %34, %35, %36, %37, %38, %39, %40, %41, %42, %43, %44, %45, %46, %47, %48, %49, %50, %51, %52, %53, %54, %55, %56, %57, %58, %59, %60, %61, %62, %63}, "
    "a, b, 1, 1, 1, 0, 1;\n"
    "wgmma.commit_group.sync.aligned;\n}"
    : "=f"(d[0]), "=f"(d[1]), "=f"(d[2]), "=f"(d[3]), "=f"(d[4]), "=f"(d[5]), "=f"(d[6]), "=f"(d[7]), "=f"(d[8]), "=f"(d[9]), "=f"(d[10]), "=f"(d[11]), "=f"(d[12]), "=f"(d[13]), "=f"(d[14]), "=f"(d[15]), "=f"(d[16]), "=f"(d[17]), "=f"(d[18]), "=f"(d[19]), "=f"(d[20]), "=f"(d[21]), "=f"(d[22]), "=f"(d[23]), "=f"(d[24]), "=f"(d[25]), "=f"(d[26]), "=f"(d[27]), "=f"(d[28]), "=f"(d[29]), "=f"(d[30]), "=f"(d[31]), "=f"(d[32]), "=f"(d[33]), "=f"(d[34]), "=f"(d[35]), "=f"(d[36]), "=f"(d[37]), "=f"(d[38]), "=f"(d[39]), "=f"(d[40]), "=f"(d[41]), "=f"(d[42]), "=f"(d[43]), "=f"(d[44]), "=f"(d[45]), "=f"(d[46]), "=f"(d[47]), "=f"(d[48]), "=f"(d[49]), "=f"(d[50]), "=f"(d[51]), "=f"(d[52]), "=f"(d[53]), "=f"(d[54]), "=f"(d[55]), "=f"(d[56]), "=f"(d[57]), "=f"(d[58]), "=f"(d[59]), "=f"(d[60]), "=f"(d[61]), "=f"(d[62]), "=f"(d[63])
    : "r"(da), "r"(db) : "memory");
}
template <int S> __device__ __forceinline__ uint2 wgmma_probe128(float (&d)[S], uint32_t da, uint32_t db, uint32_t b0, uint32_t p0, uint32_t b1, uint32_t p1) {
  uint2 ok;
  asm volatile("{\n.reg .b64 a, b;\n.reg .b32 t, u, h;\n.reg .pred p, q;\nmov.b32 h, 0x40000040;\nwgmma.fence.sync.aligned;\n"
    "add.u32 t, %66, 0;\nadd.u32 u, %67, 0;\nmov.b64 a, {t, h};\nmov.b64 b, {u, h};\n"
    "wgmma.mma_async.sync.aligned.m64n128k16.f32.bf16.bf16 "
    "{%2, %3, %4, %5, %6, %7, %8, %9, %10, %11, %12, %13, %14, %15, %16, %17, %18, %19, %20, %21, %22, %23, %24, %25, %26, %27, %28, %29, %30, %31, %32, %33, %34, %35, %36, %37, %38, %39, %40, %41, %42, %43, %44, %45, %46, %47, %48, %49, %50, %51, %52, %53, %54, %55, %56, %57, %58, %59, %60, %61, %62, %63, %64, %65}, "
    "a, b, 1, 1, 1, 0, 1;\n"
    "add.u32 t, %66, 2;\nadd.u32 u, %67, 128;\nmov.b64 a, {t, h};\nmov.b64 b, {u, h};\n"
    "wgmma.mma_async.sync.aligned.m64n128k16.f32.bf16.bf16 "
    "{%2, %3, %4, %5, %6, %7, %8, %9, %10, %11, %12, %13, %14, %15, %16, %17, %18, %19, %20, %21, %22, %23, %24, %25, %26, %27, %28, %29, %30, %31, %32, %33, %34, %35, %36, %37, %38, %39, %40, %41, %42, %43, %44, %45, %46, %47, %48, %49, %50, %51, %52, %53, %54, %55, %56, %57, %58, %59, %60, %61, %62, %63, %64, %65}, "
    "a, b, 1, 1, 1, 0, 1;\n"
    "mbarrier.test_wait.parity.shared::cta.b64 p, [%68], %69;\nmbarrier.test_wait.parity.shared::cta.b64 q, [%70], %71;\n"
    "add.u32 t, %66, 4;\nadd.u32 u, %67, 256;\nmov.b64 a, {t, h};\nmov.b64 b, {u, h};\n"
    "wgmma.mma_async.sync.aligned.m64n128k16.f32.bf16.bf16 "
    "{%2, %3, %4, %5, %6, %7, %8, %9, %10, %11, %12, %13, %14, %15, %16, %17, %18, %19, %20, %21, %22, %23, %24, %25, %26, %27, %28, %29, %30, %31, %32, %33, %34, %35, %36, %37, %38, %39, %40, %41, %42, %43, %44, %45, %46, %47, %48, %49, %50, %51, %52, %53, %54, %55, %56, %57, %58, %59, %60, %61, %62, %63, %64, %65}, "
    "a, b, 1, 1, 1, 0, 1;\n"
    "add.u32 t, %66, 6;\nadd.u32 u, %67, 384;\nmov.b64 a, {t, h};\nmov.b64 b, {u, h};\n"
    "wgmma.mma_async.sync.aligned.m64n128k16.f32.bf16.bf16 "
    "{%2, %3, %4, %5, %6, %7, %8, %9, %10, %11, %12, %13, %14, %15, %16, %17, %18, %19, %20, %21, %22, %23, %24, %25, %26, %27, %28, %29, %30, %31, %32, %33, %34, %35, %36, %37, %38, %39, %40, %41, %42, %43, %44, %45, %46, %47, %48, %49, %50, %51, %52, %53, %54, %55, %56, %57, %58, %59, %60, %61, %62, %63, %64, %65}, "
    "a, b, 1, 1, 1, 0, 1;\n"
    "wgmma.commit_group.sync.aligned;\nselp.u32 %0, 1, 0, p;\nselp.u32 %1, 1, 0, q;\n}"
    : "=r"(ok.x), "=r"(ok.y), "+f"(d[0]), "+f"(d[1]), "+f"(d[2]), "+f"(d[3]), "+f"(d[4]), "+f"(d[5]), "+f"(d[6]), "+f"(d[7]), "+f"(d[8]), "+f"(d[9]), "+f"(d[10]), "+f"(d[11]), "+f"(d[12]), "+f"(d[13]), "+f"(d[14]), "+f"(d[15]), "+f"(d[16]), "+f"(d[17]), "+f"(d[18]), "+f"(d[19]), "+f"(d[20]), "+f"(d[21]), "+f"(d[22]), "+f"(d[23]), "+f"(d[24]), "+f"(d[25]), "+f"(d[26]), "+f"(d[27]), "+f"(d[28]), "+f"(d[29]), "+f"(d[30]), "+f"(d[31]), "+f"(d[32]), "+f"(d[33]), "+f"(d[34]), "+f"(d[35]), "+f"(d[36]), "+f"(d[37]), "+f"(d[38]), "+f"(d[39]), "+f"(d[40]), "+f"(d[41]), "+f"(d[42]), "+f"(d[43]), "+f"(d[44]), "+f"(d[45]), "+f"(d[46]), "+f"(d[47]), "+f"(d[48]), "+f"(d[49]), "+f"(d[50]), "+f"(d[51]), "+f"(d[52]), "+f"(d[53]), "+f"(d[54]), "+f"(d[55]), "+f"(d[56]), "+f"(d[57]), "+f"(d[58]), "+f"(d[59]), "+f"(d[60]), "+f"(d[61]), "+f"(d[62]), "+f"(d[63])
    : "r"(da), "r"(db), "r"(b0), "r"(p0), "r"(b1), "r"(p1) : "memory");
  return ok;
}
template <int S> __device__ __forceinline__ void wgmma_first192(float (&d)[S], uint32_t da, uint32_t db) {
  asm volatile("{\n.reg .b64 a, b;\n.reg .b32 t, u, h;\n.reg .pred p, q;\nmov.b32 h, 0x40000040;\nwgmma.fence.sync.aligned;\n"
    "add.u32 t, %96, 0;\nadd.u32 u, %97, 0;\nmov.b64 a, {t, h};\nmov.b64 b, {u, h};\n"
    "wgmma.mma_async.sync.aligned.m64n192k16.f32.bf16.bf16 "
    "{%0, %1, %2, %3, %4, %5, %6, %7, %8, %9, %10, %11, %12, %13, %14, %15, %16, %17, %18, %19, %20, %21, %22, %23, %24, %25, %26, %27, %28, %29, %30, %31, %32, %33, %34, %35, %36, %37, %38, %39, %40, %41, %42, %43, %44, %45, %46, %47, %48, %49, %50, %51, %52, %53, %54, %55, %56, %57, %58, %59, %60, %61, %62, %63, %64, %65, %66, %67, %68, %69, %70, %71, %72, %73, %74, %75, %76, %77, %78, %79, %80, %81, %82, %83, %84, %85, %86, %87, %88, %89, %90, %91, %92, %93, %94, %95}, "
    "a, b, 0, 1, 1, 0, 1;\n"
    "add.u32 t, %96, 2;\nadd.u32 u, %97, 128;\nmov.b64 a, {t, h};\nmov.b64 b, {u, h};\n"
    "wgmma.mma_async.sync.aligned.m64n192k16.f32.bf16.bf16 "
    "{%0, %1, %2, %3, %4, %5, %6, %7, %8, %9, %10, %11, %12, %13, %14, %15, %16, %17, %18, %19, %20, %21, %22, %23, %24, %25, %26, %27, %28, %29, %30, %31, %32, %33, %34, %35, %36, %37, %38, %39, %40, %41, %42, %43, %44, %45, %46, %47, %48, %49, %50, %51, %52, %53, %54, %55, %56, %57, %58, %59, %60, %61, %62, %63, %64, %65, %66, %67, %68, %69, %70, %71, %72, %73, %74, %75, %76, %77, %78, %79, %80, %81, %82, %83, %84, %85, %86, %87, %88, %89, %90, %91, %92, %93, %94, %95}, "
    "a, b, 1, 1, 1, 0, 1;\n"
    "add.u32 t, %96, 4;\nadd.u32 u, %97, 256;\nmov.b64 a, {t, h};\nmov.b64 b, {u, h};\n"
    "wgmma.mma_async.sync.aligned.m64n192k16.f32.bf16.bf16 "
    "{%0, %1, %2, %3, %4, %5, %6, %7, %8, %9, %10, %11, %12, %13, %14, %15, %16, %17, %18, %19, %20, %21, %22, %23, %24, %25, %26, %27, %28, %29, %30, %31, %32, %33, %34, %35, %36, %37, %38, %39, %40, %41, %42, %43, %44, %45, %46, %47, %48, %49, %50, %51, %52, %53, %54, %55, %56, %57, %58, %59, %60, %61, %62, %63, %64, %65, %66, %67, %68, %69, %70, %71, %72, %73, %74, %75, %76, %77, %78, %79, %80, %81, %82, %83, %84, %85, %86, %87, %88, %89, %90, %91, %92, %93, %94, %95}, "
    "a, b, 1, 1, 1, 0, 1;\n"
    "add.u32 t, %96, 6;\nadd.u32 u, %97, 384;\nmov.b64 a, {t, h};\nmov.b64 b, {u, h};\n"
    "wgmma.mma_async.sync.aligned.m64n192k16.f32.bf16.bf16 "
    "{%0, %1, %2, %3, %4, %5, %6, %7, %8, %9, %10, %11, %12, %13, %14, %15, %16, %17, %18, %19, %20, %21, %22, %23, %24, %25, %26, %27, %28, %29, %30, %31, %32, %33, %34, %35, %36, %37, %38, %39, %40, %41, %42, %43, %44, %45, %46, %47, %48, %49, %50, %51, %52, %53, %54, %55, %56, %57, %58, %59, %60, %61, %62, %63, %64, %65, %66, %67, %68, %69, %70, %71, %72, %73, %74, %75, %76, %77, %78, %79, %80, %81, %82, %83, %84, %85, %86, %87, %88, %89, %90, %91, %92, %93, %94, %95}, "
    "a, b, 1, 1, 1, 0, 1;\n"
    "wgmma.commit_group.sync.aligned;\n}"
    : "=f"(d[0]), "=f"(d[1]), "=f"(d[2]), "=f"(d[3]), "=f"(d[4]), "=f"(d[5]), "=f"(d[6]), "=f"(d[7]), "=f"(d[8]), "=f"(d[9]), "=f"(d[10]), "=f"(d[11]), "=f"(d[12]), "=f"(d[13]), "=f"(d[14]), "=f"(d[15]), "=f"(d[16]), "=f"(d[17]), "=f"(d[18]), "=f"(d[19]), "=f"(d[20]), "=f"(d[21]), "=f"(d[22]), "=f"(d[23]), "=f"(d[24]), "=f"(d[25]), "=f"(d[26]), "=f"(d[27]), "=f"(d[28]), "=f"(d[29]), "=f"(d[30]), "=f"(d[31]), "=f"(d[32]), "=f"(d[33]), "=f"(d[34]), "=f"(d[35]), "=f"(d[36]), "=f"(d[37]), "=f"(d[38]), "=f"(d[39]), "=f"(d[40]), "=f"(d[41]), "=f"(d[42]), "=f"(d[43]), "=f"(d[44]), "=f"(d[45]), "=f"(d[46]), "=f"(d[47]), "=f"(d[48]), "=f"(d[49]), "=f"(d[50]), "=f"(d[51]), "=f"(d[52]), "=f"(d[53]), "=f"(d[54]), "=f"(d[55]), "=f"(d[56]), "=f"(d[57]), "=f"(d[58]), "=f"(d[59]), "=f"(d[60]), "=f"(d[61]), "=f"(d[62]), "=f"(d[63]), "=f"(d[64]), "=f"(d[65]), "=f"(d[66]), "=f"(d[67]), "=f"(d[68]), "=f"(d[69]), "=f"(d[70]), "=f"(d[71]), "=f"(d[72]), "=f"(d[73]), "=f"(d[74]), "=f"(d[75]), "=f"(d[76]), "=f"(d[77]), "=f"(d[78]), "=f"(d[79]), "=f"(d[80]), "=f"(d[81]), "=f"(d[82]), "=f"(d[83]), "=f"(d[84]), "=f"(d[85]), "=f"(d[86]), "=f"(d[87]), "=f"(d[88]), "=f"(d[89]), "=f"(d[90]), "=f"(d[91]), "=f"(d[92]), "=f"(d[93]), "=f"(d[94]), "=f"(d[95])
    : "r"(da), "r"(db) : "memory");
}
template <int S> __device__ __forceinline__ uint2 wgmma_probe192(float (&d)[S], uint32_t da, uint32_t db, uint32_t b0, uint32_t p0, uint32_t b1, uint32_t p1) {
  uint2 ok;
  asm volatile("{\n.reg .b64 a, b;\n.reg .b32 t, u, h;\n.reg .pred p, q;\nmov.b32 h, 0x40000040;\nwgmma.fence.sync.aligned;\n"
    "add.u32 t, %98, 0;\nadd.u32 u, %99, 0;\nmov.b64 a, {t, h};\nmov.b64 b, {u, h};\n"
    "wgmma.mma_async.sync.aligned.m64n192k16.f32.bf16.bf16 "
    "{%2, %3, %4, %5, %6, %7, %8, %9, %10, %11, %12, %13, %14, %15, %16, %17, %18, %19, %20, %21, %22, %23, %24, %25, %26, %27, %28, %29, %30, %31, %32, %33, %34, %35, %36, %37, %38, %39, %40, %41, %42, %43, %44, %45, %46, %47, %48, %49, %50, %51, %52, %53, %54, %55, %56, %57, %58, %59, %60, %61, %62, %63, %64, %65, %66, %67, %68, %69, %70, %71, %72, %73, %74, %75, %76, %77, %78, %79, %80, %81, %82, %83, %84, %85, %86, %87, %88, %89, %90, %91, %92, %93, %94, %95, %96, %97}, "
    "a, b, 1, 1, 1, 0, 1;\n"
    "add.u32 t, %98, 2;\nadd.u32 u, %99, 128;\nmov.b64 a, {t, h};\nmov.b64 b, {u, h};\n"
    "wgmma.mma_async.sync.aligned.m64n192k16.f32.bf16.bf16 "
    "{%2, %3, %4, %5, %6, %7, %8, %9, %10, %11, %12, %13, %14, %15, %16, %17, %18, %19, %20, %21, %22, %23, %24, %25, %26, %27, %28, %29, %30, %31, %32, %33, %34, %35, %36, %37, %38, %39, %40, %41, %42, %43, %44, %45, %46, %47, %48, %49, %50, %51, %52, %53, %54, %55, %56, %57, %58, %59, %60, %61, %62, %63, %64, %65, %66, %67, %68, %69, %70, %71, %72, %73, %74, %75, %76, %77, %78, %79, %80, %81, %82, %83, %84, %85, %86, %87, %88, %89, %90, %91, %92, %93, %94, %95, %96, %97}, "
    "a, b, 1, 1, 1, 0, 1;\n"
    "mbarrier.test_wait.parity.shared::cta.b64 p, [%100], %101;\nmbarrier.test_wait.parity.shared::cta.b64 q, [%102], %103;\n"
    "add.u32 t, %98, 4;\nadd.u32 u, %99, 256;\nmov.b64 a, {t, h};\nmov.b64 b, {u, h};\n"
    "wgmma.mma_async.sync.aligned.m64n192k16.f32.bf16.bf16 "
    "{%2, %3, %4, %5, %6, %7, %8, %9, %10, %11, %12, %13, %14, %15, %16, %17, %18, %19, %20, %21, %22, %23, %24, %25, %26, %27, %28, %29, %30, %31, %32, %33, %34, %35, %36, %37, %38, %39, %40, %41, %42, %43, %44, %45, %46, %47, %48, %49, %50, %51, %52, %53, %54, %55, %56, %57, %58, %59, %60, %61, %62, %63, %64, %65, %66, %67, %68, %69, %70, %71, %72, %73, %74, %75, %76, %77, %78, %79, %80, %81, %82, %83, %84, %85, %86, %87, %88, %89, %90, %91, %92, %93, %94, %95, %96, %97}, "
    "a, b, 1, 1, 1, 0, 1;\n"
    "add.u32 t, %98, 6;\nadd.u32 u, %99, 384;\nmov.b64 a, {t, h};\nmov.b64 b, {u, h};\n"
    "wgmma.mma_async.sync.aligned.m64n192k16.f32.bf16.bf16 "
    "{%2, %3, %4, %5, %6, %7, %8, %9, %10, %11, %12, %13, %14, %15, %16, %17, %18, %19, %20, %21, %22, %23, %24, %25, %26, %27, %28, %29, %30, %31, %32, %33, %34, %35, %36, %37, %38, %39, %40, %41, %42, %43, %44, %45, %46, %47, %48, %49, %50, %51, %52, %53, %54, %55, %56, %57, %58, %59, %60, %61, %62, %63, %64, %65, %66, %67, %68, %69, %70, %71, %72, %73, %74, %75, %76, %77, %78, %79, %80, %81, %82, %83, %84, %85, %86, %87, %88, %89, %90, %91, %92, %93, %94, %95, %96, %97}, "
    "a, b, 1, 1, 1, 0, 1;\n"
    "wgmma.commit_group.sync.aligned;\nselp.u32 %0, 1, 0, p;\nselp.u32 %1, 1, 0, q;\n}"
    : "=r"(ok.x), "=r"(ok.y), "+f"(d[0]), "+f"(d[1]), "+f"(d[2]), "+f"(d[3]), "+f"(d[4]), "+f"(d[5]), "+f"(d[6]), "+f"(d[7]), "+f"(d[8]), "+f"(d[9]), "+f"(d[10]), "+f"(d[11]), "+f"(d[12]), "+f"(d[13]), "+f"(d[14]), "+f"(d[15]), "+f"(d[16]), "+f"(d[17]), "+f"(d[18]), "+f"(d[19]), "+f"(d[20]), "+f"(d[21]), "+f"(d[22]), "+f"(d[23]), "+f"(d[24]), "+f"(d[25]), "+f"(d[26]), "+f"(d[27]), "+f"(d[28]), "+f"(d[29]), "+f"(d[30]), "+f"(d[31]), "+f"(d[32]), "+f"(d[33]), "+f"(d[34]), "+f"(d[35]), "+f"(d[36]), "+f"(d[37]), "+f"(d[38]), "+f"(d[39]), "+f"(d[40]), "+f"(d[41]), "+f"(d[42]), "+f"(d[43]), "+f"(d[44]), "+f"(d[45]), "+f"(d[46]), "+f"(d[47]), "+f"(d[48]), "+f"(d[49]), "+f"(d[50]), "+f"(d[51]), "+f"(d[52]), "+f"(d[53]), "+f"(d[54]), "+f"(d[55]), "+f"(d[56]), "+f"(d[57]), "+f"(d[58]), "+f"(d[59]), "+f"(d[60]), "+f"(d[61]), "+f"(d[62]), "+f"(d[63]), "+f"(d[64]), "+f"(d[65]), "+f"(d[66]), "+f"(d[67]), "+f"(d[68]), "+f"(d[69]), "+f"(d[70]), "+f"(d[71]), "+f"(d[72]), "+f"(d[73]), "+f"(d[74]), "+f"(d[75]), "+f"(d[76]), "+f"(d[77]), "+f"(d[78]), "+f"(d[79]), "+f"(d[80]), "+f"(d[81]), "+f"(d[82]), "+f"(d[83]), "+f"(d[84]), "+f"(d[85]), "+f"(d[86]), "+f"(d[87]), "+f"(d[88]), "+f"(d[89]), "+f"(d[90]), "+f"(d[91]), "+f"(d[92]), "+f"(d[93]), "+f"(d[94]), "+f"(d[95])
    : "r"(da), "r"(db), "r"(b0), "r"(p0), "r"(b1), "r"(p1) : "memory");
  return ok;
}
template <int S> __device__ __forceinline__ void wgmma_first256(float (&d)[S], uint32_t da, uint32_t db) {
  asm volatile("{\n.reg .b64 a, b;\n.reg .b32 t, u, h;\n.reg .pred p, q;\nmov.b32 h, 0x40000040;\nwgmma.fence.sync.aligned;\n"
    "add.u32 t, %128, 0;\nadd.u32 u, %129, 0;\nmov.b64 a, {t, h};\nmov.b64 b, {u, h};\n"
    "wgmma.mma_async.sync.aligned.m64n256k16.f32.bf16.bf16 "
    "{%0, %1, %2, %3, %4, %5, %6, %7, %8, %9, %10, %11, %12, %13, %14, %15, %16, %17, %18, %19, %20, %21, %22, %23, %24, %25, %26, %27, %28, %29, %30, %31, %32, %33, %34, %35, %36, %37, %38, %39, %40, %41, %42, %43, %44, %45, %46, %47, %48, %49, %50, %51, %52, %53, %54, %55, %56, %57, %58, %59, %60, %61, %62, %63, %64, %65, %66, %67, %68, %69, %70, %71, %72, %73, %74, %75, %76, %77, %78, %79, %80, %81, %82, %83, %84, %85, %86, %87, %88, %89, %90, %91, %92, %93, %94, %95, %96, %97, %98, %99, %100, %101, %102, %103, %104, %105, %106, %107, %108, %109, %110, %111, %112, %113, %114, %115, %116, %117, %118, %119, %120, %121, %122, %123, %124, %125, %126, %127}, "
    "a, b, 0, 1, 1, 0, 1;\n"
    "add.u32 t, %128, 2;\nadd.u32 u, %129, 128;\nmov.b64 a, {t, h};\nmov.b64 b, {u, h};\n"
    "wgmma.mma_async.sync.aligned.m64n256k16.f32.bf16.bf16 "
    "{%0, %1, %2, %3, %4, %5, %6, %7, %8, %9, %10, %11, %12, %13, %14, %15, %16, %17, %18, %19, %20, %21, %22, %23, %24, %25, %26, %27, %28, %29, %30, %31, %32, %33, %34, %35, %36, %37, %38, %39, %40, %41, %42, %43, %44, %45, %46, %47, %48, %49, %50, %51, %52, %53, %54, %55, %56, %57, %58, %59, %60, %61, %62, %63, %64, %65, %66, %67, %68, %69, %70, %71, %72, %73, %74, %75, %76, %77, %78, %79, %80, %81, %82, %83, %84, %85, %86, %87, %88, %89, %90, %91, %92, %93, %94, %95, %96, %97, %98, %99, %100, %101, %102, %103, %104, %105, %106, %107, %108, %109, %110, %111, %112, %113, %114, %115, %116, %117, %118, %119, %120, %121, %122, %123, %124, %125, %126, %127}, "
    "a, b, 1, 1, 1, 0, 1;\n"
    "add.u32 t, %128, 4;\nadd.u32 u, %129, 256;\nmov.b64 a, {t, h};\nmov.b64 b, {u, h};\n"
    "wgmma.mma_async.sync.aligned.m64n256k16.f32.bf16.bf16 "
    "{%0, %1, %2, %3, %4, %5, %6, %7, %8, %9, %10, %11, %12, %13, %14, %15, %16, %17, %18, %19, %20, %21, %22, %23, %24, %25, %26, %27, %28, %29, %30, %31, %32, %33, %34, %35, %36, %37, %38, %39, %40, %41, %42, %43, %44, %45, %46, %47, %48, %49, %50, %51, %52, %53, %54, %55, %56, %57, %58, %59, %60, %61, %62, %63, %64, %65, %66, %67, %68, %69, %70, %71, %72, %73, %74, %75, %76, %77, %78, %79, %80, %81, %82, %83, %84, %85, %86, %87, %88, %89, %90, %91, %92, %93, %94, %95, %96, %97, %98, %99, %100, %101, %102, %103, %104, %105, %106, %107, %108, %109, %110, %111, %112, %113, %114, %115, %116, %117, %118, %119, %120, %121, %122, %123, %124, %125, %126, %127}, "
    "a, b, 1, 1, 1, 0, 1;\n"
    "add.u32 t, %128, 6;\nadd.u32 u, %129, 384;\nmov.b64 a, {t, h};\nmov.b64 b, {u, h};\n"
    "wgmma.mma_async.sync.aligned.m64n256k16.f32.bf16.bf16 "
    "{%0, %1, %2, %3, %4, %5, %6, %7, %8, %9, %10, %11, %12, %13, %14, %15, %16, %17, %18, %19, %20, %21, %22, %23, %24, %25, %26, %27, %28, %29, %30, %31, %32, %33, %34, %35, %36, %37, %38, %39, %40, %41, %42, %43, %44, %45, %46, %47, %48, %49, %50, %51, %52, %53, %54, %55, %56, %57, %58, %59, %60, %61, %62, %63, %64, %65, %66, %67, %68, %69, %70, %71, %72, %73, %74, %75, %76, %77, %78, %79, %80, %81, %82, %83, %84, %85, %86, %87, %88, %89, %90, %91, %92, %93, %94, %95, %96, %97, %98, %99, %100, %101, %102, %103, %104, %105, %106, %107, %108, %109, %110, %111, %112, %113, %114, %115, %116, %117, %118, %119, %120, %121, %122, %123, %124, %125, %126, %127}, "
    "a, b, 1, 1, 1, 0, 1;\n"
    "wgmma.commit_group.sync.aligned;\n}"
    : "=f"(d[0]), "=f"(d[1]), "=f"(d[2]), "=f"(d[3]), "=f"(d[4]), "=f"(d[5]), "=f"(d[6]), "=f"(d[7]), "=f"(d[8]), "=f"(d[9]), "=f"(d[10]), "=f"(d[11]), "=f"(d[12]), "=f"(d[13]), "=f"(d[14]), "=f"(d[15]), "=f"(d[16]), "=f"(d[17]), "=f"(d[18]), "=f"(d[19]), "=f"(d[20]), "=f"(d[21]), "=f"(d[22]), "=f"(d[23]), "=f"(d[24]), "=f"(d[25]), "=f"(d[26]), "=f"(d[27]), "=f"(d[28]), "=f"(d[29]), "=f"(d[30]), "=f"(d[31]), "=f"(d[32]), "=f"(d[33]), "=f"(d[34]), "=f"(d[35]), "=f"(d[36]), "=f"(d[37]), "=f"(d[38]), "=f"(d[39]), "=f"(d[40]), "=f"(d[41]), "=f"(d[42]), "=f"(d[43]), "=f"(d[44]), "=f"(d[45]), "=f"(d[46]), "=f"(d[47]), "=f"(d[48]), "=f"(d[49]), "=f"(d[50]), "=f"(d[51]), "=f"(d[52]), "=f"(d[53]), "=f"(d[54]), "=f"(d[55]), "=f"(d[56]), "=f"(d[57]), "=f"(d[58]), "=f"(d[59]), "=f"(d[60]), "=f"(d[61]), "=f"(d[62]), "=f"(d[63]), "=f"(d[64]), "=f"(d[65]), "=f"(d[66]), "=f"(d[67]), "=f"(d[68]), "=f"(d[69]), "=f"(d[70]), "=f"(d[71]), "=f"(d[72]), "=f"(d[73]), "=f"(d[74]), "=f"(d[75]), "=f"(d[76]), "=f"(d[77]), "=f"(d[78]), "=f"(d[79]), "=f"(d[80]), "=f"(d[81]), "=f"(d[82]), "=f"(d[83]), "=f"(d[84]), "=f"(d[85]), "=f"(d[86]), "=f"(d[87]), "=f"(d[88]), "=f"(d[89]), "=f"(d[90]), "=f"(d[91]), "=f"(d[92]), "=f"(d[93]), "=f"(d[94]), "=f"(d[95]), "=f"(d[96]), "=f"(d[97]), "=f"(d[98]), "=f"(d[99]), "=f"(d[100]), "=f"(d[101]), "=f"(d[102]), "=f"(d[103]), "=f"(d[104]), "=f"(d[105]), "=f"(d[106]), "=f"(d[107]), "=f"(d[108]), "=f"(d[109]), "=f"(d[110]), "=f"(d[111]), "=f"(d[112]), "=f"(d[113]), "=f"(d[114]), "=f"(d[115]), "=f"(d[116]), "=f"(d[117]), "=f"(d[118]), "=f"(d[119]), "=f"(d[120]), "=f"(d[121]), "=f"(d[122]), "=f"(d[123]), "=f"(d[124]), "=f"(d[125]), "=f"(d[126]), "=f"(d[127])
    : "r"(da), "r"(db) : "memory");
}
template <int S> __device__ __forceinline__ void wgmma_acc256(float (&d)[S], uint32_t da, uint32_t db) {
  asm volatile("{\n.reg .b64 a, b;\n.reg .b32 t, u, h;\n.reg .pred p, q;\nmov.b32 h, 0x40000040;\nwgmma.fence.sync.aligned;\n"
    "add.u32 t, %128, 0;\nadd.u32 u, %129, 0;\nmov.b64 a, {t, h};\nmov.b64 b, {u, h};\n"
    "wgmma.mma_async.sync.aligned.m64n256k16.f32.bf16.bf16 "
    "{%0, %1, %2, %3, %4, %5, %6, %7, %8, %9, %10, %11, %12, %13, %14, %15, %16, %17, %18, %19, %20, %21, %22, %23, %24, %25, %26, %27, %28, %29, %30, %31, %32, %33, %34, %35, %36, %37, %38, %39, %40, %41, %42, %43, %44, %45, %46, %47, %48, %49, %50, %51, %52, %53, %54, %55, %56, %57, %58, %59, %60, %61, %62, %63, %64, %65, %66, %67, %68, %69, %70, %71, %72, %73, %74, %75, %76, %77, %78, %79, %80, %81, %82, %83, %84, %85, %86, %87, %88, %89, %90, %91, %92, %93, %94, %95, %96, %97, %98, %99, %100, %101, %102, %103, %104, %105, %106, %107, %108, %109, %110, %111, %112, %113, %114, %115, %116, %117, %118, %119, %120, %121, %122, %123, %124, %125, %126, %127}, "
    "a, b, 1, 1, 1, 0, 1;\n"
    "add.u32 t, %128, 2;\nadd.u32 u, %129, 128;\nmov.b64 a, {t, h};\nmov.b64 b, {u, h};\n"
    "wgmma.mma_async.sync.aligned.m64n256k16.f32.bf16.bf16 "
    "{%0, %1, %2, %3, %4, %5, %6, %7, %8, %9, %10, %11, %12, %13, %14, %15, %16, %17, %18, %19, %20, %21, %22, %23, %24, %25, %26, %27, %28, %29, %30, %31, %32, %33, %34, %35, %36, %37, %38, %39, %40, %41, %42, %43, %44, %45, %46, %47, %48, %49, %50, %51, %52, %53, %54, %55, %56, %57, %58, %59, %60, %61, %62, %63, %64, %65, %66, %67, %68, %69, %70, %71, %72, %73, %74, %75, %76, %77, %78, %79, %80, %81, %82, %83, %84, %85, %86, %87, %88, %89, %90, %91, %92, %93, %94, %95, %96, %97, %98, %99, %100, %101, %102, %103, %104, %105, %106, %107, %108, %109, %110, %111, %112, %113, %114, %115, %116, %117, %118, %119, %120, %121, %122, %123, %124, %125, %126, %127}, "
    "a, b, 1, 1, 1, 0, 1;\n"
    "add.u32 t, %128, 4;\nadd.u32 u, %129, 256;\nmov.b64 a, {t, h};\nmov.b64 b, {u, h};\n"
    "wgmma.mma_async.sync.aligned.m64n256k16.f32.bf16.bf16 "
    "{%0, %1, %2, %3, %4, %5, %6, %7, %8, %9, %10, %11, %12, %13, %14, %15, %16, %17, %18, %19, %20, %21, %22, %23, %24, %25, %26, %27, %28, %29, %30, %31, %32, %33, %34, %35, %36, %37, %38, %39, %40, %41, %42, %43, %44, %45, %46, %47, %48, %49, %50, %51, %52, %53, %54, %55, %56, %57, %58, %59, %60, %61, %62, %63, %64, %65, %66, %67, %68, %69, %70, %71, %72, %73, %74, %75, %76, %77, %78, %79, %80, %81, %82, %83, %84, %85, %86, %87, %88, %89, %90, %91, %92, %93, %94, %95, %96, %97, %98, %99, %100, %101, %102, %103, %104, %105, %106, %107, %108, %109, %110, %111, %112, %113, %114, %115, %116, %117, %118, %119, %120, %121, %122, %123, %124, %125, %126, %127}, "
    "a, b, 1, 1, 1, 0, 1;\n"
    "add.u32 t, %128, 6;\nadd.u32 u, %129, 384;\nmov.b64 a, {t, h};\nmov.b64 b, {u, h};\n"
    "wgmma.mma_async.sync.aligned.m64n256k16.f32.bf16.bf16 "
    "{%0, %1, %2, %3, %4, %5, %6, %7, %8, %9, %10, %11, %12, %13, %14, %15, %16, %17, %18, %19, %20, %21, %22, %23, %24, %25, %26, %27, %28, %29, %30, %31, %32, %33, %34, %35, %36, %37, %38, %39, %40, %41, %42, %43, %44, %45, %46, %47, %48, %49, %50, %51, %52, %53, %54, %55, %56, %57, %58, %59, %60, %61, %62, %63, %64, %65, %66, %67, %68, %69, %70, %71, %72, %73, %74, %75, %76, %77, %78, %79, %80, %81, %82, %83, %84, %85, %86, %87, %88, %89, %90, %91, %92, %93, %94, %95, %96, %97, %98, %99, %100, %101, %102, %103, %104, %105, %106, %107, %108, %109, %110, %111, %112, %113, %114, %115, %116, %117, %118, %119, %120, %121, %122, %123, %124, %125, %126, %127}, "
    "a, b, 1, 1, 1, 0, 1;\n"
    "wgmma.commit_group.sync.aligned;\n}"
    : "+f"(d[0]), "+f"(d[1]), "+f"(d[2]), "+f"(d[3]), "+f"(d[4]), "+f"(d[5]), "+f"(d[6]), "+f"(d[7]), "+f"(d[8]), "+f"(d[9]), "+f"(d[10]), "+f"(d[11]), "+f"(d[12]), "+f"(d[13]), "+f"(d[14]), "+f"(d[15]), "+f"(d[16]), "+f"(d[17]), "+f"(d[18]), "+f"(d[19]), "+f"(d[20]), "+f"(d[21]), "+f"(d[22]), "+f"(d[23]), "+f"(d[24]), "+f"(d[25]), "+f"(d[26]), "+f"(d[27]), "+f"(d[28]), "+f"(d[29]), "+f"(d[30]), "+f"(d[31]), "+f"(d[32]), "+f"(d[33]), "+f"(d[34]), "+f"(d[35]), "+f"(d[36]), "+f"(d[37]), "+f"(d[38]), "+f"(d[39]), "+f"(d[40]), "+f"(d[41]), "+f"(d[42]), "+f"(d[43]), "+f"(d[44]), "+f"(d[45]), "+f"(d[46]), "+f"(d[47]), "+f"(d[48]), "+f"(d[49]), "+f"(d[50]), "+f"(d[51]), "+f"(d[52]), "+f"(d[53]), "+f"(d[54]), "+f"(d[55]), "+f"(d[56]), "+f"(d[57]), "+f"(d[58]), "+f"(d[59]), "+f"(d[60]), "+f"(d[61]), "+f"(d[62]), "+f"(d[63]), "+f"(d[64]), "+f"(d[65]), "+f"(d[66]), "+f"(d[67]), "+f"(d[68]), "+f"(d[69]), "+f"(d[70]), "+f"(d[71]), "+f"(d[72]), "+f"(d[73]), "+f"(d[74]), "+f"(d[75]), "+f"(d[76]), "+f"(d[77]), "+f"(d[78]), "+f"(d[79]), "+f"(d[80]), "+f"(d[81]), "+f"(d[82]), "+f"(d[83]), "+f"(d[84]), "+f"(d[85]), "+f"(d[86]), "+f"(d[87]), "+f"(d[88]), "+f"(d[89]), "+f"(d[90]), "+f"(d[91]), "+f"(d[92]), "+f"(d[93]), "+f"(d[94]), "+f"(d[95]), "+f"(d[96]), "+f"(d[97]), "+f"(d[98]), "+f"(d[99]), "+f"(d[100]), "+f"(d[101]), "+f"(d[102]), "+f"(d[103]), "+f"(d[104]), "+f"(d[105]), "+f"(d[106]), "+f"(d[107]), "+f"(d[108]), "+f"(d[109]), "+f"(d[110]), "+f"(d[111]), "+f"(d[112]), "+f"(d[113]), "+f"(d[114]), "+f"(d[115]), "+f"(d[116]), "+f"(d[117]), "+f"(d[118]), "+f"(d[119]), "+f"(d[120]), "+f"(d[121]), "+f"(d[122]), "+f"(d[123]), "+f"(d[124]), "+f"(d[125]), "+f"(d[126]), "+f"(d[127])
    : "r"(da), "r"(db) : "memory");
}
template <int S> __device__ __forceinline__ void wgmma_aug192(float (&d)[S], uint32_t a0, uint32_t a1, uint32_t db) {
  asm volatile("{\n.reg .b64 b;\n.reg .b32 h, z;\nmov.b32 h, 0x40000000;\nmov.b32 z, 0;\n"
    "mov.b64 b, {%98, h};\nwgmma.fence.sync.aligned;\n"
    "wgmma.mma_async.sync.aligned.m64n192k16.f32.bf16.bf16 "
    "{%0, %1, %2, %3, %4, %5, %6, %7, %8, %9, %10, %11, %12, %13, %14, %15, %16, %17, %18, %19, %20, %21, %22, %23, %24, %25, %26, %27, %28, %29, %30, %31, %32, %33, %34, %35, %36, %37, %38, %39, %40, %41, %42, %43, %44, %45, %46, %47, %48, %49, %50, %51, %52, %53, %54, %55, %56, %57, %58, %59, %60, %61, %62, %63, %64, %65, %66, %67, %68, %69, %70, %71, %72, %73, %74, %75, %76, %77, %78, %79, %80, %81, %82, %83, %84, %85, %86, %87, %88, %89, %90, %91, %92, %93, %94, %95}, "
    "{%96, %97, z, z}, b, 1, 1, 1, 1;\n"
    "wgmma.commit_group.sync.aligned;\n}"
    : "+f"(d[0]), "+f"(d[1]), "+f"(d[2]), "+f"(d[3]), "+f"(d[4]), "+f"(d[5]), "+f"(d[6]), "+f"(d[7]), "+f"(d[8]), "+f"(d[9]), "+f"(d[10]), "+f"(d[11]), "+f"(d[12]), "+f"(d[13]), "+f"(d[14]), "+f"(d[15]), "+f"(d[16]), "+f"(d[17]), "+f"(d[18]), "+f"(d[19]), "+f"(d[20]), "+f"(d[21]), "+f"(d[22]), "+f"(d[23]), "+f"(d[24]), "+f"(d[25]), "+f"(d[26]), "+f"(d[27]), "+f"(d[28]), "+f"(d[29]), "+f"(d[30]), "+f"(d[31]), "+f"(d[32]), "+f"(d[33]), "+f"(d[34]), "+f"(d[35]), "+f"(d[36]), "+f"(d[37]), "+f"(d[38]), "+f"(d[39]), "+f"(d[40]), "+f"(d[41]), "+f"(d[42]), "+f"(d[43]), "+f"(d[44]), "+f"(d[45]), "+f"(d[46]), "+f"(d[47]), "+f"(d[48]), "+f"(d[49]), "+f"(d[50]), "+f"(d[51]), "+f"(d[52]), "+f"(d[53]), "+f"(d[54]), "+f"(d[55]), "+f"(d[56]), "+f"(d[57]), "+f"(d[58]), "+f"(d[59]), "+f"(d[60]), "+f"(d[61]), "+f"(d[62]), "+f"(d[63]), "+f"(d[64]), "+f"(d[65]), "+f"(d[66]), "+f"(d[67]), "+f"(d[68]), "+f"(d[69]), "+f"(d[70]), "+f"(d[71]), "+f"(d[72]), "+f"(d[73]), "+f"(d[74]), "+f"(d[75]), "+f"(d[76]), "+f"(d[77]), "+f"(d[78]), "+f"(d[79]), "+f"(d[80]), "+f"(d[81]), "+f"(d[82]), "+f"(d[83]), "+f"(d[84]), "+f"(d[85]), "+f"(d[86]), "+f"(d[87]), "+f"(d[88]), "+f"(d[89]), "+f"(d[90]), "+f"(d[91]), "+f"(d[92]), "+f"(d[93]), "+f"(d[94]), "+f"(d[95])
    : "r"(a0), "r"(a1), "r"(db) : "memory");
}
template <int S> __device__ __forceinline__ void wgmma_aug256(float (&d)[S], uint32_t a0, uint32_t a1, uint32_t db) {
  asm volatile("{\n.reg .b64 b;\n.reg .b32 h, z;\nmov.b32 h, 0x40000000;\nmov.b32 z, 0;\n"
    "mov.b64 b, {%130, h};\nwgmma.fence.sync.aligned;\n"
    "wgmma.mma_async.sync.aligned.m64n256k16.f32.bf16.bf16 "
    "{%0, %1, %2, %3, %4, %5, %6, %7, %8, %9, %10, %11, %12, %13, %14, %15, %16, %17, %18, %19, %20, %21, %22, %23, %24, %25, %26, %27, %28, %29, %30, %31, %32, %33, %34, %35, %36, %37, %38, %39, %40, %41, %42, %43, %44, %45, %46, %47, %48, %49, %50, %51, %52, %53, %54, %55, %56, %57, %58, %59, %60, %61, %62, %63, %64, %65, %66, %67, %68, %69, %70, %71, %72, %73, %74, %75, %76, %77, %78, %79, %80, %81, %82, %83, %84, %85, %86, %87, %88, %89, %90, %91, %92, %93, %94, %95, %96, %97, %98, %99, %100, %101, %102, %103, %104, %105, %106, %107, %108, %109, %110, %111, %112, %113, %114, %115, %116, %117, %118, %119, %120, %121, %122, %123, %124, %125, %126, %127}, "
    "{%128, %129, z, z}, b, 1, 1, 1, 1;\n"
    "wgmma.commit_group.sync.aligned;\n}"
    : "+f"(d[0]), "+f"(d[1]), "+f"(d[2]), "+f"(d[3]), "+f"(d[4]), "+f"(d[5]), "+f"(d[6]), "+f"(d[7]), "+f"(d[8]), "+f"(d[9]), "+f"(d[10]), "+f"(d[11]), "+f"(d[12]), "+f"(d[13]), "+f"(d[14]), "+f"(d[15]), "+f"(d[16]), "+f"(d[17]), "+f"(d[18]), "+f"(d[19]), "+f"(d[20]), "+f"(d[21]), "+f"(d[22]), "+f"(d[23]), "+f"(d[24]), "+f"(d[25]), "+f"(d[26]), "+f"(d[27]), "+f"(d[28]), "+f"(d[29]), "+f"(d[30]), "+f"(d[31]), "+f"(d[32]), "+f"(d[33]), "+f"(d[34]), "+f"(d[35]), "+f"(d[36]), "+f"(d[37]), "+f"(d[38]), "+f"(d[39]), "+f"(d[40]), "+f"(d[41]), "+f"(d[42]), "+f"(d[43]), "+f"(d[44]), "+f"(d[45]), "+f"(d[46]), "+f"(d[47]), "+f"(d[48]), "+f"(d[49]), "+f"(d[50]), "+f"(d[51]), "+f"(d[52]), "+f"(d[53]), "+f"(d[54]), "+f"(d[55]), "+f"(d[56]), "+f"(d[57]), "+f"(d[58]), "+f"(d[59]), "+f"(d[60]), "+f"(d[61]), "+f"(d[62]), "+f"(d[63]), "+f"(d[64]), "+f"(d[65]), "+f"(d[66]), "+f"(d[67]), "+f"(d[68]), "+f"(d[69]), "+f"(d[70]), "+f"(d[71]), "+f"(d[72]), "+f"(d[73]), "+f"(d[74]), "+f"(d[75]), "+f"(d[76]), "+f"(d[77]), "+f"(d[78]), "+f"(d[79]), "+f"(d[80]), "+f"(d[81]), "+f"(d[82]), "+f"(d[83]), "+f"(d[84]), "+f"(d[85]), "+f"(d[86]), "+f"(d[87]), "+f"(d[88]), "+f"(d[89]), "+f"(d[90]), "+f"(d[91]), "+f"(d[92]), "+f"(d[93]), "+f"(d[94]), "+f"(d[95]), "+f"(d[96]), "+f"(d[97]), "+f"(d[98]), "+f"(d[99]), "+f"(d[100]), "+f"(d[101]), "+f"(d[102]), "+f"(d[103]), "+f"(d[104]), "+f"(d[105]), "+f"(d[106]), "+f"(d[107]), "+f"(d[108]), "+f"(d[109]), "+f"(d[110]), "+f"(d[111]), "+f"(d[112]), "+f"(d[113]), "+f"(d[114]), "+f"(d[115]), "+f"(d[116]), "+f"(d[117]), "+f"(d[118]), "+f"(d[119]), "+f"(d[120]), "+f"(d[121]), "+f"(d[122]), "+f"(d[123]), "+f"(d[124]), "+f"(d[125]), "+f"(d[126]), "+f"(d[127])
    : "r"(a0), "r"(a1), "r"(db) : "memory");
}

__device__ __forceinline__ uint32_t clock32() { uint32_t c; asm volatile("mov.u32 %0, %%clock;" : "=r"(c)); return c; }
__device__ __forceinline__ void spin_until(uint32_t c) {
  asm volatile("{\n.reg .pred p;\n.reg .s32 t;\nLAB_WAIT:\nmov.u32 t, %%clock;\nsub.s32 t, t, %0;\nsetp.lt.s32 p, t, 0;\n@p bra.uni LAB_WAIT;\n}" ::"r"(c) : "memory");
}
struct Nop { __device__ __forceinline__ void operator()(int) const {} };
template <int V> struct IC { static constexpr int v = V; };
struct Pipe {
  uint32_t p, g8, a8, aph, tph, aend, curB, curA, prevB, prevA, bo, so, sph;
  int w; bool l0;
  __device__ __forceinline__ void adv_a() { a8 += 8; if (a8 == aend) { a8 -= NA * 8; aph ^= 1; } }
  __device__ __forceinline__ uint32_t take() { const uint32_t a = SB + OFF_A + a8 * 1024; adv_a(); return a; }
  __device__ __forceinline__ uint32_t ahead(int d) const { uint32_t ls = a8 + d * 8; if (ls >= aend) ls -= NA * 8; return SB + OFF_A + ls * 1024; }
  __device__ __forceinline__ uint32_t wait_ahead(int d) {
    uint32_t ls = a8 + d * 8, lp = aph;
    if (ls >= aend) { ls -= NA * 8; lp ^= 1; }
    mbar_spin(SB + BAR_FULLA + ls, lp);
    return SB + OFF_A + ls * 1024;
  }
  template <int N, bool FIRST, int S> __device__ __forceinline__ uint2 iss(float (&acc)[S], bool skip) {
    if (p + N / 64 > 16) p = 0;
    const uint32_t da = (((SB + OFF_A) >> 4) | (1u << 16)) + a8 * 64;
    const uint32_t db = (((SB + OFF_B) >> 4) | (512u << 16)) + p * 512;
    prevB = curB; prevA = curA;
    curB = g8 & 56; curA = a8;
    p += N / 64; g8 += 8;
    a8 += skip ? 16 : 8;
    if (a8 >= aend) { a8 -= NA * 8; aph ^= 1; }
    uint2 ok = make_uint2(0, 0);
    if constexpr (N == 128) {
      if (FIRST) wgmma_first128(acc, da, db);
      else ok = wgmma_probe128(acc, da, db, SB + BAR_FULLB + (g8 & 56), (g8 >> 6) & 1, SB + BAR_FULLA + a8, aph);
    }
    if constexpr (N == 192) {
      if (FIRST) wgmma_first192(acc, da, db);
      else ok = wgmma_probe192(acc, da, db, SB + BAR_FULLB + (g8 & 56), (g8 >> 6) & 1, SB + BAR_FULLA + a8, aph);
    }
    if constexpr (N == 256) { if (FIRST) wgmma_first256(acc, da, db); else wgmma_acc256(acc, da, db); }
    return ok;
  }
  __device__ __forceinline__ void ensure(uint2 ok) {
    asm volatile(
        "{\n.reg .pred p, q;\nsetp.ne.u32 p, %4, 0;\nsetp.ne.u32 q, %5, 0;\n@!p bra.uni LAB_WAIT;\n@q bra.uni DONE;\n"
        "LAB_WAIT:\nmbarrier.try_wait.parity.shared::cta.b64 p, [%0], %1;\nmbarrier.try_wait.parity.shared::cta.b64 q, [%2], %3;\n"
        "and.pred p, p, q;\n@!p bra.uni LAB_WAIT;\nDONE:\n}" ::"r"(SB + BAR_FULLB + (g8 & 56)), "r"((g8 >> 6) & 1), "r"(SB + BAR_FULLA + a8), "r"(aph), "r"(ok.x), "r"(ok.y) : "memory");
  }
  template <class Hook> __device__ __forceinline__ void validate(bool check, const CUtensorMap* tm16, int c0, int c1, int wp, int j, Hook hook) {
    const uint32_t rows = SB + OFF_A + a8 * 1024 + wp * 2048, ad = a8 * 1024 + so;
    uint32_t v0 = lds32(ad), v1 = lds32(ad + 1024);
    hook();
    while (__any_sync(~0u, check && max(v0, v1) == 0xffffffffu)) {
      const uint32_t bar = SB + BAR_SPEC + (w * 4 + wp) * 8;
      e_load<2048>(rows, tm16, c0 + sched_k(c_sched.v[j][g8 >> 3]), c1 + wp * 16, bar);
      mbar_spin(bar, sph);
      sph ^= 1;
      v0 = lds32(ad); v1 = lds32(ad + 1024);
    }
  }
  __device__ __forceinline__ void drain() {
    wg_wait<0>();
    arrive_n(SB + BAR_EMPTYB + curB, l0); arrive_n(SB + BAR_EMPTYA + curA, l0);
    curB = BAR_DUMMY - BAR_EMPTYB; curA = BAR_DUMMY - BAR_EMPTYA;
  }
  __device__ __forceinline__ void signal_server(uint32_t odd) { __syncwarp(); arrive_n(SB + BAR_SRV + w * 16 + odd * 8, l0); }
  __device__ __forceinline__ void signal_loader() { __syncwarp(); arrive_n(SB + BAR_STG + w * 8, l0); }
  template <int N, bool HOLD = false, int S> __device__ __forceinline__ void begin(float (&acc)[S], uint32_t p0, int proft) {
    p = p0;
    const uint32_t c1 = HOLD ? clock32() : 0;
    ensure(make_uint2(0, 0));
    if (HOLD) spin_until(c1 + lds32(SB + OFF_HOLD + w * 4));
    PROF_T(w, proft, 0);
    ensure(iss<N, true>(acc, false));
  }
  template <int N, bool ENSURE = true, int S, class Hook, class Mid = Nop> __device__ __forceinline__ void run(float (&acc)[S], int i0, int i1, uint32_t skips, int pause, Hook hook, int imid = -1, Mid mid = Mid()) {
    int i = i0, ev = imid >= 0 ? imid : (w ? pause : -1);
#pragma unroll 1
    while (true) {
      const uint2 ok = iss<N, false>(acc, (skips >> i) & 1);
      wg_wait<1>();
      arrive_n(SB + BAR_EMPTYB + prevB, l0); arrive_n(SB + BAR_EMPTYA + prevA, l0);
      if (pause >= 0 && i + 1 == i1) break;
      if constexpr (ENSURE) { ensure(ok); hook(i); } else hook(i, ok);
      i++;
      if (pause < 0 && i == i1) break;
      if (i == ev) {
        const bool ps = w && i == pause;
        if (ps) drain();
        if (i == imid) mid(i);
        if (ps) mbar_spin(SB + BAR_LEAD, tph);
        ev = pause;
      }
    }
  }
  template <int N, bool AUG, int S> __device__ __forceinline__ void end(float (&acc)[S], int ns, uint32_t pa, uint32_t au0, uint32_t au1, int proft) {
    uint32_t augB = 0;
    if constexpr (AUG) {
      mbar_spin(SB + BAR_FULLB + (g8 & 56), (g8 >> 6) & 1);
      const uint32_t db = (((SB + OFF_B) >> 4) | (64u << 16)) + pa * 512;
      if constexpr (N == 192) wgmma_aug192(acc, au0, au1, db); else wgmma_aug256(acc, au0, au1, db);
      augB = g8 & 56; g8 += 8;
    }
    arrive_n(SB + BAR_LEAD, w == 0 && l0);
    tph ^= 1;
    if (ns > 0) wait_ahead(ns - 1);
    wg_wait<0>();
    arrive_n(SB + BAR_EMPTYB + curB, l0); arrive_n(SB + BAR_EMPTYA + curA, l0);
    if (AUG) arrive_n(SB + BAR_EMPTYB + augB, l0);
    PROF_T(w, proft, 1);
  }
};

__device__ __forceinline__ uint32_t box_addr(uint32_t buf, uint32_t bo, int u) { return (buf + bo) ^ (u * 32); }

__device__ __forceinline__ float bf_round(float x) { return __bfloat162float(__float2bfloat16_rn(x)); }
__device__ __forceinline__ void own_rstd(int w, int wp, float (&rstd)[2]) {
#pragma unroll
  for (int hh = 0; hh < 2; hh++) rstd[hh] = __uint_as_float(lds32(SB + OFF_RSTD + (w * 72 + 8 + wp * 16 + ((threadIdx.x & 31) >> 2) + hh * 8) * 4));
}
__device__ __forceinline__ void stats_fetch(int w, int wp, uint32_t (&au)[2]) {
  const int g = (threadIdx.x & 31) >> 2, q4 = threadIdx.x & 3;
  float rstd[2];
  own_rstd(w, wp, rstd);
#pragma unroll
  for (int hh = 0; hh < 2; hh++) {
    const float m = __uint_as_float(lds32(SB + OFF_MEAN + (w * 64 + wp * 16 + g + hh * 8) * 4));
    const float v = q4 == 3 ? rcp(rstd[hh]) : -m;
    const float v1 = bf_round(v), v2 = bf_round(v - v1);
    const float p = q4 == 1 ? v2 : (q4 == 2 ? v - v1 - v2 : v1);
    au[hh] = pack_bf16(p, q4 == 3 ? v2 : p);
  }
}

__device__ __forceinline__ void halo_fetch(uint32_t slot, int w, const uint4* src, uint32_t bar) {
  asm volatile("{\n.reg .pred p;\nelect.sync _|p, 0xffffffff;\n@p mbarrier.arrive.expect_tx.shared::cta.b64 _, [%4], 2080;\n"
               "@p cp.async.bulk.shared::cluster.global.mbarrier::complete_tx::bytes [%0], [%2], 2048, [%4];\n"
               "@p cp.async.bulk.shared::cluster.global.mbarrier::complete_tx::bytes [%1], [%3], 32, [%4];\n}"
               ::"r"(slot), "r"(SB + OFF_RSTD + w * 288), "l"(src), "l"(src + 128), "r"(bar) : "memory");
}
struct Attn {
  uint32_t lo[24], hi[24], ha[16], hslot;
  float c[8][4], rstd[2];
  float2 rk[3];
  __device__ __forceinline__ void A(const float (&acc)[96], Pipe& M, int w, int wp, int r, uint4* halo_out) {
    const int lane = threadIdx.x & 31;
    M.signal_loader();
#pragma unroll
    for (int nb = 8; nb < 24; nb++) hi[nb] = pack_bf16(acc[4 * nb + 2], acc[4 * nb + 3]);
    hslot = M.ahead(3);
    const uint32_t hbuf = hslot + wp * 2048 + lane * 16;
#pragma unroll
    for (int nb = 16; nb < 24; nb++) hi[nb] = movm(hi[nb]);
    if (wp == 3) {
      if (r < 15) {
        const uint32_t rh = lds32(SB + OFF_RSTD + (w * 72 + 64 + (lane & 7)) * 4);
#pragma unroll
        for (int p = 0; p < 4; p++) halo_out[p * 32 + lane] = make_uint4(hi[8 + 4 * p] ? hi[8 + 4 * p] : 0x8000u, hi[9 + 4 * p], hi[10 + 4 * p], hi[11 + 4 * p]);
        if (lane < 8) reinterpret_cast<uint32_t*>(halo_out + 128)[lane] = rh ? rh : 0x80000000u;
      }
    } else {
#pragma unroll
      for (int p = 0; p < 4; p++)
        asm volatile("st.shared.v4.b32 [%0], {%1,%2,%3,%4};" ::"r"(hbuf + 2048 + p * 512), "r"(hi[8 + 4 * p]), "r"(hi[9 + 4 * p]), "r"(hi[10 + 4 * p]), "r"(hi[11 + 4 * p]) : "memory");
      __syncwarp();
      arrive_n(SB + BAR_HALO + w * 8, M.l0);
    }
#pragma unroll
    for (int nb = 23; nb >= 0; nb--) {
      asm volatile("cvt.rn.bf16x2.f32 %0, %1, %2;" : "=r"(lo[nb]) : "f"(acc[4 * nb + 1]), "f"(acc[4 * nb]));
      if (nb < 8) asm volatile("cvt.rn.bf16x2.f32 %0, %1, %2;" : "=r"(hi[nb]) : "f"(acc[4 * nb + 3]), "f"(acc[4 * nb + 2]));
      if (nb >= 16) lo[nb] = movm(lo[nb]);
    }
  }
  __device__ __forceinline__ void B(int w, int wp, uint32_t hph) {
    const int lane = threadIdx.x & 31;
    own_rstd(w, wp, rstd);
    mbar_spin(SB + BAR_HALO + w * 8, hph);
#pragma unroll
    for (int p = 0; p < 4; p++)
      asm volatile("ld.shared.v4.b32 {%0,%1,%2,%3}, [%4];" : "=r"(ha[4 * p]), "=r"(ha[4 * p + 1]), "=r"(ha[4 * p + 2]), "=r"(ha[4 * p + 3]) : "r"(hslot + wp * 2048 + lane * 16 + p * 512) : "memory");
#pragma unroll
    for (int u = 0; u < 3; u++) rk[u] = lds64(SB + OFF_RSTD + (w * 72 + wp * 16 + u * 8 + 2 * (lane & 3)) * 4);
  }
  __device__ __forceinline__ void C(int wp, int r, uint32_t zero) {
    const int lane = threadIdx.x & 31, g = lane >> 2, q = lane & 3;
    const bool nohalo = (wp == 0) && (r == 0);
    const bool up0 = 2 * q > g, up1 = 2 * q + 1 > g;
    const float sc = 0.17677669529663687f * 1.4426950408889634f;
    const float kx0 = up0 ? rk[0].x : rk[1].x, kx1 = up1 ? rk[0].y : rk[1].y;
    const float ky0 = up0 ? rk[1].x : rk[2].x, ky1 = up1 ? rk[1].y : rk[2].y;
    const float fx = rstd[0] * sc, fy = rstd[1] * sc;
    float sm[2][4] = {}, s0[2][4] = {}, s1[2][4] = {};
#pragma unroll
    for (int ks = 0; ks < 2; ks++)
#pragma unroll
      for (int h = 0; h < 2; h++) {
        const int a = 4 * h + 2 * ks;
        mma16(s0[h], lo[a], hi[a], lo[a + 1], hi[a + 1], lo[8 + a], lo[9 + a]);
        mma16(s1[h], lo[a], hi[a], lo[a + 1], hi[a + 1], hi[8 + a], hi[9 + a]);
      }
#pragma unroll
    for (int u = 0; u < 4; u++) { const int a = 4 * (u & 1) + (u & 2); mma16(sm[u & 1], lo[a], hi[a], lo[a + 1], hi[a + 1], ha[a], ha[a + 1]); }
    uint32_t pf[2][4];
    const uint32_t um = (up0 ? 0xffffu : 0u) | (up1 ? 0xffff0000u : 0u);
#pragma unroll
    for (int h = 0; h < 2; h++) {
      if (nohalo) { sm[h][0] = -INFINITY; sm[h][1] = -INFINITY; }
      float x0 = (up0 ? sm[h][0] : s0[h][0]) * (kx0 * fx), x1 = (up1 ? sm[h][1] : s0[h][1]) * (kx1 * fx);
      float y0 = (up0 ? s0[h][2] : s1[h][2]) * (ky0 * fy), y1 = (up1 ? s0[h][3] : s1[h][3]) * (ky1 * fy);
      float mx = fmaxf(x0, x1), my = fmaxf(y0, y1);
      mx = fmaxf(mx, __shfl_xor_sync(~0u, mx, 1)); my = fmaxf(my, __shfl_xor_sync(~0u, my, 1));
      mx = fmaxf(mx, __shfl_xor_sync(~0u, mx, 2)); my = fmaxf(my, __shfl_xor_sync(~0u, my, 2));
      x0 = ex2(x0 - mx); x1 = ex2(x1 - mx); y0 = ex2(y0 - my); y1 = ex2(y1 - my);
      float sx = x0 + x1, sy = y0 + y1;
      x0 *= kx0; x1 *= kx1; y0 *= ky0; y1 *= ky1;
      sx += __shfl_xor_sync(~0u, sx, 1); sy += __shfl_xor_sync(~0u, sy, 1);
      sx += __shfl_xor_sync(~0u, sx, 2); sy += __shfl_xor_sync(~0u, sy, 2);
      sx = rcp(sx); sy = rcp(sy);
      x0 *= sx; x1 *= sx; y0 *= sy; y1 *= sy;
      const uint32_t px = pack_bf16(x0, x1), py = pack_bf16(y0, y1);
      pf[h][0] = px & um; pf[h][1] = px & ~um; pf[h][2] = py & um; pf[h][3] = py & ~um;
    }
#pragma unroll
    for (int u = 0; u < 4; u++) {
#pragma unroll
      for (int e = 0; e < 4; e++) { c[2 * u][e] = 0.f; c[2 * u + 1][e] = 0.f; }
      mma8(c[2 * u], ha[8 + 2 * u], ha[9 + 2 * u], pf[u >> 1][0]);
      mma8(c[2 * u + 1], lo[16 + 2 * u], lo[17 + 2 * u], pf[u >> 1][2]);
    }
#pragma unroll
    for (int u = 0; u < 4; u++) {
      mma8(c[2 * u], lo[16 + 2 * u], lo[17 + 2 * u], pf[u >> 1][1]);
      mma8(c[2 * u + 1], hi[16 + 2 * u], hi[17 + 2 * u], pf[u >> 1][3]);
    }
    uint32_t dep = 0;
#pragma unroll
    for (int u = 0; u < 8; u++) dep |= __float_as_uint(c[u][0]);
    asm volatile("bar.sync %0, 256;" ::"r"(3 + (dep & zero)) : "memory");
  }
  __device__ __forceinline__ void E(Pipe& M, bool urgent) {
#pragma unroll
    for (int u = 0; u < 4; u++)
      asm volatile("stmatrix.sync.aligned.m8n8.x4.trans.shared.b16 [%0], {%1, %2, %3, %4};" ::"r"(box_addr(hslot, M.bo, u)),
                   "r"(pack_bf16(c[2 * u][0], c[2 * u][1])), "r"(pack_bf16(c[2 * u + 1][0], c[2 * u + 1][1])),
                   "r"(pack_bf16(c[2 * u][2], c[2 * u][3])), "r"(pack_bf16(c[2 * u + 1][2], c[2 * u + 1][3])) : "memory");
    if (urgent) M.signal_loader(); else M.signal_server(1);
  }
};

__device__ __forceinline__ void epi_res(const float (&acc)[64], const float (&pre)[64], float sc0, float sc1, uint32_t (&xr)[32], Pipe& M, int wp) {
  Pipe T = M;
  const uint32_t buf0 = T.take(), buf1 = T.take();
#pragma unroll
  for (int u = 0; u < 8; u++) {
#pragma unroll
    for (int nb = 2 * u; nb < 2 * u + 2; nb++) {
      xr[2 * nb] = pack_bf16(fmaf(acc[4 * nb], sc0, pre[2 * nb]), fmaf(acc[4 * nb + 1], sc0, pre[32 + 2 * nb]));
      xr[2 * nb + 1] = pack_bf16(fmaf(acc[4 * nb + 2], sc1, pre[2 * nb + 1]), fmaf(acc[4 * nb + 3], sc1, pre[33 + 2 * nb]));
    }
    stsm4(box_addr(u < 4 ? buf0 : buf1, M.bo, u & 3), xr[4 * u], xr[4 * u + 1], xr[4 * u + 2], xr[4 * u + 3]);
    if (u == 3) M.signal_loader();
  }
  __syncwarp();
  arrive_n(SB + BAR_STG2 + M.w * 8, M.l0);
  fence_async_smem();
  wg_bar(M.w);
}
__device__ __forceinline__ void presum(float (&pre)[64], float usebias) {
  const uint32_t bias = SB + OFF_VEC + (threadIdx.x & 3) * 8;
#pragma unroll
  for (int nb = 0; nb < 16; nb++) {
    const float2 b = lds64(bias + nb * 32);
#pragma unroll
    for (int u = 2 * nb; u < 2 * nb + 2; u++) {
      const uint32_t v = __float_as_uint(pre[u]);
      pre[32 + u] = fmaf(b.y, usebias, bf_hi(v)); pre[u] = fmaf(b.x, usebias, bf_lo(v));
    }
  }
}
template <int S, int Q> __device__ __forceinline__ void pack_relu(uint32_t (&o)[Q], const float (&acc)[S]) {
#pragma unroll
  for (int u = 0; u < Q; u++) asm("cvt.rn.relu.bf16x2.f32 %0, %1, %2;" : "=r"(o[u]) : "f"(acc[2 * u + 1]), "f"(acc[2 * u]));
}
__device__ __forceinline__ uint32_t sq_bf16x2(uint32_t a) { uint32_t d; asm("mul.rn.bf16x2 %0, %1, %1;" : "=r"(d) : "r"(a)); return d; }
template <int Q> __device__ __forceinline__ void ffn_stage(const uint32_t (&o)[Q], int i, Pipe& M) {
  i -= M.w;
  if (i == 1 || i == 4 || i == 7 || (Q == 64 && i == 10)) {
    const uint32_t buf = M.wait_ahead(2 - M.w);
#pragma unroll
    for (int b = 0; b < Q / 16; b++)
      if (i == 3 * b + 1) {
#pragma unroll
        for (int u = 4 * b; u < 4 * b + 4; u++)
          stsm4(box_addr(buf, M.bo, u & 3), sq_bf16x2(o[4 * u]), sq_bf16x2(o[4 * u + 1]), sq_bf16x2(o[4 * u + 2]), sq_bf16x2(o[4 * u + 3]));
      }
    M.signal_server((i & 1) ^ (Q == 64));
  }
}

__device__ __forceinline__ void wait_flags(const uint8_t* f, uint32_t tag, int lane) {
  const uint32_t t4 = (tag & 0xff) * 0x01010101u;
  const uint32_t* fp = reinterpret_cast<const uint32_t*>(f) + (lane & 3);
  while (__any_sync(~0u, __vsub4(ld_relaxed(fp), t4) & 0x80808080u)) {}
  asm volatile("fence.acquire.gpu;\nfence.proxy.async.global;" ::: "memory");
}
__device__ __forceinline__ void aloader(const Params& P, int bid, int r, int j, int lane, int w, uint32_t epoch) {
  uint32_t e = c_sched.v[j][NPRO];
  const uint32_t abase = SB + OFF_A + w * NA * 8192, fbase = SB + BAR_FULLA + w * NA * 8, ebase = SB + BAR_EMPTYA + w * NA * 8;
  uint32_t slot = NPRO, ph = 1, nst = 0, hph = 0, npace = 0;
  int t = -1, kind = -1, a0 = 0, a1 = 0;
  const CUtensorMap* tmA = nullptr;
  uint64_t pol = 0;
  uint4* hin = P.s->halo[0][0] + (r * 16 + j * 2 + w - 16) * 136;
  uint32_t* const pace = P.s->pace[r >> 1];
  const uint8_t* const flags = P.s->flags[r >> 1][w];
  auto adv = [&] { if (++slot == NA) { slot = 0; ph ^= 1; } };
#pragma unroll 1
  for (int g = NPRO; g <= NSTEP; g++) {
    const uint32_t cur = e;
    e = c_sched.v[j][g + 1];
    if (!(cur & E_RARE)) {
      if (cur & E_HAND) { mbar_spin(ebase + slot * 8, ph); e_arrive(fbase + slot * 8, 1); adv(); }
    } else {
      if (cur & F_NEW) {
        t++; kind = kind == 5 ? 0 : kind + 1;
        const bool narrow = kind == 2 || kind == 5;
        static_assert(TM_XIN == 0 && TM_X == 1 && TM_XA == 2 && TM_O == 3 && TM_H == 4, "map order");
        tmA = &P.tm[t < 2 ? 0 : (0x422311 >> (4 * kind)) & 15];
        pol = ((AEF >> t) & 1) ? 0x12F0000000000000ull : 0x1000000000000000ull;
        a0 = narrow ? 0 : w * 1024; a1 = narrow ? r * 128 + w * 64 : r * 64;
      }
      const bool xo = cur & E_XPUB0;
      uint32_t s = slot;
      if (cur & (E_HAND | E_ATTN | E_XPUB0)) {
        if (cur & E_KEEP) e_arrive(ebase + slot * 8, 4);
#pragma unroll 1
        for (int u = xo ? 0 : 1; u < 2; u++) { mbar_wait(ebase + slot * 8, ph); e_arrive(fbase + slot * 8, 1); adv(); }
      }
      uint32_t hold = 0;
      if ((xo && t < 12) || (cur & F_GATH)) {
        uint32_t v;
        do v = ld_relaxed(pace + npace + (lane & 15)); while (__any_sync(~0u, (v ^ (epoch * 16 + t - 1)) & 31));
        npace ^= 16;
        hold = min(__reduce_max_sync(~0u, (int)(v - __shfl_sync(~0u, v, bid & 15))), 4000) * 27 >> 4;
        asm volatile("st.shared.b32 [%0], %1;" ::"r"(SB + OFF_HOLD + w * 4), "r"(hold) : "memory");
      }
      if (cur & (E_ATTN | E_XPUB0)) {
        const uint32_t s2 = s == NA - 1 ? 0 : s + 1;
        constexpr int NP = NPREPX > NPREPO ? NPREPX : NPREPO;
        uint32_t pf[NP + 1], pk[NP + 1];
        const int np = t == 12 ? 0 : (xo ? NPREPX : NPREPO);
#pragma unroll
        for (int u = 0; u < NP; u++) {
          pf[u] = slot; pk[u] = a0 + sched_k(c_sched.v[j][g + 1 + xo + u]);
          if (u < np) {
            if (u == np - 1) mbar_spin(ebase + slot * 8, ph);
            adv();
          }
        }
        mbar_wait(SB + BAR_STG + w * 8, nst & 1);
        nst++;
        LT(0);
        const uint32_t c1 = clock32();
        e_store(tmA, a0 + sched_k(cur), a1, abase + s * 8192);
        if (xo) {
          mbar_spin(SB + BAR_STG2 + w * 8, ~t & 1);
          e_store(tmA, a0 + sched_k(cur) + 64, a1, abase + s2 * 8192);
        } else e_arrive(SB + BAR_OWN + w * 8, 1);
        LT(1);
        if (t == 12) break;
        spin_until(c1 + hold + (xo ? SDELAY : SDELAYO));
        LT(2);
#pragma unroll
        for (int u = 0; u < NP; u++)
          if (u < np) e_load(abase + pf[u] * 8192, tmA, pk[u], a1, fbase + pf[u] * 8);
        LT(5);
      }
      if (cur & E_SIG) {
        e_arrive(SB + BAR_SRV + w * 16, 4);
      }
      if (cur & E_REL) bulk_wait_all();
      if (cur & E_HALO) {
        mbar_spin(SB + BAR_STG + w * 8, nst & 1);
        nst++;
        const uint32_t hs = abase + (slot >= 3 ? slot - 3 : slot + 3) * 8192, ad = hs + lane * 32 + (lane & 4) * 4;
        if (r == 0) {
#pragma unroll
          for (int p = 0; p < 4; p++) sts128(hs + lane * 16 + p * 512, 0, 0, 0, 0);
          asm volatile("st.shared.b32 [%0], %1;" ::"r"(SB + OFF_RSTD + w * 288 + (lane & 7) * 4), "r"(0x3f800000) : "memory");
        } else {
          spin_until(clock32() + HDELAY);
          do {
            halo_fetch(hs, w, hin, SB + BAR_SPEC + 80 + w * 8);
            mbar_spin(SB + BAR_SPEC + 80 + w * 8, hph);
            hph ^= 1;
          } while (__any_sync(~0u, min(min(lds32(ad), lds32(ad + 1024)), lds32(SB + OFF_RSTD + w * 288)) == 0));
        }
        e_arrive(SB + BAR_HALO + w * 8, 1);
      }
      if ((cur & E_REL) && (kind == 1 || kind == 2) && r > 0) {
        uint4* hz = hin + lane;
        hin += 256 * 136;
#pragma unroll
        for (int p = 0; p < 4; p++) hz[p * 32] = make_uint4(0, 0, 0, 0);
        if (lane < 2) hz[128] = make_uint4(0, 0, 0, 0);
      }
      if (cur & E_WAIT) {
        wait_flags(flags + ((cur & E_PART1) ? 16 : 0), epoch * 16 + t, lane);
      }
    }
    if (!(cur & (F_AUG | F_NOA))) {
      mbar_wait(ebase + slot * 8, ph);
      e_load(abase + slot * 8192, tmA, a0 + sched_k(cur), a1, fbase + slot * 8, pol);
      adv();
      if ((cur & F_STAMP) && w == 0) {
        mbar_spin(SB + BAR_EMPTYB + ((g - 6) & 7) * 8, ((g - 6) >> 3) & 1);
        uint32_t stamp;
        asm volatile("mov.u32 %0, %%globaltimer_lo;" : "=r"(stamp));
        asm volatile("st.relaxed.gpu.global.u32 [%0], %1;" ::"l"(pace + npace + (bid & 15)), "r"((stamp & ~31u) | ((epoch * 16 + t) & 31)) : "memory");
      }
    }
  }
  bulk_wait_all();
  if (w == 1 && lane == 0) P.s->epoch[bid] = epoch;
}

__device__ __forceinline__ void bloader(const Params& P, int bid, int j, int lane, uint32_t epoch) {
  uint32_t e = c_sched.v[j][NPRO];
  int kind = -1, c2 = 0, c3 = 0, na = 0;
  const CUtensorMap* tmB = nullptr;
  uint32_t sph = 0, efm = BEF * 2;
  uint64_t pol = 0;
#pragma unroll 1
  for (int g = NPRO; g < NSTEP; g++) {
    const uint32_t cur = e;
    e = c_sched.v[j][g + 1];
    if (cur & F_NEW) {
      kind = kind == 5 ? 0 : kind + 1;
      static_assert(TM_WQKV == 5 && TM_WO == 6 && TM_W1A == 7 && TM_W1B == 8 && TM_W2 == 9, "map order");
      tmB = &P.tm[(0x978655 >> (4 * kind)) & 15];
      efm >>= 1;
      pol = (efm & 1) ? 0x12F0000000000000ull : 0x1000000000000000ull;
      na = (0x243233 >> (4 * kind)) & 15;
      c2 = ((0x277200 >> (4 * kind)) & 15) * j + (kind == 4 ? 3 : 0);
      c3 = kind <= 1 ? kind * 8 + j : 0;
    }
    const int need = g - (int)((cur >> 4) & 15);
    const uint32_t dst = SB + OFF_B + (cur & 15) * 8192, bar = SB + BAR_FULLB + (g & 7) * 8;
    mbar_wait(SB + BAR_EMPTYB + (need & 7) * 8, (need >> 3) & 1);
    if (!(cur & F_AUG)) {
      asm volatile("{\n.reg .pred p;\nelect.sync _|p, 0xffffffff;\n@p mbarrier.arrive.expect_tx.shared::cta.b64 _, [%2], %7;\n"
                   "@p cp.async.bulk.tensor.4d.shared::cluster.global.mbarrier::complete_tx::bytes.L2::cache_hint [%0], [%1, {%3, %4, %5, %6}], [%2], %8;\n}"
                   ::"r"(dst), "l"(tmB), "r"(bar), "r"(0), "r"(sched_k(cur)), "r"(c2), "r"(c3), "r"(na * 8192), "l"(pol) : "memory");
    } else {
      const bool chk = g < NSTEP / 2;
      const uint32_t b2 = chk ? SB + BAR_AUG : bar, ad = dst + lane * 16 + (lane >> 3) * 4;
      while (true) {
        asm volatile("{\n.reg .pred p;\nelect.sync _|p, 0xffffffff;\n@p mbarrier.arrive.expect_tx.shared::cta.b64 _, [%2], 4096;\n"
                     "@p cp.async.bulk.shared::cluster.global.mbarrier::complete_tx::bytes [%0], [%1], 4096, [%2];\n}"
                     ::"r"(dst), "l"(P.s->aug[epoch & 1][(kind - (kind >= 3)) * 8 + j]), "r"(b2) : "memory");
        if (!chk) break;
        mbar_spin(b2, sph);
        sph ^= 1;
        uint32_t mn = ~0u;
#pragma unroll
        for (int u = 0; u < 8; u++) mn = min(mn, lds32(ad + u * 512));
        if (!__any_sync(~0u, mn == 0)) { e_arrive(bar, 1); break; }
      }
      __syncwarp();
    }
  }
}

constexpr uint32_t job_slots(int layer) {
  const int pos[10] = {11, 26, 63, 73, 77, 81, 92, 96, 100, 104};
  uint32_t v = 0;
  for (int m = 0; m < 10; m++) v |= (uint32_t)((layer * 148 + pos[m]) % NA) << (3 * m);
  return v;
}
constexpr uint32_t JOB_SLOTS0 = job_slots(0), JOB_SLOTS1 = job_slots(1);
__device__ __forceinline__ void server(const Params& P, int bid, int r, int j, int lane, uint32_t epoch) {
  epoch += __shfl_sync(~0u, c_sched.v[j][lane < 18 ? lane * 16 : 0] >> 31, 0);
  {
    const uint2 b = reinterpret_cast<const uint2*>(P.b2 + j * 128)[lane];
    sts128(SB + OFF_VEC + lane * 16, b.x << 16, b.x & 0xffff0000u, b.y << 16, b.y & 0xffff0000u);
  }
  int hl = 0;
  uint32_t fph = 0, pend = SB + BAR_DUMMY3;
#pragma unroll 1
  for (int n = 0; n < 20; n++) {
    const int layer = n >= 10, m = n - 10 * layer;
    const bool stat = m == 0 || m == 2;
    const uint32_t slot = ((layer ? JOB_SLOTS1 : JOB_SLOTS0) >> (m * 3)) & 7;
    auto fetch = [&](int w) {
      asm volatile("{\n.reg .pred p;\nelect.sync _|p, 0xffffffff;\n@p mbarrier.arrive.expect_tx.shared::cta.b64 _, [%2], 4096;\n"
                   "@p cp.async.bulk.shared::cluster.global.mbarrier::complete_tx::bytes [%0], [%1], 4096, [%2];\n}"
                   ::"r"(SB + OFF_A + (w * NA + slot) * 8192), "l"(&P.s->stats[hl][r * 32 + w * 16][0][0]), "r"(SB + BAR_SPEC + 64 + w * 8) : "memory");
    };
#pragma unroll 1
    for (int w = 0; w < 2; w++) {
      mbar_spin(SB + BAR_SRV + w * 16 + (n & 1) * 8, (n >> 1) & 1);
      if (stat) fetch(w);
      else {
        e_store(&P.tm[m == 1 ? TM_O : TM_H], m == 1 ? j * 64 : 448 * j + (m - 3) * 64, r * 128 + w * 64, SB + OFF_A + (w * NA + slot) * 8192);
        bulk_wait_read<1>();
        e_arrive(pend, 4);
        pend = SB + BAR_EMPTYA + (w * NA + slot) * 8;
      }
    }
    if (stat) {
#pragma unroll 1
      for (int w = 0; w < 2; w++) {
        const uint32_t src = SB + OFF_A + (w * NA + slot) * 8192 + (lane >> 1) * 256 + ((lane >> 1) & 7) * 32 + (lane & 1) * 16;
        float ms[2], md[2], mq[2], m0[2];
        while (true) {
          mbar_spin(SB + BAR_SPEC + 64 + w * 8, (fph >> w) & 1);
          fph ^= 1u << w;
          uint32_t bad = 0;
          ms[0] = ms[1] = md[0] = md[1] = mq[0] = mq[1] = m0[0] = m0[1] = 0.f;
#pragma unroll 1
          for (int p = 0; p < 8; p += 2) {
            const float4 v2[2] = {lds128(src ^ (p * 32)), lds128(src ^ (p * 32) ^ 32)};
            if (p == 0) { m0[0] = v2[0].x; m0[1] = v2[0].z; }
#pragma unroll
            for (int z = 0; z < 2; z++) {
              const float4 v = v2[z];
              const float a = v.x - m0[0], b = v.z - m0[1];
              bad |= __float_as_uint(v.y) ^ epoch;
              ms[0] += a; md[0] = fmaf(a, a, md[0]); mq[0] += __uint_as_float(__float_as_uint(v.y) & ~63u);
              ms[1] += b; md[1] = fmaf(b, b, md[1]); mq[1] += v.w;
            }
          }
          if (!__any_sync(~0u, bad & 63)) break;
          fetch(w);
          __syncwarp();
        }
        e_arrive(SB + BAR_EMPTYA + (w * NA + slot) * 8, 4);
        const int row = (lane >> 3) * 16 + (lane & 7);
#pragma unroll
        for (int z = 0; z < 2; z++) {
          const float d = ms[z] * 0.125f;
          asm volatile("st.shared.f32 [%0], %1;" ::"r"(SB + OFF_MEAN + (w * 64 + row + z * 8) * 4), "f"(m0[z] + d) : "memory");
          asm volatile("st.shared.f32 [%0], %1;" ::"r"(SB + OFF_RSTD + (w * 72 + 8 + row + z * 8) * 4), "f"(rsq(fmaf(mq[z], 1.f / 1024.f, fmaxf(fmaf(md[z], 0.125f, -d * d), 0.f)) + 1e-5f)) : "memory");
        }
        e_arrive(SB + BAR_STAT + w * 8, 1);
      }
    }
    if (stat && n != 12) {
#pragma unroll 1
      for (int u = 0; u < (m ? 2 : 3); u++) {
        const uint32_t pitch = u == 2 ? 448 : 128;
        uint4* p = reinterpret_cast<uint4*>(u == 2 ? P.s->h : (m ? P.out : P.s->x)) + (u == 2 ? 64 + j * 8 : j * 16 + u * 8) + ((r * 128 + (lane >> 3)) * pitch + (lane & 7));
#pragma unroll 1
        for (int k = 0; k < 32 / FUN; k++) {
#pragma unroll
          for (int z = 0; z < FUN; z++) {
            *p = make_uint4(~0u, ~0u, ~0u, ~0u);
            p += 4 * pitch;
            asm volatile("" : "+l"(p));
          }
        }
      }
      __syncwarp();
    }
    if ((0x222 >> m) & 1) {
      bulk_wait_all();
      e_arrive(pend, 4);
      pend = SB + BAR_DUMMY3;
      if (lane < 2) st_release8(&P.s->flags[r >> 1][lane][(bid & 15) + (m == 9 ? 16 : 0)], epoch * 16 + layer * 6 + (m == 1 ? 2 : 5));
      __syncwarp();
    }
    hl += stat;
  }
}

__device__ __forceinline__ void aux_cta(const Params& P, int bid, int warp, int lane, uint32_t epoch) {
  constexpr uint32_t sb = SB;
  const int g = lane >> 2, q = lane & 3;
  if (warp >= 8) {
    if (warp == 8 && elect_one()) {
      uint32_t s8 = 0, ph = 0;
#pragma unroll 1
      for (int t = 0; t < 4; t++) {
        const uint32_t sz = t == 3 ? 32768 : 24576;
        if (t == 3) { mbar_spin(sb + BAR_EMPTYA + 48, 1); mbar_spin(sb + BAR_EMPTYA + 56, 1); }
#pragma unroll 1
        for (int k = t ? 0 : 8; k < 32; k++) {
          const int jj = 2 * (bid - NMAIN) + (k & 1);
          mbar_spin(sb + BAR_EMPTYA + s8 * 8, ph);
          mbar_expect_tx(sb + BAR_FULLA + s8 * 8, sz);
          tma_ld4(sb + s8 * sz, &P.tm[(0x7855 >> (4 * t)) & 15], (k >> 1) * 64, t < 2 ? 0 : 7 * jj + (t - 2) * 3, t < 2 ? t * 8 + jj : 0, sb + BAR_FULLA + s8 * 8, ((XEF >> t) & 1) ? 0x12F0000000000000ull : 0x1000000000000000ull);
          if (++s8 == (t == 3 ? 6 : 8)) { s8 = 0; ph ^= 1; }
        }
      }
    }
    if (warp == 10 && lane == 0) P.s->epoch[bid] = epoch;
  } else {
    const int jj = 2 * (bid - NMAIN) + (warp >> 2), c0 = (warp & 3) * 2;
    uint32_t s8 = warp >> 2, ph = 0, bf[16][4] = {};
#pragma unroll 1
    for (int t = 0; t < 4; t++) {
      float acc[8][4] = {};
      uint32_t bias[8];
#pragma unroll
      for (int a = 0; a < 8; a++) bias[a] = t >= 2 ? reinterpret_cast<const uint32_t*>(P.b1 + 448 * jj + (t - 2) * 192 + c0 * 8)[(a >> 1) * 32 + (a & 1) * 4 + q] : 0u;
#pragma unroll 1
      for (int i = 0; i < 16; i++) {
        mbar_spin(sb + BAR_FULLA + s8 * 8, ph);
        const uint32_t ad = sb + s8 * (t == 3 ? 32768 : 24576) + lane * 128 + ((c0 ^ (lane & 7)) << 4);
#pragma unroll
        for (int u = 0; u < 16; u++)
          asm volatile("{\n.reg .pred p;\nsetp.ne.u32 p, %5, 0;\n@p ldmatrix.sync.aligned.m8n8.x4.trans.shared.b16 {%0,%1,%2,%3}, [%4];\n}"
                       : "+r"(bf[u][0]), "+r"(bf[u][1]), "+r"(bf[u][2]), "+r"(bf[u][3])
                       : "r"((ad ^ ((u & 1) << 4)) + ((u >> 1) & 3) * 8192 + (u >> 3) * 4096), "r"((u & 6) != 6 || t == 3 ? 1 : 0) : "memory");
        e_arrive(sb + BAR_EMPTYA + s8 * 8, 1);
        s8 += 2;
        if (s8 >= (t == 3 ? 6 : 8)) { s8 &= 1; ph ^= 1; }
#pragma unroll
        for (int u = 0; u < 32; u++) mma16(acc[u & 7], 0x3F803F80u, 0x3F803F80u, 0x3F803F80u, 0x3F803F80u, bf[(u & 7) + (u >> 4) * 8][(u >> 2) & 2], bf[(u & 7) + (u >> 4) * 8][((u >> 2) & 2) + 1]);
      }
      const float k1 = (g & 1) ? 1.f : 0.f;
      const uint32_t o = (t * 8 + jj) * 1024 + g * 32 + ((c0 ^ g) << 2) + q + (epoch & 1) * 32768;
      uint32_t *const p0 = P.s->aug[0][0] + o, *const p1 = P.s->aug[0][0] + (o ^ 4);
#pragma unroll
      for (int a = 0; a < 8; a++) {
        float u = acc[a][0], v = acc[a][1];
        uint32_t h = pack_bf16(u, v);
        u = fmaf(-k1, bf_lo(h), u); v = fmaf(-k1, bf_hi(h), v); h = pack_bf16(u, v);
        if (g >= 6) h = bias[a];
        ((a & 1) ? p1 : p0)[(a >> 1) * 256] = h ? h : 0x8000u;
      }
      uint4* const z = reinterpret_cast<uint4*>(P.s->aug[~epoch & 1][t * 8 + jj]) + (threadIdx.x & 127);
      z[0] = z[128] = make_uint4(0, 0, 0, 0);
    }
  }
}

__global__ void __launch_bounds__(NTHREADS, 1) mega_kernel(const __grid_constant__ Params P) {
  extern __shared__ __align__(1024) uint8_t smem_raw[];
  constexpr uint32_t sb = SB;
  const uint32_t centry = clock32();
  const int warp = __shfl_sync(~0u, threadIdx.x >> 5, 0), lane = threadIdx.x & 31;
  const int bid = work_id();
  const bool aux = bid >= NMAIN;
  const int r = ((bid >> 4) << 1) | (bid & 1), j = (bid >> 1) & 7;
  if (warp == 11)
    asm volatile("st.shared.b32 [%0], %1;" ::"r"(sb + OFF_HOLD + 8), "r"(ld_relaxed(&P.s->epoch[bid]) + 1 + (EARLYC ? c_sched.v[j][NPRO] >> 31 : 0)) : "memory");
  if (elect_one()) {
    const uint64_t lc = warp < 5 ? 0xaffff0000000000ull : (warp < 10 ? 0x2a82aa0aaaaaaull : 0xa0000ull);
    uint32_t bits = (uint32_t)(lc >> ((warp - (warp >= 5) * 5 - (warp >= 10) * 5) * 12));
#pragma unroll 1
    for (int k = 0; k < 6; k++, bits >>= 2) {
      const uint32_t bar = sb + OFF_BAR + (warp * 6 + k) * 8;
      mbar_init(bar, 1 << (bits & 3));
      const int st = aux ? warp * 6 + k : k;
      if (st < (aux ? 8 : NPRO) && warp < 3) {
        const int kc = aux ? (st >> 1) * 64 : (k < D0 ? (k + (k >= j)) * 128 : j * 128 + (k - D0) * 64);
        if (OWNDLY && !aux && k == D0) spin_until(clock32() + OWNDLY);
        if (aux || warp == 2) {
          mbar_expect_tx(bar, 24576);
          tma_ld4(sb + OFF_B + (st + !aux) * 24576, &P.tm[TM_WQKV], kc, 0, aux ? 2 * (bid - NMAIN) + (st & 1) : j, bar);
        } else {
          mbar_expect_tx(bar, 8192);
          tma_ld2(sb + OFF_A + (warp * NA + k) * 8192, &P.tm[TM_XIN], warp * 1024 + kc, r * 64, bar);
        }
      }
    }
    asm volatile("fence.mbarrier_init.release.cluster;" ::: "memory");
    asm volatile("prefetch.tensormap [%0];" ::"l"(&P.tm[warp]) : "memory");
    if (smem_u32(smem_raw) != SB) __trap();
  }
  __syncthreads();
  const uint32_t epoch = __shfl_sync(~0u, lds32(sb + OFF_HOLD + 8), 0);

  if (aux) aux_cta(P, bid, warp, lane, epoch);
  else if (warp >= 8) {
    asm volatile("setmaxnreg.dec.sync.aligned.u32 24;");
    if (warp == 11) server(P, bid, r, j, lane, epoch);
    else if (warp != 8) aloader(P, bid, r, j, lane, warp - 9, epoch);
    else bloader(P, bid, j, lane, epoch);
  } else {
    asm volatile("setmaxnreg.inc.sync.aligned.u32 240;");
    const int w = warp >> 2, wp = warp & 3, g = lane >> 2, q = lane & 3;
    {
      PROF_T(w, 0, 3);
      spin_until(centry + STARTC);
      uint32_t xr[32];
#pragma unroll
      for (int u = 0; u < 32; u++) xr[u] = 0;
      const int rowpair = r * 64 + w * 32 + wp * 8 + g;
      Pipe M;
      M.p = 0; M.g8 = 0; M.a8 = w * NA * 8; M.aph = 0; M.tph = 0; M.aend = (w + 1) * NA * 8;
      M.curB = M.curA = M.prevB = M.prevA = M.sph = 0; M.w = w; M.l0 = lane == 0;
      M.bo = (wp * 16 + (lane & 15)) * 128 + (((lane >> 4) ^ (lane & 7)) << 4);
      M.so = __shfl_sync(~0u, SB + OFF_A + wp * 2048 + lane * 32 + (lane >> 2) * 4, lane);
      M.bo = __shfl_sync(~0u, M.bo, lane);
      auto nop = [](int) {};
      const uint32_t zero = gridDim.y - 1;
#pragma unroll 1
      for (int hl = 0; hl < 4; hl++) {
        const int t0 = hl * 3;
        const bool ffn = hl & 1;
        float acc[96], acn[64];
        uint32_t au[2] = {0u, 0u};
        {
          M.begin<192>(acc, ffn ? 12 : 3, t0);
          float ss[2] = {0.f, 0.f}, sq[2] = {0.f, 0.f};
          auto part = [&](auto c0, auto c1) {
#pragma unroll
            for (int u = c0.v; u < c1.v; u++) {
              float a, b;
              asm volatile("shl.b32 %0, %2, 16;\nand.b32 %1, %2, 0xffff0000;" : "=f"(a), "=f"(b) : "r"(xr[u]));
              ss[u & 1] += a + b; sq[u & 1] = fmaf(a, a, fmaf(b, b, sq[u & 1]));
            }
          };
          const int d = hl ? 0 : D0;
          M.run<192, false>(acc, 1, 16, 1u << 10, 16 - (ffn ? LEAD3 : LEAD0), [&](int i, uint2 ok) {
           CT(0);
           if (i == d + 1) part(IC<0>{}, IC<Q1>{});
           CT(1);
           M.ensure(ok);
           CT(3);
           M.validate(hl != 0, &P.tm[ffn ? TM_XA16 : TM_X16], w * 1024, r * 64, wp, j, [&] {
            if (i <= d + 5) {
              if (i == d) {
#pragma unroll
                for (int u = 0; u < 8; u++)
                  asm volatile("ldmatrix.sync.aligned.m8n8.x4.shared.b16 {%0,%1,%2,%3}, [%4];" : "=r"(xr[4 * u]), "=r"(xr[4 * u + 1]), "=r"(xr[4 * u + 2]), "=r"(xr[4 * u + 3])
                               : "r"(box_addr(sb + OFF_A + (w * NA + D0 + (u >> 2)) * 8192, M.bo, u & 3)) : "memory");
              }
              if (i == d + 2) part(IC<Q1>{}, IC<Q2>{});
              if (i == d + 3) part(IC<Q2>{}, IC<Q3>{});
              if (i == d + 4) part(IC<Q3>{}, IC<32>{});
              if (i == d + 5) {
#pragma unroll
                for (int o = 1; o < 4; o *= 2)
#pragma unroll
                  for (int z = 0; z < 2; z++) { ss[z] += __shfl_xor_sync(~0u, ss[z], o); sq[z] += __shfl_xor_sync(~0u, sq[z], o); }
                const float m0 = ss[0] * (1.f / 128.f), m1 = ss[1] * (1.f / 128.f);
                if (q == 0)
                  st_pkt(&P.s->stats[hl][rowpair >> 1][j][rowpair & 1], __float_as_uint(m0), (__float_as_uint(fmaxf(fmaf(-ss[0], m0, sq[0]), 0.f)) & ~63u) | (epoch & 63),
                         __float_as_uint(m1), __float_as_uint(fmaxf(fmaf(-ss[1], m1, sq[1]), 0.f)));
              }
            }
            if (i == 13) { mbar_spin(sb + BAR_STAT + w * 8, hl & 1); stats_fetch(w, wp, au); }
           });
           CT(4);
          });
          M.end<192, true>(acc, ffn ? 0 : 4, 15, au[0], au[1], t0);
          PROF_T(w, t0, 2);
        }
        if (!ffn) {
          Attn T;
#pragma unroll 1
          for (int wave = 0; wave < 2; wave++) {
            AP(9);
            uint4* const hp = P.s->halo[0][0] + (uint32_t)(((hl + wave) * 256 + r * 16 + j * 2 + w) * 136);
            T.A(acc, M, w, wp, r, hp);
            AP(0);
            if (wave == 0) {
              M.begin<192, PACE2 & 1>(acc, 6, t0 + 1);
              M.run<192>(acc, 1, NH1, 4, -1, nop);
              T.B(w, wp, 0);
              M.drain();
            } else {
              M.begin<128, (PACE2 >> 1) & 1>(acn, 12, t0 + 2);
              M.run<128>(acn, 1, NH2, 4, -1, nop);
              T.B(w, wp, 1);
              M.drain();
#pragma unroll
              for (int z = 0; z < 64; z++) asm volatile("mov.b32 %0, %1;" : "=f"(acc[z]) : "f"(acn[z]));
#pragma unroll
              for (int z = 64; z < 96; z++) acc[z] = 0.f;
            }
            AP(2);
            T.C(wp, r, zero);
            AP(3);
            if (wave == 1) break;
            M.run<192>(acc, NH1, 16, 1u << 7, 16 - LEAD1, [&](int i) { if (i == NH1) T.E(M, false); });
            M.end<192, true>(acc, 4, 10, au[0], au[1], t0 + 1);
            PROF_T(w, t0 + 1, 2);
          }
#pragma unroll
          for (int z = 0; z < 64; z++) asm volatile("mov.b32 %0, %1;" : "=f"(acn[z]) : "f"(acc[z]));
          M.ensure(M.iss<128, false>(acn, false));
          T.E(M, true);
        } else {
          uint32_t pk[48], pk2[64];
          pack_relu(pk, acc);
          {
            float acc2[128];
            M.begin<256, (PACE2 >> 3) & 1>(acc2, 0, t0 + 1);
            M.run<256>(acc2, 1, 16, 0x248, 16 - LEAD4, [&](int i) { ffn_stage(pk, i, M); });
            M.end<256, true>(acc2, 0, 0, au[0], au[1], t0 + 1);
            pack_relu(pk2, acc2);
            PROF_T(w, t0 + 1, 2);
          }
          M.begin<128, (PACE2 >> 4) & 1>(acn, 2, t0 + 2);
          M.run<128>(acn, 1, 13, 0x1248, -1, [&](int i) { ffn_stage(pk2, i, M); });
        }
        {
          float pre[64], rstd[2] = {0.f, 0.f};
#pragma unroll
          for (int u = 0; u < 32; u++) { pre[u] = __uint_as_float(xr[u]); pre[32 + u] = 0.f; }
          const int ks = ffn ? 56 : 16, pause = ks - (ffn ? LEAD5 : LEAD2), vfrom = ffn ? 99 : 7;
          M.run<128>(acn, ffn ? 13 : NH2 + 1, ks, 0, pause, [&](int i) {
            if (i >= vfrom) {
              if (i == 7) mbar_spin(sb + BAR_OWN + w * 8, hl >> 1);
              M.validate(true, &P.tm[TM_O16], 0, r * 128 + w * 64, wp, j, [] {});
            }
          }, w ? (ffn ? (PRE5 ? PRE5 : pause) : (PRE2 ? PRE2 : pause)) : (ffn ? 20 : IPRE), [&](int) { presum(pre, ffn ? 1.f : 0.f); own_rstd(w, wp, rstd); });
          M.end<128, false>(acn, 2, 0, 0, 0, t0 + 2);
          epi_res(acn, pre, ffn ? rstd[0] * rstd[0] : 1.f, ffn ? rstd[1] * rstd[1] : 1.f, xr, M, wp);
          PROF_T(w, t0 + 2, 2);
        }
      }
    }
  }
}

typedef CUresult (*EncFn)(CUtensorMap*, CUtensorMapDataType, cuuint32_t, void*, const cuuint64_t*, const cuuint64_t*, const cuuint32_t*,
                          const cuuint32_t*, CUtensorMapInterleave, CUtensorMapSwizzle, CUtensorMapL2promotion, CUtensorMapFloatOOBfill);

void enc2(EncFn enc, CUtensorMap* tm, const void* p, uint64_t cols, uint64_t rows, uint32_t boxrows = 64, CUtensorMapL2promotion promo = CU_TENSOR_MAP_L2_PROMOTION_L2_128B) {
  cuuint64_t gd[2] = {cols, rows}, gs[1] = {cols * 2};
  cuuint32_t box[2] = {64, boxrows}, es[2] = {1, 1};
  enc(tm, CU_TENSOR_MAP_DATA_TYPE_BFLOAT16, 2, const_cast<void*>(p), gd, gs, box, es, CU_TENSOR_MAP_INTERLEAVE_NONE, CU_TENSOR_MAP_SWIZZLE_128B,
      promo, CU_TENSOR_MAP_FLOAT_OOB_FILL_NONE);
}
void enc4(EncFn enc, CUtensorMap* tm, const void* p, uint64_t K, uint64_t N, uint64_t d2, uint64_t s2, uint64_t d3, uint64_t s3, uint32_t na) {
  cuuint64_t gd[4] = {64, K, d2, d3}, gs[3] = {N * 2, s2, s3};
  cuuint32_t box[4] = {64, 64, na, 1}, es[4] = {1, 1, 1, 1};
  enc(tm, CU_TENSOR_MAP_DATA_TYPE_BFLOAT16, 4, const_cast<void*>(p), gd, gs, box, es, CU_TENSOR_MAP_INTERLEAVE_NONE, CU_TENSOR_MAP_SWIZZLE_128B,
      WPROMO, CU_TENSOR_MAP_FLOAT_OOB_FILL_NONE);
}

}

extern "C" void kernel_launch(void* const* d_in, const int* in_sizes, int n_in, void* d_out, int out_size) {
  static EncFn enc = nullptr;
  static Scratch* ps = nullptr;
  if (!enc) {
    cudaDriverEntryPointQueryResult qr;
    cudaGetDriverEntryPoint("cuTensorMapEncodeTiled", (void**)&enc, cudaEnableDefault, &qr);
    cudaFuncSetAttribute(mega_kernel, cudaFuncAttributeMaxDynamicSharedMemorySize, SMEM_BYTES);
    cudaGetSymbolAddress((void**)&ps, g_s);
  }
  Params P;
  P.s = ps;
  void *p_h = ps->h, *p_x = ps->x;
  enc2(enc, &P.tm[TM_XIN], d_in[0], 2048, 1024, 64, XPROMO);
  enc2(enc, &P.tm[TM_X], d_out, 2048, 1024);
  enc2(enc, &P.tm[TM_XA], p_x, 2048, 1024);
  enc2(enc, &P.tm[TM_O], p_h, 3584, 2048);
  enc2(enc, &P.tm[TM_H], p_h, 3584, 2048);
  enc2(enc, &P.tm[TM_X16], d_out, 2048, 1024, 16);
  enc2(enc, &P.tm[TM_XA16], p_x, 2048, 1024, 16);
  enc2(enc, &P.tm[TM_O16], p_h, 3584, 2048, 16);
  enc4(enc, &P.tm[TM_WQKV], d_in[1], 1024, 3072, 3, 2048, 16, 128, 3);
  enc4(enc, &P.tm[TM_WO], d_in[2], 1024, 1024, 16, 128, 1, 128, 2);
  enc4(enc, &P.tm[TM_W1A], d_in[4], 1024, 3584, 56, 128, 1, 128, 4);
  enc4(enc, &P.tm[TM_W1B], d_in[4], 1024, 3584, 56, 128, 1, 128, 3);
  enc4(enc, &P.tm[TM_W2], d_in[6], 3584, 1024, 16, 128, 1, 128, 2);
  P.out = (__nv_bfloat16*)d_out;
  P.b1 = (const __nv_bfloat16*)d_in[5];
  P.b2 = (const __nv_bfloat16*)d_in[7];
  mega_kernel<<<NMAIN + NAUX, NTHREADS, SMEM_BYTES, cudaStreamPerThread>>>(P);
}
```

```cpp
#include <cuda_runtime.h>
#include <cuda_bf16.h>
#include <cuda.h>
#include <stdint.h>

#define LEAD0 2
#define LEAD1 2
#define LEAD2 3
#define LEAD3 1
#define LEAD4 1
#define LEAD5 4
#define WPROMO CU_TENSOR_MAP_L2_PROMOTION_L2_128B
#define PLAN1 0x40201008070000ull
#define PLAN0 0x4030020c8180ull
#define PLANZ 0x40300a050000ull
#define VSKIP 1
#define ELA 1
#define LSO 1
#define STATI 13
#define PACE2 0x1a
#define ST2 14
#define STB 3
#define PROBE 4
#define OWNP 0x22221110
#define SIG0 14
#define STGX 2
#define STGM 3
#define NPRO 4
#define XPROMO CU_TENSOR_MAP_L2_PROMOTION_L2_256B
#define IPRE 7
#define FILLT 1
#define EARLYC 1
#define OWNDLY 0
#define EPW 0
#define CPF 5000
#define STG0 800
#define STG1 500
#define STGL (STG0 + 4 * STG1)
#define STGLX 0
#define STARTC 0
#define PRE5 0
#define PRE2 0
#define FUN 4
#define XEF 0
#define BEF 0xff8
#define AEF 0xdb6
#define SEF 0
#define NPREPX 0
#define NPREPO 0
#define SDELAYO SDELAY
#define SDELAY 300
#define HDELAY 600
#define NH1 6
#define NH2 4
namespace {

constexpr int NMAIN = 128, NAUX = 4, NTHREADS = 384;
constexpr uint32_t OFF_B = 0;
constexpr uint32_t OFF_A = 131072;
constexpr uint32_t OFF_VEC = 229376;
constexpr uint32_t OFF_BAR = 231424;
constexpr uint32_t OFF_RSTD = OFF_VEC + 512, OFF_MEAN = OFF_VEC + 1088, OFF_HOLD = OFF_VEC + 2032;
constexpr uint32_t SMEM_BYTES = OFF_BAR + 960;
constexpr uint32_t BAR_FULLA = OFF_BAR, BAR_FULLB = OFF_BAR + 96, BAR_OWN = OFF_BAR + 160, BAR_EPOCH = OFF_BAR + 176, BAR_AUG = OFF_BAR + 184, BAR_SPEC = OFF_BAR + 192,
                   BAR_EMPTYA = OFF_BAR + 288, BAR_STG = OFF_BAR + 384, BAR_SRV = OFF_BAR + 400, BAR_LEAD = OFF_BAR + 432, BAR_HALO = OFF_BAR + 440, BAR_STG2 = OFF_BAR + 456,
                   BAR_DUMMY3 = OFF_BAR + 472, BAR_EMPTYB = OFF_BAR + 480, BAR_STAT = OFF_BAR + 544, BAR_DUMMY = OFF_BAR + 560;
constexpr int NA = 6;
constexpr uint32_t SB = 1024;
constexpr uint32_t SPIN_LIMIT = 1u << 22;

enum { TM_XIN = 0, TM_X, TM_XA, TM_O, TM_H, TM_WQKV, TM_WO, TM_W1A, TM_W1B, TM_W2, TM_X16, TM_XA16, TM_O16, TM_COUNT };

struct Scratch;
struct Ptrs {
  Scratch* s;
  __nv_bfloat16* out;
  const __nv_bfloat16* b1;
  const __nv_bfloat16* b2;
};
struct Params { CUtensorMap tm[TM_COUNT]; };

constexpr int NSTEP = 280, NSTEP_AUX = 128;
enum : uint32_t { F_STAMP = 1u << 28, F_GATH = 1u << 15, F_NEW = 1u << 16, F_AUG = 1u << 17, F_NOA = 1u << 18, E_HAND = 1u << 19, E_ATTN = 1u << 20, E_XPUB0 = 1u << 21,
                  E_WAIT = 1u << 22, E_REL = 1u << 23, E_KEEP = 1u << 24, E_PART1 = 1u << 25, E_HALO = 1u << 26,
                  E_SIG = 1u << 27, E_RARE = F_NEW | E_KEEP | (0xfu << 20) | (3u << 26) };
constexpr int own_round(int j) { return (OWNP >> (4 * j)) & 15; }
constexpr uint32_t first_order(int j) {
  uint32_t used = 0, v = 0;
  for (int p = 0; p < 8; p++) {
    int c = own_round(j) == p ? j : -1;
    for (int u = 0; u < 8 && c < 0; u++) if (u != j && !((used >> u) & 1) && own_round(u) < p) c = u;
    if (c < 0 && own_round(j ^ 1) == p) c = j ^ 1;
    for (int u = 0; u < 8 && c < 0; u++) { const int x = (u + (j & 6)) & 7; if (x != j && own_round(x) == p) c = x; }
    used |= 1u << c; v |= (uint32_t)c << (4 * p);
  }
  return v;
}
constexpr uint32_t first_round(int p) { uint32_t v = 0; for (int j = 0; j < 8; j++) v |= ((first_order(j) >> (4 * p)) & 15) << (4 * j); return v; }
constexpr uint32_t ROUND0 = first_round(0), ROUND1 = first_round(1);
struct Sched { uint32_t v[9][NSTEP + 8]; };
constexpr Sched make_sched() {
  Sched T{};
  for (int j = 0; j < 8; j++) {
    int owner[16] = {};
    for (int i = 0; i < 16; i++) owner[i] = -100;
    int p = 0, g = 0;
    for (int t = 0; t < 12; t++) {
      const int kind = t % 6, ks = kind == 5 ? 56 : (kind == 2 ? 16 : 17);
      for (int i = 0; i < ks; i++) {
        const bool augs = ks == 17 && i == 16;
        const int na = (kind == 2 || kind == 5) ? 2 : (augs ? 1 : (kind == 4 ? 4 : 3));
        if (i == 0) p = (0x20cc63 >> (4 * kind)) & 15;
        if (augs) p = (0x0f0af >> (4 * kind)) & 15;
        if (p + na > 16) p = 0;
        int need = g - 8;
        for (int a = p; a < p + na; a++) { if (owner[a] > need) need = owner[a]; owner[a] = g; }
        uint32_t k = i, f = i == (t ? 0 : NPRO) ? F_NEW | (1u << 29) : 0;
        if (augs) { k = 0; f |= F_AUG; }
        else if (kind == 0 || kind == 3) {
          const int o = i - 2;
          if (t == 0) k = ((first_order(j) >> (4 * (i >> 1))) & 15) * 2 + (i & 1);
          else if (i < 2) { k = 2 * j + i; f |= F_NOA | (i == 0 ? E_XPUB0 : 0); }
          else { const int half = o >= 7; int u = o - 7 * half; u += u >= j; k = 2 * u + half; if (i == 6) f |= E_REL; if (i < 2 + NPREPX) f |= F_NOA; }
          if (i == 11) f |= E_HAND;
          if (i == (t ? 11 : SIG0)) f |= E_SIG;
        } else if (kind == 1 || kind == 4) {
          if (kind == 1) f |= i == 3 ? E_HAND : (i == 8 ? E_HAND | E_KEEP : (i == 5 ? E_HALO : 0));
          if (kind == 1) f |= i == 13 ? E_REL : 0;
          else if (i == 4 || i == 7 || i == 10) f |= E_HAND;
        } else if (kind == 2) {
          f |= i == 0 ? E_WAIT : (i == 3 ? E_HAND : (i == 5 ? E_HALO : 0));
          if (i == 8) { k = 8 + j; f |= E_ATTN | E_KEEP | F_NOA; }
          if (i > 8) k = i - 1 + (i - 9 >= j);
          if (i > 8 && i < 9 + NPREPO) f |= F_NOA;
          if (i == 11) f |= E_REL;
        } else {
          k = i < 24 ? (i / 3) * 7 + i % 3 : ((i - 24) / 4) * 7 + 3 + (i - 24) % 4;
          if (i == 4 || i == 7 || i == 10 || i == 13) f |= E_HAND;
          f |= i == 0 ? E_WAIT : (i == 24 ? E_WAIT | E_PART1 : 0);
        }
        if ((kind == 2 || kind == 5) && t < 11 && i == ks - (kind == 2 ? 1 : STB)) f |= F_STAMP;
        if (((PACE2 >> kind) & 1) && i == ST2) f |= F_STAMP;
        if (i == 0 && t && ((PACE2 >> ((t - 1) % 6)) & 1)) f |= F_GATH;
        T.v[j][g] = p | ((g - need) << 5) | (k << 9) | f;
        p += na; g++;
      }
    }
    T.v[j][NSTEP] = F_NEW | F_NOA | E_XPUB0 | (2 * j << 9);
  }
  for (int w = 0; w < 2; w++) {
    int owner[14] = {};
    for (int i = 0; i < 14; i++) owner[i] = -100;
    for (int g = w, p = 0; g < NSTEP_AUX; g += 2) {
      const int na = g < 96 ? 3 : 4;
      if (p + na > 14) p = 0;
      int need = g - 8;
      for (int a = p; a < p + na; a++) { if (owner[a] > need) need = owner[a]; owner[a] = g; }
      T.v[8][g] = (p + 14 * w) | ((g - need) << 5) | ((g & 31) >> 1 << 9) | ((g & 30) && g - w != 8 ? 0 : F_NEW | (g - w == 64 ? 2u : 1u) << 29);
      p += na;
    }
  }
  return T;
}
__constant__ Sched c_sched = make_sched();
__device__ __forceinline__ int sched_k(uint32_t e) { return (e >> 3) & 0xfc0; }

struct Scratch {
  __nv_bfloat16 x[2048 * 1024];
  __nv_bfloat16 h[2048 * 3584];
  uint32_t epoch[160];
  uint8_t flags[8][2][64];
  uint32_t pace[8][32];
  uint32_t aug[2][32][1024];
  uint4 stats[4][512][8][2];
  uint4 halo[4][256][136];
};
__device__ __align__(1024) Scratch g_s;
#define PROF_T(w, t, i)
#define PRO(i)
#define LT(i)
#define CT(n)
#define ST(i)
#define AP(i)

__device__ __forceinline__ int work_id() {
  uint32_t smid;
  asm volatile("mov.u32 %0, %%smid;" : "=r"(smid));
  const int t = smid >> 1, u = t - 32, d = (u * 37) >> 8;
  int id = (t & 7) * 16 + (t >> 3) * 2;
  if (t >= 32) id = (1 + u - 7 * d) * 16 + (4 + d) * 2;
  if (t >= 60) id = t < 62 ? t * 2 + 8 : t * 2 - 116;
  return id + (smid & 1);
}

__device__ __forceinline__ uint32_t smem_u32(const void* p) { return (uint32_t)__cvta_generic_to_shared(p); }
__device__ __forceinline__ void mbar_init(uint32_t bar, int cnt) { asm volatile("mbarrier.init.shared::cta.b64 [%0], %1;" ::"r"(bar), "r"(cnt)); }
__device__ __forceinline__ void mbar_expect_tx(uint32_t bar, uint32_t bytes) { asm volatile("mbarrier.arrive.expect_tx.shared::cta.b64 _, [%0], %1;" ::"r"(bar), "r"(bytes) : "memory"); }
__device__ __forceinline__ void mbar_arrive(uint32_t bar, uint32_t cnt) { asm volatile("mbarrier.arrive.shared::cta.b64 _, [%0], %1;" ::"r"(bar), "r"(cnt) : "memory"); }
__device__ __forceinline__ void arrive_n(uint32_t bar, bool) { asm volatile("{\n.reg .pred p;\nelect.sync _|p, 0xffffffff;\n@p mbarrier.arrive.shared::cta.b64 _, [%0];\n}" ::"r"(bar) : "memory"); }
__device__ __forceinline__ void arrive_2(uint32_t b0, uint32_t b1, bool) {
  asm volatile("{\n.reg .pred p;\nelect.sync _|p, 0xffffffff;\n@p mbarrier.arrive.shared::cta.b64 _, [%0];\n@p mbarrier.arrive.shared::cta.b64 _, [%1];\n}" ::"r"(b0), "r"(b1) : "memory");
}
__device__ __forceinline__ void mbar_wait(uint32_t bar, uint32_t parity) {
  asm volatile(
      "{\n.reg .pred p;\n.reg .u32 c;\nmov.u32 c, 0;\n"
      "LAB_WAIT:\nmbarrier.try_wait.parity.shared::cta.b64 p, [%0], %1;\n@p bra.uni DONE;\n"
      "add.u32 c, c, 1;\nsetp.lt.u32 p, c, 4000000;\n@p bra.uni LAB_WAIT;\ntrap;\nDONE:\n}" ::"r"(bar), "r"(parity) : "memory");
}
__device__ __forceinline__ void mbar_spin(uint32_t bar, uint32_t parity) {
  asm volatile("{\n.reg .pred p;\nLAB_WAIT:\nmbarrier.try_wait.parity.shared::cta.b64 p, [%0], %1;\n@!p pmevent 7;\n@!p bra.uni LAB_WAIT;\n}" ::"r"(bar), "r"(parity) : "memory");
}
__device__ __forceinline__ bool elect_one() {
  uint32_t p;
  asm volatile("{\n.reg .pred P;\nelect.sync _|P, 0xffffffff;\nselp.u32 %0, 1, 0, P;\n}" : "=r"(p));
  return p != 0;
}
__device__ __forceinline__ bool mbar_test(uint32_t bar, uint32_t parity) {
  uint32_t ok;
  asm volatile("{\n.reg .pred p;\nmbarrier.test_wait.parity.shared::cta.b64 p, [%1], %2;\nselp.u32 %0, 1, 0, p;\n}" : "=r"(ok) : "r"(bar), "r"(parity) : "memory");
  return ok != 0;
}
__device__ __forceinline__ void tma_ld2(uint32_t dst, const CUtensorMap* tm, int c0, int c1, uint32_t bar) {
  asm volatile("cp.async.bulk.tensor.2d.shared::cluster.global.mbarrier::complete_tx::bytes [%0], [%1, {%3, %4}], [%2];" ::"r"(dst), "l"(tm), "r"(bar), "r"(c0), "r"(c1) : "memory");
}
__device__ __forceinline__ void tma_ld4(uint32_t dst, const CUtensorMap* tm, int c1, int c2, int c3, uint32_t bar, uint64_t pol = 0x1000000000000000ull) {
  asm volatile("cp.async.bulk.tensor.4d.shared::cluster.global.mbarrier::complete_tx::bytes.L2::cache_hint [%0], [%1, {%3, %4, %5, %6}], [%2], %7;" ::"r"(dst), "l"(tm), "r"(bar), "r"(0), "r"(c1), "r"(c2), "r"(c3), "l"(pol) : "memory");
}
__device__ __forceinline__ void tma_st2(const CUtensorMap* tm, int c0, int c1, uint32_t src) {
  asm volatile("cp.async.bulk.tensor.2d.global.shared::cta.bulk_group [%0, {%2, %3}], [%1];" ::"l"(tm), "r"(src), "r"(c0), "r"(c1) : "memory");
}
__device__ __forceinline__ void bulk_ld(uint32_t dst, const void* src, uint32_t bytes, uint32_t bar) {
  asm volatile("cp.async.bulk.shared::cluster.global.mbarrier::complete_tx::bytes [%0], [%1], %2, [%3];" ::"r"(dst), "l"(src), "r"(bytes), "r"(bar) : "memory");
}
__device__ __forceinline__ void e_arrive(uint32_t bar, uint32_t cnt) {
  if (cnt == 1) asm volatile("{\n.reg .pred p;\nelect.sync _|p, 0xffffffff;\n@p mbarrier.arrive.shared::cta.b64 _, [%0];\n}" ::"r"(bar) : "memory");
  else asm volatile("{\n.reg .pred p;\nelect.sync _|p, 0xffffffff;\n@p mbarrier.arrive.shared::cta.b64 _, [%0], %1;\n}" ::"r"(bar), "r"(cnt) : "memory");
}
template <int BYTES = 8192> __device__ __forceinline__ void e_load(uint32_t dst, const CUtensorMap* tm, int c0, int c1, uint32_t bar, uint64_t pol = 0x1000000000000000ull) {
  asm volatile("{\n.reg .pred p;\nelect.sync _|p, 0xffffffff;\n@p mbarrier.arrive.expect_tx.shared::cta.b64 _, [%2], %5;\n"
               "@p cp.async.bulk.tensor.2d.shared::cluster.global.mbarrier::complete_tx::bytes.L2::cache_hint [%0], [%1, {%3, %4}], [%2], %6;\n}"
               ::"r"(dst), "l"(tm), "r"(bar), "r"(c0), "r"(c1), "n"(BYTES), "l"(pol) : "memory");
}
__device__ __forceinline__ void e_store(const CUtensorMap* tm, int c0, int c1, uint32_t src) {
  asm volatile("{\n.reg .pred p;\nfence.proxy.async.shared::cta;\nelect.sync _|p, 0xffffffff;\n"
               "@p cp.async.bulk.tensor.2d.global.shared::cta.bulk_group [%0, {%2, %3}], [%1];\ncp.async.bulk.commit_group;\n}"
               ::"l"(tm), "r"(src), "r"(c0), "r"(c1) : "memory");
}
__device__ __forceinline__ void bulk_commit() { asm volatile("cp.async.bulk.commit_group;" ::: "memory"); }
template <int N> __device__ __forceinline__ void bulk_wait_read() { asm volatile("cp.async.bulk.wait_group.read %0;" ::"n"(N) : "memory"); }
__device__ __forceinline__ void bulk_wait_all() { asm volatile("cp.async.bulk.wait_group 0;" ::: "memory"); }
__device__ __forceinline__ void fence_async_smem() { asm volatile("fence.proxy.async.shared::cta;" ::: "memory"); }
__device__ __forceinline__ void wg_fence() { asm volatile("wgmma.fence.sync.aligned;" ::: "memory"); }
__device__ __forceinline__ void wg_commit() { asm volatile("wgmma.commit_group.sync.aligned;" ::: "memory"); }
template <int N> __device__ __forceinline__ void wg_wait() { asm volatile("wgmma.wait_group.sync.aligned %0;" ::"n"(N) : "memory"); }
__device__ __forceinline__ void wg_bar(int w) { asm volatile("bar.sync %0, 128;" ::"r"(w + 1) : "memory"); }
__device__ __forceinline__ uint32_t ld_acquire(const uint32_t* p) { uint32_t v; asm volatile("ld.acquire.gpu.global.u32 %0, [%1];" : "=r"(v) : "l"(p) : "memory"); return v; }
__device__ __forceinline__ uint4 ld_relaxed4(const uint32_t* p) {
  uint4 v; asm volatile("ld.relaxed.gpu.global.v4.u32 {%0,%1,%2,%3}, [%4];" : "=r"(v.x), "=r"(v.y), "=r"(v.z), "=r"(v.w) : "l"(p) : "memory"); return v;
}
__device__ __forceinline__ void st_release8(uint8_t* p, uint32_t v) { asm volatile("st.release.gpu.global.u8 [%0], %1;" ::"l"(p), "r"(v) : "memory"); }
__device__ __forceinline__ uint32_t ld_relaxed(const uint32_t* p) { uint32_t v; asm volatile("ld.relaxed.gpu.global.u32 %0, [%1];" : "=r"(v) : "l"(p) : "memory"); return v; }
__device__ __forceinline__ void st_release(uint32_t* p, uint32_t v) { asm volatile("st.release.gpu.global.u32 [%0], %1;" ::"l"(p), "r"(v) : "memory"); }
__device__ __forceinline__ void st_pkt(uint4* p, uint32_t a, uint32_t b, uint32_t c, uint32_t d) {
  asm volatile("{\n.reg .b64 lo, hi;\n.reg .b128 v;\nmov.b64 lo, {%1, %2};\nmov.b64 hi, {%3, %4};\nmov.b128 v, {lo, hi};\nst.relaxed.gpu.global.b128 [%0], v;\n}" ::"l"(p), "r"(a), "r"(b), "r"(c), "r"(d) : "memory");
}
__device__ __forceinline__ uint4 ld_pkt(const uint4* p) {
  uint4 r;
  asm volatile("{\n.reg .b64 lo, hi;\n.reg .b128 v;\nld.relaxed.gpu.global.b128 v, [%4];\nmov.b128 {lo, hi}, v;\nmov.b64 {%0, %1}, lo;\nmov.b64 {%2, %3}, hi;\n}" : "=r"(r.x), "=r"(r.y), "=r"(r.z), "=r"(r.w) : "l"(p) : "memory");
  return r;
}
__device__ __forceinline__ uint32_t pack_bf16(float lo, float hi) { uint32_t d; asm("cvt.rn.bf16x2.f32 %0, %1, %2;" : "=r"(d) : "f"(hi), "f"(lo)); return d; }
__device__ __forceinline__ float ex2(float x) { float y; asm("ex2.approx.ftz.f32 %0, %1;" : "=f"(y) : "f"(x)); return y; }
__device__ __forceinline__ float rsq(float x) { float y; asm("rsqrt.approx.ftz.f32 %0, %1;" : "=f"(y) : "f"(x)); return y; }
__device__ __forceinline__ float rcp(float x) { float y; asm("rcp.approx.ftz.f32 %0, %1;" : "=f"(y) : "f"(x)); return y; }
__device__ __forceinline__ float bf_lo(uint32_t v) { return __uint_as_float(v << 16); }
__device__ __forceinline__ float bf_hi(uint32_t v) { return __uint_as_float(v & 0xffff0000u); }
__device__ __forceinline__ void stsm4(uint32_t addr, uint32_t a, uint32_t b, uint32_t c, uint32_t d) {
  asm volatile("stmatrix.sync.aligned.m8n8.x4.shared.b16 [%0], {%1, %2, %3, %4};" ::"r"(addr), "r"(a), "r"(b), "r"(c), "r"(d) : "memory");
}
__device__ __forceinline__ uint32_t movm(uint32_t a) { uint32_t d; asm volatile("movmatrix.sync.aligned.m8n8.trans.b16 %0, %1;" : "=r"(d) : "r"(a)); return d; }
__device__ __forceinline__ void mma16(float (&c)[4], uint32_t a0, uint32_t a1, uint32_t a2, uint32_t a3, uint32_t b0, uint32_t b1) {
  asm volatile("mma.sync.aligned.m16n8k16.row.col.f32.bf16.bf16.f32 {%0,%1,%2,%3}, {%4,%5,%6,%7}, {%8,%9}, {%0,%1,%2,%3};"
               : "+f"(c[0]), "+f"(c[1]), "+f"(c[2]), "+f"(c[3]) : "r"(a0), "r"(a1), "r"(a2), "r"(a3), "r"(b0), "r"(b1));
}
__device__ __forceinline__ void mma8(float (&c)[4], uint32_t a0, uint32_t a1, uint32_t b0) {
  asm volatile("mma.sync.aligned.m16n8k8.row.col.f32.bf16.bf16.f32 {%0,%1,%2,%3}, {%4,%5}, {%6}, {%0,%1,%2,%3};"
               : "+f"(c[0]), "+f"(c[1]), "+f"(c[2]), "+f"(c[3]) : "r"(a0), "r"(a1), "r"(b0));
}
__device__ __forceinline__ void sts128(uint32_t a, uint32_t x, uint32_t y, uint32_t z, uint32_t w) {
  asm volatile("st.shared.v4.b32 [%0], {%1,%2,%3,%4};" ::"r"(a), "r"(x), "r"(y), "r"(z), "r"(w) : "memory");
}
__device__ __forceinline__ float2 lds64(uint32_t a) { float2 v; asm volatile("ld.shared.v2.f32 {%0,%1}, [%2];" : "=f"(v.x), "=f"(v.y) : "r"(a)); return v; }
__device__ __forceinline__ float4 lds128(uint32_t a) { float4 v; asm volatile("ld.shared.v4.f32 {%0,%1,%2,%3}, [%4];" : "=f"(v.x), "=f"(v.y), "=f"(v.z), "=f"(v.w) : "r"(a)); return v; }
__device__ __forceinline__ uint32_t lds32(uint32_t a) { uint32_t v; asm volatile("ld.shared.b32 %0, [%1];" : "=r"(v) : "r"(a)); return v; }
template <int S> __device__ __forceinline__ void wgmma_first128(float (&d)[S], uint32_t da, uint32_t db) {
  asm volatile("{\n.reg .b64 a, b;\n.reg .b32 t, u, h;\n.reg .pred p, q;\nmov.b32 h, 0x40000040;\nwgmma.fence.sync.aligned;\n"
    "add.u32 t, %64, 0;\nadd.u32 u, %65, 0;\nmov.b64 a, {t, h};\nmov.b64 b, {u, h};\n"
    "wgmma.mma_async.sync.aligned.m64n128k16.f32.bf16.bf16 "
    "{%0, %1, %2, %3, %4, %5, %6, %7, %8, %9, %10, %11, %12, %13, %14, %15, %16, %17, %18, %19, %20, %21, %22, %23, %24, %25, %26, %27, %28, %29, %30, %31, %32, %33, %34, %35, %36, %37, %38, %39, %40, %41, %42, %43, %44, %45, %46, %47, %48, %49, %50, %51, %52, %53, %54, %55, %56, %57, %58, %59, %60, %61, %62, %63}, "
    "a, b, 0, 1, 1, 0, 1;\n"
    "add.u32 t, %64, 2;\nadd.u32 u, %65, 128;\nmov.b64 a, {t, h};\nmov.b64 b, {u, h};\n"
    "wgmma.mma_async.sync.aligned.m64n128k16.f32.bf16.bf16 "
    "{%0, %1, %2, %3, %4, %5, %6, %7, %8, %9, %10, %11, %12, %13, %14, %15, %16, %17, %18, %19, %20, %21, %22, %23, %24, %25, %26, %27, %28, %29, %30, %31, %32, %33, %34, %35, %36, %37, %38, %39, %40, %41, %42, %43, %44, %45, %46, %47, %48, %49, %50, %51, %52, %53, %54, %55, %56, %57, %58, %59, %60, %61, %62, %63}, "
    "a, b, 1, 1, 1, 0, 1;\n"
    "add.u32 t, %64, 4;\nadd.u32 u, %65, 256;\nmov.b64 a, {t, h};\nmov.b64 b, {u, h};\n"
    "wgmma.mma_async.sync.aligned.m64n128k16.f32.bf16.bf16 "
    "{%0, %1, %2, %3, %4, %5, %6, %7, %8, %9, %10, %11, %12, %13, %14, %15, %16, %17, %18, %19, %20, %21, %22, %23, %24, %25, %26, %27, %28, %29, %30, %31, %32, %33, %34, %35, %36, %37, %38, %39, %40, %41, %42, %43, %44, %45, %46, %47, %48, %49, %50, %51, %52, %53, %54, %55, %56, %57, %58, %59, %60, %61, %62, %63}, "
    "a, b, 1, 1, 1, 0, 1;\n"
    "add.u32 t, %64, 6;\nadd.u32 u, %65, 384;\nmov.b64 a, {t, h};\nmov.b64 b, {u, h};\n"
    "wgmma.mma_async.sync.aligned.m64n128k16.f32.bf16.bf16 "
    "{%0, %1, %2, %3, %4, %5, %6, %7, %8, %9, %10, %11, %12, %13, %14, %15, %16, %17, %18, %19, %20, %21, %22, %23, %24, %25, %26, %27, %28, %29, %30, %31, %32, %33, %34, %35, %36, %37, %38, %39, %40, %41, %42, %43, %44, %45, %46, %47, %48, %49, %50, %51, %52, %53, %54, %55, %56, %57, %58, %59, %60, %61, %62, %63}, "
    "a, b, 1, 1, 1, 0, 1;\n"
    "wgmma.commit_group.sync.aligned;\n}"
    : "=f"(d[0]), "=f"(d[1]), "=f"(d[2]), "=f"(d[3]), "=f"(d[4]), "=f"(d[5]), "=f"(d[6]), "=f"(d[7]), "=f"(d[8]), "=f"(d[9]), "=f"(d[10]), "=f"(d[11]), "=f"(d[12]), "=f"(d[13]), "=f"(d[14]), "=f"(d[15]), "=f"(d[16]), "=f"(d[17]), "=f"(d[18]), "=f"(d[19]), "=f"(d[20]), "=f"(d[21]), "=f"(d[22]), "=f"(d[23]), "=f"(d[24]), "=f"(d[25]), "=f"(d[26]), "=f"(d[27]), "=f"(d[28]), "=f"(d[29]), "=f"(d[30]), "=f"(d[31]), "=f"(d[32]), "=f"(d[33]), "=f"(d[34]), "=f"(d[35]), "=f"(d[36]), "=f"(d[37]), "=f"(d[38]), "=f"(d[39]), "=f"(d[40]), "=f"(d[41]), "=f"(d[42]), "=f"(d[43]), "=f"(d[44]), "=f"(d[45]), "=f"(d[46]), "=f"(d[47]), "=f"(d[48]), "=f"(d[49]), "=f"(d[50]), "=f"(d[51]), "=f"(d[52]), "=f"(d[53]), "=f"(d[54]), "=f"(d[55]), "=f"(d[56]), "=f"(d[57]), "=f"(d[58]), "=f"(d[59]), "=f"(d[60]), "=f"(d[61]), "=f"(d[62]), "=f"(d[63])
    : "r"(da), "r"(db) : "memory");
}
template <int S> __device__ __forceinline__ uint2 wgmma_probe128(float (&d)[S], uint32_t da, uint32_t db, uint32_t b0, uint32_t p0, uint32_t b1, uint32_t p1) {
  uint2 ok;
  asm volatile("{\n.reg .b64 a, b;\n.reg .b32 t, u, h;\n.reg .pred p, q;\nmov.b32 h, 0x40000040;\nwgmma.fence.sync.aligned;\n"
    "add.u32 t, %66, 0;\nadd.u32 u, %67, 0;\nmov.b64 a, {t, h};\nmov.b64 b, {u, h};\n"
    "wgmma.mma_async.sync.aligned.m64n128k16.f32.bf16.bf16 "
    "{%2, %3, %4, %5, %6, %7, %8, %9, %10, %11, %12, %13, %14, %15, %16, %17, %18, %19, %20, %21, %22, %23, %24, %25, %26, %27, %28, %29, %30, %31, %32, %33, %34, %35, %36, %37, %38, %39, %40, %41, %42, %43, %44, %45, %46, %47, %48, %49, %50, %51, %52, %53, %54, %55, %56, %57, %58, %59, %60, %61, %62, %63, %64, %65}, "
    "a, b, 1, 1, 1, 0, 1;\n"
    "add.u32 t, %66, 2;\nadd.u32 u, %67, 128;\nmov.b64 a, {t, h};\nmov.b64 b, {u, h};\n"
    "wgmma.mma_async.sync.aligned.m64n128k16.f32.bf16.bf16 "
    "{%2, %3, %4, %5, %6, %7, %8, %9, %10, %11, %12, %13, %14, %15, %16, %17, %18, %19, %20, %21, %22, %23, %24, %25, %26, %27, %28, %29, %30, %31, %32, %33, %34, %35, %36, %37, %38, %39, %40, %41, %42, %43, %44, %45, %46, %47, %48, %49, %50, %51, %52, %53, %54, %55, %56, %57, %58, %59, %60, %61, %62, %63, %64, %65}, "
    "a, b, 1, 1, 1, 0, 1;\n"
    "mbarrier.test_wait.parity.shared::cta.b64 p, [%68], %69;\nmbarrier.test_wait.parity.shared::cta.b64 q, [%70], %71;\n"
    "add.u32 t, %66, 4;\nadd.u32 u, %67, 256;\nmov.b64 a, {t, h};\nmov.b64 b, {u, h};\n"
    "wgmma.mma_async.sync.aligned.m64n128k16.f32.bf16.bf16 "
    "{%2, %3, %4, %5, %6, %7, %8, %9, %10, %11, %12, %13, %14, %15, %16, %17, %18, %19, %20, %21, %22, %23, %24, %25, %26, %27, %28, %29, %30, %31, %32, %33, %34, %35, %36, %37, %38, %39, %40, %41, %42, %43, %44, %45, %46, %47, %48, %49, %50, %51, %52, %53, %54, %55, %56, %57, %58, %59, %60, %61, %62, %63, %64, %65}, "
    "a, b, 1, 1, 1, 0, 1;\n"
    "add.u32 t, %66, 6;\nadd.u32 u, %67, 384;\nmov.b64 a, {t, h};\nmov.b64 b, {u, h};\n"
    "wgmma.mma_async.sync.aligned.m64n128k16.f32.bf16.bf16 "
    "{%2, %3, %4, %5, %6, %7, %8, %9, %10, %11, %12, %13, %14, %15, %16, %17, %18, %19, %20, %21, %22, %23, %24, %25, %26, %27, %28, %29, %30, %31, %32, %33, %34, %35, %36, %37, %38, %39, %40, %41, %42, %43, %44, %45, %46, %47, %48, %49, %50, %51, %52, %53, %54, %55, %56, %57, %58, %59, %60, %61, %62, %63, %64, %65}, "
    "a, b, 1, 1, 1, 0, 1;\n"
    "wgmma.commit_group.sync.aligned;\nselp.u32 %0, 1, 0, p;\nselp.u32 %1, 1, 0, q;\n}"
    : "=r"(ok.x), "=r"(ok.y), "+f"(d[0]), "+f"(d[1]), "+f"(d[2]), "+f"(d[3]), "+f"(d[4]), "+f"(d[5]), "+f"(d[6]), "+f"(d[7]), "+f"(d[8]), "+f"(d[9]), "+f"(d[10]), "+f"(d[11]), "+f"(d[12]), "+f"(d[13]), "+f"(d[14]), "+f"(d[15]), "+f"(d[16]), "+f"(d[17]), "+f"(d[18]), "+f"(d[19]), "+f"(d[20]), "+f"(d[21]), "+f"(d[22]), "+f"(d[23]), "+f"(d[24]), "+f"(d[25]), "+f"(d[26]), "+f"(d[27]), "+f"(d[28]), "+f"(d[29]), "+f"(d[30]), "+f"(d[31]), "+f"(d[32]), "+f"(d[33]), "+f"(d[34]), "+f"(d[35]), "+f"(d[36]), "+f"(d[37]), "+f"(d[38]), "+f"(d[39]), "+f"(d[40]), "+f"(d[41]), "+f"(d[42]), "+f"(d[43]), "+f"(d[44]), "+f"(d[45]), "+f"(d[46]), "+f"(d[47]), "+f"(d[48]), "+f"(d[49]), "+f"(d[50]), "+f"(d[51]), "+f"(d[52]), "+f"(d[53]), "+f"(d[54]), "+f"(d[55]), "+f"(d[56]), "+f"(d[57]), "+f"(d[58]), "+f"(d[59]), "+f"(d[60]), "+f"(d[61]), "+f"(d[62]), "+f"(d[63])
    : "r"(da), "r"(db), "r"(b0), "r"(p0), "r"(b1), "r"(p1) : "memory");
  return ok;
}
template <int S> __device__ __forceinline__ void wgmma_first192(float (&d)[S], uint32_t da, uint32_t db) {
  asm volatile("{\n.reg .b64 a, b;\n.reg .b32 t, u, h;\n.reg .pred p, q;\nmov.b32 h, 0x40000040;\nwgmma.fence.sync.aligned;\n"
    "add.u32 t, %96, 0;\nadd.u32 u, %97, 0;\nmov.b64 a, {t, h};\nmov.b64 b, {u, h};\n"
    "wgmma.mma_async.sync.aligned.m64n192k16.f32.bf16.bf16 "
    "{%0, %1, %2, %3, %4, %5, %6, %7, %8, %9, %10, %11, %12, %13, %14, %15, %16, %17, %18, %19, %20, %21, %22, %23, %24, %25, %26, %27, %28, %29, %30, %31, %32, %33, %34, %35, %36, %37, %38, %39, %40, %41, %42, %43, %44, %45, %46, %47, %48, %49, %50, %51, %52, %53, %54, %55, %56, %57, %58, %59, %60, %61, %62, %63, %64, %65, %66, %67, %68, %69, %70, %71, %72, %73, %74, %75, %76, %77, %78, %79, %80, %81, %82, %83, %84, %85, %86, %87, %88, %89, %90, %91, %92, %93, %94, %95}, "
    "a, b, 0, 1, 1, 0, 1;\n"
    "add.u32 t, %96, 2;\nadd.u32 u, %97, 128;\nmov.b64 a, {t, h};\nmov.b64 b, {u, h};\n"
    "wgmma.mma_async.sync.aligned.m64n192k16.f32.bf16.bf16 "
    "{%0, %1, %2, %3, %4, %5, %6, %7, %8, %9, %10, %11, %12, %13, %14, %15, %16, %17, %18, %19, %20, %21, %22, %23, %24, %25, %26, %27, %28, %29, %30, %31, %32, %33, %34, %35, %36, %37, %38, %39, %40, %41, %42, %43, %44, %45, %46, %47, %48, %49, %50, %51, %52, %53, %54, %55, %56, %57, %58, %59, %60, %61, %62, %63, %64, %65, %66, %67, %68, %69, %70, %71, %72, %73, %74, %75, %76, %77, %78, %79, %80, %81, %82, %83, %84, %85, %86, %87, %88, %89, %90, %91, %92, %93, %94, %95}, "
    "a, b, 1, 1, 1, 0, 1;\n"
    "add.u32 t, %96, 4;\nadd.u32 u, %97, 256;\nmov.b64 a, {t, h};\nmov.b64 b, {u, h};\n"
    "wgmma.mma_async.sync.aligned.m64n192k16.f32.bf16.bf16 "
    "{%0, %1, %2, %3, %4, %5, %6, %7, %8, %9, %10, %11, %12, %13, %14, %15, %16, %17, %18, %19, %20, %21, %22, %23, %24, %25, %26, %27, %28, %29, %30, %31, %32, %33, %34, %35, %36, %37, %38, %39, %40, %41, %42, %43, %44, %45, %46, %47, %48, %49, %50, %51, %52, %53, %54, %55, %56, %57, %58, %59, %60, %61, %62, %63, %64, %65, %66, %67, %68, %69, %70, %71, %72, %73, %74, %75, %76, %77, %78, %79, %80, %81, %82, %83, %84, %85, %86, %87, %88, %89, %90, %91, %92, %93, %94, %95}, "
    "a, b, 1, 1, 1, 0, 1;\n"
    "add.u32 t, %96, 6;\nadd.u32 u, %97, 384;\nmov.b64 a, {t, h};\nmov.b64 b, {u, h};\n"
    "wgmma.mma_async.sync.aligned.m64n192k16.f32.bf16.bf16 "
    "{%0, %1, %2, %3, %4, %5, %6, %7, %8, %9, %10, %11, %12, %13, %14, %15, %16, %17, %18, %19, %20, %21, %22, %23, %24, %25, %26, %27, %28, %29, %30, %31, %32, %33, %34, %35, %36, %37, %38, %39, %40, %41, %42, %43, %44, %45, %46, %47, %48, %49, %50, %51, %52, %53, %54, %55, %56, %57, %58, %59, %60, %61, %62, %63, %64, %65, %66, %67, %68, %69, %70, %71, %72, %73, %74, %75, %76, %77, %78, %79, %80, %81, %82, %83, %84, %85, %86, %87, %88, %89, %90, %91, %92, %93, %94, %95}, "
    "a, b, 1, 1, 1, 0, 1;\n"
    "wgmma.commit_group.sync.aligned;\n}"
    : "=f"(d[0]), "=f"(d[1]), "=f"(d[2]), "=f"(d[3]), "=f"(d[4]), "=f"(d[5]), "=f"(d[6]), "=f"(d[7]), "=f"(d[8]), "=f"(d[9]), "=f"(d[10]), "=f"(d[11]), "=f"(d[12]), "=f"(d[13]), "=f"(d[14]), "=f"(d[15]), "=f"(d[16]), "=f"(d[17]), "=f"(d[18]), "=f"(d[19]), "=f"(d[20]), "=f"(d[21]), "=f"(d[22]), "=f"(d[23]), "=f"(d[24]), "=f"(d[25]), "=f"(d[26]), "=f"(d[27]), "=f"(d[28]), "=f"(d[29]), "=f"(d[30]), "=f"(d[31]), "=f"(d[32]), "=f"(d[33]), "=f"(d[34]), "=f"(d[35]), "=f"(d[36]), "=f"(d[37]), "=f"(d[38]), "=f"(d[39]), "=f"(d[40]), "=f"(d[41]), "=f"(d[42]), "=f"(d[43]), "=f"(d[44]), "=f"(d[45]), "=f"(d[46]), "=f"(d[47]), "=f"(d[48]), "=f"(d[49]), "=f"(d[50]), "=f"(d[51]), "=f"(d[52]), "=f"(d[53]), "=f"(d[54]), "=f"(d[55]), "=f"(d[56]), "=f"(d[57]), "=f"(d[58]), "=f"(d[59]), "=f"(d[60]), "=f"(d[61]), "=f"(d[62]), "=f"(d[63]), "=f"(d[64]), "=f"(d[65]), "=f"(d[66]), "=f"(d[67]), "=f"(d[68]), "=f"(d[69]), "=f"(d[70]), "=f"(d[71]), "=f"(d[72]), "=f"(d[73]), "=f"(d[74]), "=f"(d[75]), "=f"(d[76]), "=f"(d[77]), "=f"(d[78]), "=f"(d[79]), "=f"(d[80]), "=f"(d[81]), "=f"(d[82]), "=f"(d[83]), "=f"(d[84]), "=f"(d[85]), "=f"(d[86]), "=f"(d[87]), "=f"(d[88]), "=f"(d[89]), "=f"(d[90]), "=f"(d[91]), "=f"(d[92]), "=f"(d[93]), "=f"(d[94]), "=f"(d[95])
    : "r"(da), "r"(db) : "memory");
}
template <int S> __device__ __forceinline__ uint2 wgmma_probe192(float (&d)[S], uint32_t da, uint32_t db, uint32_t b0, uint32_t p0, uint32_t b1, uint32_t p1) {
  uint2 ok;
  asm volatile("{\n.reg .b64 a, b;\n.reg .b32 t, u, h;\n.reg .pred p, q;\nmov.b32 h, 0x40000040;\nwgmma.fence.sync.aligned;\n"
    "add.u32 t, %98, 0;\nadd.u32 u, %99, 0;\nmov.b64 a, {t, h};\nmov.b64 b, {u, h};\n"
    "wgmma.mma_async.sync.aligned.m64n192k16.f32.bf16.bf16 "
    "{%2, %3, %4, %5, %6, %7, %8, %9, %10, %11, %12, %13, %14, %15, %16, %17, %18, %19, %20, %21, %22, %23, %24, %25, %26, %27, %28, %29, %30, %31, %32, %33, %34, %35, %36, %37, %38, %39, %40, %41, %42, %43, %44, %45, %46, %47, %48, %49, %50, %51, %52, %53, %54, %55, %56, %57, %58, %59, %60, %61, %62, %63, %64, %65, %66, %67, %68, %69, %70, %71, %72, %73, %74, %75, %76, %77, %78, %79, %80, %81, %82, %83, %84, %85, %86, %87, %88, %89, %90, %91, %92, %93, %94, %95, %96, %97}, "
    "a, b, 1, 1, 1, 0, 1;\n"
    "add.u32 t, %98, 2;\nadd.u32 u, %99, 128;\nmov.b64 a, {t, h};\nmov.b64 b, {u, h};\n"
    "wgmma.mma_async.sync.aligned.m64n192k16.f32.bf16.bf16 "
    "{%2, %3, %4, %5, %6, %7, %8, %9, %10, %11, %12, %13, %14, %15, %16, %17, %18, %19, %20, %21, %22, %23, %24, %25, %26, %27, %28, %29, %30, %31, %32, %33, %34, %35, %36, %37, %38, %39, %40, %41, %42, %43, %44, %45, %46, %47, %48, %49, %50, %51, %52, %53, %54, %55, %56, %57, %58, %59, %60, %61, %62, %63, %64, %65, %66, %67, %68, %69, %70, %71, %72, %73, %74, %75, %76, %77, %78, %79, %80, %81, %82, %83, %84, %85, %86, %87, %88, %89, %90, %91, %92, %93, %94, %95, %96, %97}, "
    "a, b, 1, 1, 1, 0, 1;\n"
    "mbarrier.test_wait.parity.shared::cta.b64 p, [%100], %101;\nmbarrier.test_wait.parity.shared::cta.b64 q, [%102], %103;\n"
    "add.u32 t, %98, 4;\nadd.u32 u, %99, 256;\nmov.b64 a, {t, h};\nmov.b64 b, {u, h};\n"
    "wgmma.mma_async.sync.aligned.m64n192k16.f32.bf16.bf16 "
    "{%2, %3, %4, %5, %6, %7, %8, %9, %10, %11, %12, %13, %14, %15, %16, %17, %18, %19, %20, %21, %22, %23, %24, %25, %26, %27, %28, %29, %30, %31, %32, %33, %34, %35, %36, %37, %38, %39, %40, %41, %42, %43, %44, %45, %46, %47, %48, %49, %50, %51, %52, %53, %54, %55, %56, %57, %58, %59, %60, %61, %62, %63, %64, %65, %66, %67, %68, %69, %70, %71, %72, %73, %74, %75, %76, %77, %78, %79, %80, %81, %82, %83, %84, %85, %86, %87, %88, %89, %90, %91, %92, %93, %94, %95, %96, %97}, "
    "a, b, 1, 1, 1, 0, 1;\n"
    "add.u32 t, %98, 6;\nadd.u32 u, %99, 384;\nmov.b64 a, {t, h};\nmov.b64 b, {u, h};\n"
    "wgmma.mma_async.sync.aligned.m64n192k16.f32.bf16.bf16 "
    "{%2, %3, %4, %5, %6, %7, %8, %9, %10, %11, %12, %13, %14, %15, %16, %17, %18, %19, %20, %21, %22, %23, %24, %25, %26, %27, %28, %29, %30, %31, %32, %33, %34, %35, %36, %37, %38, %39, %40, %41, %42, %43, %44, %45, %46, %47, %48, %49, %50, %51, %52, %53, %54, %55, %56, %57, %58, %59, %60, %61, %62, %63, %64, %65, %66, %67, %68, %69, %70, %71, %72, %73, %74, %75, %76, %77, %78, %79, %80, %81, %82, %83, %84, %85, %86, %87, %88, %89, %90, %91, %92, %93, %94, %95, %96, %97}, "
    "a, b, 1, 1, 1, 0, 1;\n"
    "wgmma.commit_group.sync.aligned;\nselp.u32 %0, 1, 0, p;\nselp.u32 %1, 1, 0, q;\n}"
    : "=r"(ok.x), "=r"(ok.y), "+f"(d[0]), "+f"(d[1]), "+f"(d[2]), "+f"(d[3]), "+f"(d[4]), "+f"(d[5]), "+f"(d[6]), "+f"(d[7]), "+f"(d[8]), "+f"(d[9]), "+f"(d[10]), "+f"(d[11]), "+f"(d[12]), "+f"(d[13]), "+f"(d[14]), "+f"(d[15]), "+f"(d[16]), "+f"(d[17]), "+f"(d[18]), "+f"(d[19]), "+f"(d[20]), "+f"(d[21]), "+f"(d[22]), "+f"(d[23]), "+f"(d[24]), "+f"(d[25]), "+f"(d[26]), "+f"(d[27]), "+f"(d[28]), "+f"(d[29]), "+f"(d[30]), "+f"(d[31]), "+f"(d[32]), "+f"(d[33]), "+f"(d[34]), "+f"(d[35]), "+f"(d[36]), "+f"(d[37]), "+f"(d[38]), "+f"(d[39]), "+f"(d[40]), "+f"(d[41]), "+f"(d[42]), "+f"(d[43]), "+f"(d[44]), "+f"(d[45]), "+f"(d[46]), "+f"(d[47]), "+f"(d[48]), "+f"(d[49]), "+f"(d[50]), "+f"(d[51]), "+f"(d[52]), "+f"(d[53]), "+f"(d[54]), "+f"(d[55]), "+f"(d[56]), "+f"(d[57]), "+f"(d[58]), "+f"(d[59]), "+f"(d[60]), "+f"(d[61]), "+f"(d[62]), "+f"(d[63]), "+f"(d[64]), "+f"(d[65]), "+f"(d[66]), "+f"(d[67]), "+f"(d[68]), "+f"(d[69]), "+f"(d[70]), "+f"(d[71]), "+f"(d[72]), "+f"(d[73]), "+f"(d[74]), "+f"(d[75]), "+f"(d[76]), "+f"(d[77]), "+f"(d[78]), "+f"(d[79]), "+f"(d[80]), "+f"(d[81]), "+f"(d[82]), "+f"(d[83]), "+f"(d[84]), "+f"(d[85]), "+f"(d[86]), "+f"(d[87]), "+f"(d[88]), "+f"(d[89]), "+f"(d[90]), "+f"(d[91]), "+f"(d[92]), "+f"(d[93]), "+f"(d[94]), "+f"(d[95])
    : "r"(da), "r"(db), "r"(b0), "r"(p0), "r"(b1), "r"(p1) : "memory");
  return ok;
}
template <int S> __device__ __forceinline__ void wgmma_first256(float (&d)[S], uint32_t da, uint32_t db) {
  asm volatile("{\n.reg .b64 a, b;\n.reg .b32 t, u, h;\n.reg .pred p, q;\nmov.b32 h, 0x40000040;\nwgmma.fence.sync.aligned;\n"
    "add.u32 t, %128, 0;\nadd.u32 u, %129, 0;\nmov.b64 a, {t, h};\nmov.b64 b, {u, h};\n"
    "wgmma.mma_async.sync.aligned.m64n256k16.f32.bf16.bf16 "
    "{%0, %1, %2, %3, %4, %5, %6, %7, %8, %9, %10, %11, %12, %13, %14, %15, %16, %17, %18, %19, %20, %21, %22, %23, %24, %25, %26, %27, %28, %29, %30, %31, %32, %33, %34, %35, %36, %37, %38, %39, %40, %41, %42, %43, %44, %45, %46, %47, %48, %49, %50, %51, %52, %53, %54, %55, %56, %57, %58, %59, %60, %61, %62, %63, %64, %65, %66, %67, %68, %69, %70, %71, %72, %73, %74, %75, %76, %77, %78, %79, %80, %81, %82, %83, %84, %85, %86, %87, %88, %89, %90, %91, %92, %93, %94, %95, %96, %97, %98, %99, %100, %101, %102, %103, %104, %105, %106, %107, %108, %109, %110, %111, %112, %113, %114, %115, %116, %117, %118, %119, %120, %121, %122, %123, %124, %125, %126, %127}, "
    "a, b, 0, 1, 1, 0, 1;\n"
    "add.u32 t, %128, 2;\nadd.u32 u, %129, 128;\nmov.b64 a, {t, h};\nmov.b64 b, {u, h};\n"
    "wgmma.mma_async.sync.aligned.m64n256k16.f32.bf16.bf16 "
    "{%0, %1, %2, %3, %4, %5, %6, %7, %8, %9, %10, %11, %12, %13, %14, %15, %16, %17, %18, %19, %20, %21, %22, %23, %24, %25, %26, %27, %28, %29, %30, %31, %32, %33, %34, %35, %36, %37, %38, %39, %40, %41, %42, %43, %44, %45, %46, %47, %48, %49, %50, %51, %52, %53, %54, %55, %56, %57, %58, %59, %60, %61, %62, %63, %64, %65, %66, %67, %68, %69, %70, %71, %72, %73, %74, %75, %76, %77, %78, %79, %80, %81, %82, %83, %84, %85, %86, %87, %88, %89, %90, %91, %92, %93, %94, %95, %96, %97, %98, %99, %100, %101, %102, %103, %104, %105, %106, %107, %108, %109, %110, %111, %112, %113, %114, %115, %116, %117, %118, %119, %120, %121, %122, %123, %124, %125, %126, %127}, "
    "a, b, 1, 1, 1, 0, 1;\n"
    "add.u32 t, %128, 4;\nadd.u32 u, %129, 256;\nmov.b64 a, {t, h};\nmov.b64 b, {u, h};\n"
    "wgmma.mma_async.sync.aligned.m64n256k16.f32.bf16.bf16 "
    "{%0, %1, %2, %3, %4, %5, %6, %7, %8, %9, %10, %11, %12, %13, %14, %15, %16, %17, %18, %19, %20, %21, %22, %23, %24, %25, %26, %27, %28, %29, %30, %31, %32, %33, %34, %35, %36, %37, %38, %39, %40, %41, %42, %43, %44, %45, %46, %47, %48, %49, %50, %51, %52, %53, %54, %55, %56, %57, %58, %59, %60, %61, %62, %63, %64, %65, %66, %67, %68, %69, %70, %71, %72, %73, %74, %75, %76, %77, %78, %79, %80, %81, %82, %83, %84, %85, %86, %87, %88, %89, %90, %91, %92, %93, %94, %95, %96, %97, %98, %99, %100, %101, %102, %103, %104, %105, %106, %107, %108, %109, %110, %111, %112, %113, %114, %115, %116, %117, %118, %119, %120, %121, %122, %123, %124, %125, %126, %127}, "
    "a, b, 1, 1, 1, 0, 1;\n"
    "add.u32 t, %128, 6;\nadd.u32 u, %129, 384;\nmov.b64 a, {t, h};\nmov.b64 b, {u, h};\n"
    "wgmma.mma_async.sync.aligned.m64n256k16.f32.bf16.bf16 "
    "{%0, %1, %2, %3, %4, %5, %6, %7, %8, %9, %10, %11, %12, %13, %14, %15, %16, %17, %18, %19, %20, %21, %22, %23, %24, %25, %26, %27, %28, %29, %30, %31, %32, %33, %34, %35, %36, %37, %38, %39, %40, %41, %42, %43, %44, %45, %46, %47, %48, %49, %50, %51, %52, %53, %54, %55, %56, %57, %58, %59, %60, %61, %62, %63, %64, %65, %66, %67, %68, %69, %70, %71, %72, %73, %74, %75, %76, %77, %78, %79, %80, %81, %82, %83, %84, %85, %86, %87, %88, %89, %90, %91, %92, %93, %94, %95, %96, %97, %98, %99, %100, %101, %102, %103, %104, %105, %106, %107, %108, %109, %110, %111, %112, %113, %114, %115, %116, %117, %118, %119, %120, %121, %122, %123, %124, %125, %126, %127}, "
    "a, b, 1, 1, 1, 0, 1;\n"
    "wgmma.commit_group.sync.aligned;\n}"
    : "=f"(d[0]), "=f"(d[1]), "=f"(d[2]), "=f"(d[3]), "=f"(d[4]), "=f"(d[5]), "=f"(d[6]), "=f"(d[7]), "=f"(d[8]), "=f"(d[9]), "=f"(d[10]), "=f"(d[11]), "=f"(d[12]), "=f"(d[13]), "=f"(d[14]), "=f"(d[15]), "=f"(d[16]), "=f"(d[17]), "=f"(d[18]), "=f"(d[19]), "=f"(d[20]), "=f"(d[21]), "=f"(d[22]), "=f"(d[23]), "=f"(d[24]), "=f"(d[25]), "=f"(d[26]), "=f"(d[27]), "=f"(d[28]), "=f"(d[29]), "=f"(d[30]), "=f"(d[31]), "=f"(d[32]), "=f"(d[33]), "=f"(d[34]), "=f"(d[35]), "=f"(d[36]), "=f"(d[37]), "=f"(d[38]), "=f"(d[39]), "=f"(d[40]), "=f"(d[41]), "=f"(d[42]), "=f"(d[43]), "=f"(d[44]), "=f"(d[45]), "=f"(d[46]), "=f"(d[47]), "=f"(d[48]), "=f"(d[49]), "=f"(d[50]), "=f"(d[51]), "=f"(d[52]), "=f"(d[53]), "=f"(d[54]), "=f"(d[55]), "=f"(d[56]), "=f"(d[57]), "=f"(d[58]), "=f"(d[59]), "=f"(d[60]), "=f"(d[61]), "=f"(d[62]), "=f"(d[63]), "=f"(d[64]), "=f"(d[65]), "=f"(d[66]), "=f"(d[67]), "=f"(d[68]), "=f"(d[69]), "=f"(d[70]), "=f"(d[71]), "=f"(d[72]), "=f"(d[73]), "=f"(d[74]), "=f"(d[75]), "=f"(d[76]), "=f"(d[77]), "=f"(d[78]), "=f"(d[79]), "=f"(d[80]), "=f"(d[81]), "=f"(d[82]), "=f"(d[83]), "=f"(d[84]), "=f"(d[85]), "=f"(d[86]), "=f"(d[87]), "=f"(d[88]), "=f"(d[89]), "=f"(d[90]), "=f"(d[91]), "=f"(d[92]), "=f"(d[93]), "=f"(d[94]), "=f"(d[95]), "=f"(d[96]), "=f"(d[97]), "=f"(d[98]), "=f"(d[99]), "=f"(d[100]), "=f"(d[101]), "=f"(d[102]), "=f"(d[103]), "=f"(d[104]), "=f"(d[105]), "=f"(d[106]), "=f"(d[107]), "=f"(d[108]), "=f"(d[109]), "=f"(d[110]), "=f"(d[111]), "=f"(d[112]), "=f"(d[113]), "=f"(d[114]), "=f"(d[115]), "=f"(d[116]), "=f"(d[117]), "=f"(d[118]), "=f"(d[119]), "=f"(d[120]), "=f"(d[121]), "=f"(d[122]), "=f"(d[123]), "=f"(d[124]), "=f"(d[125]), "=f"(d[126]), "=f"(d[127])
    : "r"(da), "r"(db) : "memory");
}
template <int S> __device__ __forceinline__ void wgmma_acc256(float (&d)[S], uint32_t da, uint32_t db) {
  asm volatile("{\n.reg .b64 a, b;\n.reg .b32 t, u, h;\n.reg .pred p, q;\nmov.b32 h, 0x40000040;\nwgmma.fence.sync.aligned;\n"
    "add.u32 t, %128, 0;\nadd.u32 u, %129, 0;\nmov.b64 a, {t, h};\nmov.b64 b, {u, h};\n"
    "wgmma.mma_async.sync.aligned.m64n256k16.f32.bf16.bf16 "
    "{%0, %1, %2, %3, %4, %5, %6, %7, %8, %9, %10, %11, %12, %13, %14, %15, %16, %17, %18, %19, %20, %21, %22, %23, %24, %25, %26, %27, %28, %29, %30, %31, %32, %33, %34, %35, %36, %37, %38, %39, %40, %41, %42, %43, %44, %45, %46, %47, %48, %49, %50, %51, %52, %53, %54, %55, %56, %57, %58, %59, %60, %61, %62, %63, %64, %65, %66, %67, %68, %69, %70, %71, %72, %73, %74, %75, %76, %77, %78, %79, %80, %81, %82, %83, %84, %85, %86, %87, %88, %89, %90, %91, %92, %93, %94, %95, %96, %97, %98, %99, %100, %101, %102, %103, %104, %105, %106, %107, %108, %109, %110, %111, %112, %113, %114, %115, %116, %117, %118, %119, %120, %121, %122, %123, %124, %125, %126, %127}, "
    "a, b, 1, 1, 1, 0, 1;\n"
    "add.u32 t, %128, 2;\nadd.u32 u, %129, 128;\nmov.b64 a, {t, h};\nmov.b64 b, {u, h};\n"
    "wgmma.mma_async.sync.aligned.m64n256k16.f32.bf16.bf16 "
    "{%0, %1, %2, %3, %4, %5, %6, %7, %8, %9, %10, %11, %12, %13, %14, %15, %16, %17, %18, %19, %20, %21, %22, %23, %24, %25, %26, %27, %28, %29, %30, %31, %32, %33, %34, %35, %36, %37, %38, %39, %40, %41, %42, %43, %44, %45, %46, %47, %48, %49, %50, %51, %52, %53, %54, %55, %56, %57, %58, %59, %60, %61, %62, %63, %64, %65, %66, %67, %68, %69, %70, %71, %72, %73, %74, %75, %76, %77, %78, %79, %80, %81, %82, %83, %84, %85, %86, %87, %88, %89, %90, %91, %92, %93, %94, %95, %96, %97, %98, %99, %100, %101, %102, %103, %104, %105, %106, %107, %108, %109, %110, %111, %112, %113, %114, %115, %116, %117, %118, %119, %120, %121, %122, %123, %124, %125, %126, %127}, "
    "a, b, 1, 1, 1, 0, 1;\n"
    "add.u32 t, %128, 4;\nadd.u32 u, %129, 256;\nmov.b64 a, {t, h};\nmov.b64 b, {u, h};\n"
    "wgmma.mma_async.sync.aligned.m64n256k16.f32.bf16.bf16 "
    "{%0, %1, %2, %3, %4, %5, %6, %7, %8, %9, %10, %11, %12, %13, %14, %15, %16, %17, %18, %19, %20, %21, %22, %23, %24, %25, %26, %27, %28, %29, %30, %31, %32, %33, %34, %35, %36, %37, %38, %39, %40, %41, %42, %43, %44, %45, %46, %47, %48, %49, %50, %51, %52, %53, %54, %55, %56, %57, %58, %59, %60, %61, %62, %63, %64, %65, %66, %67, %68, %69, %70, %71, %72, %73, %74, %75, %76, %77, %78, %79, %80, %81, %82, %83, %84, %85, %86, %87, %88, %89, %90, %91, %92, %93, %94, %95, %96, %97, %98, %99, %100, %101, %102, %103, %104, %105, %106, %107, %108, %109, %110, %111, %112, %113, %114, %115, %116, %117, %118, %119, %120, %121, %122, %123, %124, %125, %126, %127}, "
    "a, b, 1, 1, 1, 0, 1;\n"
    "add.u32 t, %128, 6;\nadd.u32 u, %129, 384;\nmov.b64 a, {t, h};\nmov.b64 b, {u, h};\n"
    "wgmma.mma_async.sync.aligned.m64n256k16.f32.bf16.bf16 "
    "{%0, %1, %2, %3, %4, %5, %6, %7, %8, %9, %10, %11, %12, %13, %14, %15, %16, %17, %18, %19, %20, %21, %22, %23, %24, %25, %26, %27, %28, %29, %30, %31, %32, %33, %34, %35, %36, %37, %38, %39, %40, %41, %42, %43, %44, %45, %46, %47, %48, %49, %50, %51, %52, %53, %54, %55, %56, %57, %58, %59, %60, %61, %62, %63, %64, %65, %66, %67, %68, %69, %70, %71, %72, %73, %74, %75, %76, %77, %78, %79, %80, %81, %82, %83, %84, %85, %86, %87, %88, %89, %90, %91, %92, %93, %94, %95, %96, %97, %98, %99, %100, %101, %102, %103, %104, %105, %106, %107, %108, %109, %110, %111, %112, %113, %114, %115, %116, %117, %118, %119, %120, %121, %122, %123, %124, %125, %126, %127}, "
    "a, b, 1, 1, 1, 0, 1;\n"
    "wgmma.commit_group.sync.aligned;\n}"
    : "+f"(d[0]), "+f"(d[1]), "+f"(d[2]), "+f"(d[3]), "+f"(d[4]), "+f"(d[5]), "+f"(d[6]), "+f"(d[7]), "+f"(d[8]), "+f"(d[9]), "+f"(d[10]), "+f"(d[11]), "+f"(d[12]), "+f"(d[13]), "+f"(d[14]), "+f"(d[15]), "+f"(d[16]), "+f"(d[17]), "+f"(d[18]), "+f"(d[19]), "+f"(d[20]), "+f"(d[21]), "+f"(d[22]), "+f"(d[23]), "+f"(d[24]), "+f"(d[25]), "+f"(d[26]), "+f"(d[27]), "+f"(d[28]), "+f"(d[29]), "+f"(d[30]), "+f"(d[31]), "+f"(d[32]), "+f"(d[33]), "+f"(d[34]), "+f"(d[35]), "+f"(d[36]), "+f"(d[37]), "+f"(d[38]), "+f"(d[39]), "+f"(d[40]), "+f"(d[41]), "+f"(d[42]), "+f"(d[43]), "+f"(d[44]), "+f"(d[45]), "+f"(d[46]), "+f"(d[47]), "+f"(d[48]), "+f"(d[49]), "+f"(d[50]), "+f"(d[51]), "+f"(d[52]), "+f"(d[53]), "+f"(d[54]), "+f"(d[55]), "+f"(d[56]), "+f"(d[57]), "+f"(d[58]), "+f"(d[59]), "+f"(d[60]), "+f"(d[61]), "+f"(d[62]), "+f"(d[63]), "+f"(d[64]), "+f"(d[65]), "+f"(d[66]), "+f"(d[67]), "+f"(d[68]), "+f"(d[69]), "+f"(d[70]), "+f"(d[71]), "+f"(d[72]), "+f"(d[73]), "+f"(d[74]), "+f"(d[75]), "+f"(d[76]), "+f"(d[77]), "+f"(d[78]), "+f"(d[79]), "+f"(d[80]), "+f"(d[81]), "+f"(d[82]), "+f"(d[83]), "+f"(d[84]), "+f"(d[85]), "+f"(d[86]), "+f"(d[87]), "+f"(d[88]), "+f"(d[89]), "+f"(d[90]), "+f"(d[91]), "+f"(d[92]), "+f"(d[93]), "+f"(d[94]), "+f"(d[95]), "+f"(d[96]), "+f"(d[97]), "+f"(d[98]), "+f"(d[99]), "+f"(d[100]), "+f"(d[101]), "+f"(d[102]), "+f"(d[103]), "+f"(d[104]), "+f"(d[105]), "+f"(d[106]), "+f"(d[107]), "+f"(d[108]), "+f"(d[109]), "+f"(d[110]), "+f"(d[111]), "+f"(d[112]), "+f"(d[113]), "+f"(d[114]), "+f"(d[115]), "+f"(d[116]), "+f"(d[117]), "+f"(d[118]), "+f"(d[119]), "+f"(d[120]), "+f"(d[121]), "+f"(d[122]), "+f"(d[123]), "+f"(d[124]), "+f"(d[125]), "+f"(d[126]), "+f"(d[127])
    : "r"(da), "r"(db) : "memory");
}
template <int S> __device__ __forceinline__ void wgmma_aug192(float (&d)[S], uint32_t a0, uint32_t a1, uint32_t db) {
  asm volatile("{\n.reg .b64 b;\n.reg .b32 h, z;\nmov.b32 h, 0x40000000;\nmov.b32 z, 0;\n"
    "mov.b64 b, {%98, h};\nwgmma.fence.sync.aligned;\n"
    "wgmma.mma_async.sync.aligned.m64n192k16.f32.bf16.bf16 "
    "{%0, %1, %2, %3, %4, %5, %6, %7, %8, %9, %10, %11, %12, %13, %14, %15, %16, %17, %18, %19, %20, %21, %22, %23, %24, %25, %26, %27, %28, %29, %30, %31, %32, %33, %34, %35, %36, %37, %38, %39, %40, %41, %42, %43, %44, %45, %46, %47, %48, %49, %50, %51, %52, %53, %54, %55, %56, %57, %58, %59, %60, %61, %62, %63, %64, %65, %66, %67, %68, %69, %70, %71, %72, %73, %74, %75, %76, %77, %78, %79, %80, %81, %82, %83, %84, %85, %86, %87, %88, %89, %90, %91, %92, %93, %94, %95}, "
    "{%96, %97, z, z}, b, 1, 1, 1, 1;\n"
    "wgmma.commit_group.sync.aligned;\n}"
    : "+f"(d[0]), "+f"(d[1]), "+f"(d[2]), "+f"(d[3]), "+f"(d[4]), "+f"(d[5]), "+f"(d[6]), "+f"(d[7]), "+f"(d[8]), "+f"(d[9]), "+f"(d[10]), "+f"(d[11]), "+f"(d[12]), "+f"(d[13]), "+f"(d[14]), "+f"(d[15]), "+f"(d[16]), "+f"(d[17]), "+f"(d[18]), "+f"(d[19]), "+f"(d[20]), "+f"(d[21]), "+f"(d[22]), "+f"(d[23]), "+f"(d[24]), "+f"(d[25]), "+f"(d[26]), "+f"(d[27]), "+f"(d[28]), "+f"(d[29]), "+f"(d[30]), "+f"(d[31]), "+f"(d[32]), "+f"(d[33]), "+f"(d[34]), "+f"(d[35]), "+f"(d[36]), "+f"(d[37]), "+f"(d[38]), "+f"(d[39]), "+f"(d[40]), "+f"(d[41]), "+f"(d[42]), "+f"(d[43]), "+f"(d[44]), "+f"(d[45]), "+f"(d[46]), "+f"(d[47]), "+f"(d[48]), "+f"(d[49]), "+f"(d[50]), "+f"(d[51]), "+f"(d[52]), "+f"(d[53]), "+f"(d[54]), "+f"(d[55]), "+f"(d[56]), "+f"(d[57]), "+f"(d[58]), "+f"(d[59]), "+f"(d[60]), "+f"(d[61]), "+f"(d[62]), "+f"(d[63]), "+f"(d[64]), "+f"(d[65]), "+f"(d[66]), "+f"(d[67]), "+f"(d[68]), "+f"(d[69]), "+f"(d[70]), "+f"(d[71]), "+f"(d[72]), "+f"(d[73]), "+f"(d[74]), "+f"(d[75]), "+f"(d[76]), "+f"(d[77]), "+f"(d[78]), "+f"(d[79]), "+f"(d[80]), "+f"(d[81]), "+f"(d[82]), "+f"(d[83]), "+f"(d[84]), "+f"(d[85]), "+f"(d[86]), "+f"(d[87]), "+f"(d[88]), "+f"(d[89]), "+f"(d[90]), "+f"(d[91]), "+f"(d[92]), "+f"(d[93]), "+f"(d[94]), "+f"(d[95])
    : "r"(a0), "r"(a1), "r"(db) : "memory");
}
template <int S> __device__ __forceinline__ void wgmma_aug256(float (&d)[S], uint32_t a0, uint32_t a1, uint32_t db) {
  asm volatile("{\n.reg .b64 b;\n.reg .b32 h, z;\nmov.b32 h, 0x40000000;\nmov.b32 z, 0;\n"
    "mov.b64 b, {%130, h};\nwgmma.fence.sync.aligned;\n"
    "wgmma.mma_async.sync.aligned.m64n256k16.f32.bf16.bf16 "
    "{%0, %1, %2, %3, %4, %5, %6, %7, %8, %9, %10, %11, %12, %13, %14, %15, %16, %17, %18, %19, %20, %21, %22, %23, %24, %25, %26, %27, %28, %29, %30, %31, %32, %33, %34, %35, %36, %37, %38, %39, %40, %41, %42, %43, %44, %45, %46, %47, %48, %49, %50, %51, %52, %53, %54, %55, %56, %57, %58, %59, %60, %61, %62, %63, %64, %65, %66, %67, %68, %69, %70, %71, %72, %73, %74, %75, %76, %77, %78, %79, %80, %81, %82, %83, %84, %85, %86, %87, %88, %89, %90, %91, %92, %93, %94, %95, %96, %97, %98, %99, %100, %101, %102, %103, %104, %105, %106, %107, %108, %109, %110, %111, %112, %113, %114, %115, %116, %117, %118, %119, %120, %121, %122, %123, %124, %125, %126, %127}, "
    "{%128, %129, z, z}, b, 1, 1, 1, 1;\n"
    "wgmma.commit_group.sync.aligned;\n}"
    : "+f"(d[0]), "+f"(d[1]), "+f"(d[2]), "+f"(d[3]), "+f"(d[4]), "+f"(d[5]), "+f"(d[6]), "+f"(d[7]), "+f"(d[8]), "+f"(d[9]), "+f"(d[10]), "+f"(d[11]), "+f"(d[12]), "+f"(d[13]), "+f"(d[14]), "+f"(d[15]), "+f"(d[16]), "+f"(d[17]), "+f"(d[18]), "+f"(d[19]), "+f"(d[20]), "+f"(d[21]), "+f"(d[22]), "+f"(d[23]), "+f"(d[24]), "+f"(d[25]), "+f"(d[26]), "+f"(d[27]), "+f"(d[28]), "+f"(d[29]), "+f"(d[30]), "+f"(d[31]), "+f"(d[32]), "+f"(d[33]), "+f"(d[34]), "+f"(d[35]), "+f"(d[36]), "+f"(d[37]), "+f"(d[38]), "+f"(d[39]), "+f"(d[40]), "+f"(d[41]), "+f"(d[42]), "+f"(d[43]), "+f"(d[44]), "+f"(d[45]), "+f"(d[46]), "+f"(d[47]), "+f"(d[48]), "+f"(d[49]), "+f"(d[50]), "+f"(d[51]), "+f"(d[52]), "+f"(d[53]), "+f"(d[54]), "+f"(d[55]), "+f"(d[56]), "+f"(d[57]), "+f"(d[58]), "+f"(d[59]), "+f"(d[60]), "+f"(d[61]), "+f"(d[62]), "+f"(d[63]), "+f"(d[64]), "+f"(d[65]), "+f"(d[66]), "+f"(d[67]), "+f"(d[68]), "+f"(d[69]), "+f"(d[70]), "+f"(d[71]), "+f"(d[72]), "+f"(d[73]), "+f"(d[74]), "+f"(d[75]), "+f"(d[76]), "+f"(d[77]), "+f"(d[78]), "+f"(d[79]), "+f"(d[80]), "+f"(d[81]), "+f"(d[82]), "+f"(d[83]), "+f"(d[84]), "+f"(d[85]), "+f"(d[86]), "+f"(d[87]), "+f"(d[88]), "+f"(d[89]), "+f"(d[90]), "+f"(d[91]), "+f"(d[92]), "+f"(d[93]), "+f"(d[94]), "+f"(d[95]), "+f"(d[96]), "+f"(d[97]), "+f"(d[98]), "+f"(d[99]), "+f"(d[100]), "+f"(d[101]), "+f"(d[102]), "+f"(d[103]), "+f"(d[104]), "+f"(d[105]), "+f"(d[106]), "+f"(d[107]), "+f"(d[108]), "+f"(d[109]), "+f"(d[110]), "+f"(d[111]), "+f"(d[112]), "+f"(d[113]), "+f"(d[114]), "+f"(d[115]), "+f"(d[116]), "+f"(d[117]), "+f"(d[118]), "+f"(d[119]), "+f"(d[120]), "+f"(d[121]), "+f"(d[122]), "+f"(d[123]), "+f"(d[124]), "+f"(d[125]), "+f"(d[126]), "+f"(d[127])
    : "r"(a0), "r"(a1), "r"(db) : "memory");
}

__device__ __forceinline__ uint32_t clock32() { uint32_t c; asm volatile("mov.u32 %0, %%clock;" : "=r"(c)); return c; }
__device__ __forceinline__ void spin_until(uint32_t c) {
  asm volatile("{\n.reg .pred p;\n.reg .s32 t;\nLAB_WAIT:\nmov.u32 t, %%clock;\nsub.s32 t, t, %0;\nsetp.lt.s32 p, t, 0;\n@p bra.uni LAB_WAIT;\n}" ::"r"(c) : "memory");
}
struct Nop { __device__ __forceinline__ void operator()(int) const {} };
template <int V> struct IC { static constexpr int v = V; };
struct Pipe {
  uint32_t p, g8, a8, aph, tph, aend, curB, curA, prevB, prevA, bo, so, sph;
  int w; bool l0;
  __device__ __forceinline__ int lane() const { return LSO ? (so >> 5) & 31 : threadIdx.x & 31; }
  __device__ __forceinline__ void adv_a() { a8 += 8; if (a8 == aend) { a8 -= NA * 8; aph ^= 1; } }
  __device__ __forceinline__ uint32_t take() { const uint32_t a = SB + OFF_A + a8 * 1024; adv_a(); return a; }
  __device__ __forceinline__ uint32_t ahead(int d) const { uint32_t ls = a8 + d * 8; if (ls >= aend) ls -= NA * 8; return SB + OFF_A + ls * 1024; }
  __device__ __forceinline__ uint32_t wait_ahead(int d) {
    uint32_t ls = a8 + d * 8, lp = aph;
    if (ls >= aend) { ls -= NA * 8; lp ^= 1; }
    mbar_spin(SB + BAR_FULLA + ls, lp);
    return SB + OFF_A + ls * 1024;
  }
  template <int N, bool FIRST, int S> __device__ __forceinline__ uint2 iss(float (&acc)[S], bool skip) {
    if (p + N / 64 > 16) p = 0;
    const uint32_t da = (((SB + OFF_A) >> 4) | (1u << 16)) + a8 * 64;
    const uint32_t db = (((SB + OFF_B) >> 4) | (512u << 16)) + p * 512;
    prevB = curB; prevA = curA;
    curB = g8 & 56; curA = a8;
    p += N / 64; g8 += 8;
    a8 += skip ? 16 : 8;
    if (a8 >= aend) { a8 -= NA * 8; aph ^= 1; }
    uint2 ok = make_uint2(0, 0);
    if constexpr (N == 128) {
      if (FIRST) wgmma_first128(acc, da, db);
      else ok = wgmma_probe128(acc, da, db, SB + BAR_FULLB + (g8 & 56), (g8 >> 6) & 1, SB + BAR_FULLA + a8, aph);
    }
    if constexpr (N == 192) {
      if (FIRST) wgmma_first192(acc, da, db);
      else ok = wgmma_probe192(acc, da, db, SB + BAR_FULLB + (g8 & 56), (g8 >> 6) & 1, SB + BAR_FULLA + a8, aph);
    }
    if constexpr (N == 256) { if (FIRST) wgmma_first256(acc, da, db); else wgmma_acc256(acc, da, db); }
    return ok;
  }
  __device__ __forceinline__ void ensure(uint2 ok) {
    asm volatile(
        "{\n.reg .pred p, q;\nsetp.ne.u32 p, %4, 0;\nsetp.ne.u32 q, %5, 0;\n@!p bra.uni LAB_WAIT;\n@q bra.uni DONE;\n"
        "LAB_WAIT:\nmbarrier.try_wait.parity.shared::cta.b64 p, [%0], %1;\nmbarrier.try_wait.parity.shared::cta.b64 q, [%2], %3;\n"
        "and.pred p, p, q;\n@!p bra.uni LAB_WAIT;\nDONE:\n}" ::"r"(SB + BAR_FULLB + (g8 & 56)), "r"((g8 >> 6) & 1), "r"(SB + BAR_FULLA + a8), "r"(aph), "r"(ok.x), "r"(ok.y) : "memory");
  }
  template <class Hook> __device__ __forceinline__ void validate(bool check, const CUtensorMap* tm16, int c0, int c1, int wp, int j, Hook hook) {
    const uint32_t rows = SB + OFF_A + a8 * 1024 + wp * 2048, ad = a8 * 1024 + so;
    uint32_t v0 = 0, v1 = 0;
    asm volatile("{\n.reg .pred p;\nsetp.ne.u32 p, %3, 0;\n@p ld.shared.b32 %0, [%2];\n@p ld.shared.b32 %1, [%2 + 1024];\n}" : "+r"(v0), "+r"(v1) : "r"(ad), "r"((uint32_t)check));
    check = true;
    hook();
    while (__any_sync(~0u, check && max(v0, v1) == 0xffffffffu)) {
      const uint32_t bar = SB + BAR_SPEC + (w * 4 + wp) * 8;
      e_load<2048>(rows, tm16, c0 + sched_k(c_sched.v[j][g8 >> 3]), c1 + wp * 16, bar);
      mbar_spin(bar, sph);
      sph ^= 1;
      v0 = lds32(ad); v1 = lds32(ad + 1024);
    }
  }
  __device__ __forceinline__ void drain() {
    wg_wait<0>();
    arrive_2(SB + BAR_EMPTYB + curB, SB + BAR_EMPTYA + curA, l0);
    curB = BAR_DUMMY - BAR_EMPTYB; curA = BAR_DUMMY - BAR_EMPTYA;
  }
  __device__ __forceinline__ void signal_server(uint32_t odd) { __syncwarp(); arrive_n(SB + BAR_SRV + w * 16 + odd * 8, l0); }
  __device__ __forceinline__ void signal_loader() { __syncwarp(); arrive_n(SB + BAR_STG + w * 8, l0); }
  template <int N, bool HOLD = false, int S, class Pre = Nop> __device__ __forceinline__ void begin(float (&acc)[S], uint32_t p0, int proft, Pre pre = Pre()) {
    p = p0;
    const uint32_t c1 = HOLD ? clock32() : 0;
    ensure(make_uint2(0, 0));
    if (HOLD) spin_until(c1 + lds32(SB + OFF_HOLD + w * 4));
    pre(0);
    PROF_T(w, proft, 0);
    ensure(iss<N, true>(acc, false));
  }
  template <int N, bool ENSURE = true, int S, class Hook, class Mid = Nop> __device__ __forceinline__ void run(float (&acc)[S], int i0, int i1, uint32_t skips, int pause, Hook hook, int imid = -1, Mid mid = Mid()) {
    int i = i0, ev = imid >= 0 ? imid : (w ? pause : -1);
#pragma unroll 1
    while (true) {
      const uint2 ok = iss<N, false>(acc, (skips >> i) & 1);
      wg_wait<1>();
      arrive_2(SB + BAR_EMPTYB + prevB, SB + BAR_EMPTYA + prevA, l0);
      if (pause >= 0 && i + 1 == i1) break;
      if constexpr (ENSURE) { ensure(ok); hook(i); } else hook(i, ok);
      i++;
      if (pause < 0 && i == i1) break;
      if (i == ev) {
        const bool ps = w && i == pause;
        if (ps) drain();
        if (i == imid) mid(i);
        if (ps) mbar_spin(SB + BAR_LEAD, tph);
        ev = pause;
      }
    }
  }
  template <int N, bool AUG, int S> __device__ __forceinline__ void end(float (&acc)[S], int ns, uint32_t pa, uint32_t au0, uint32_t au1, int proft) {
    uint32_t augB = 0;
    if constexpr (AUG) {
      mbar_spin(SB + BAR_FULLB + (g8 & 56), (g8 >> 6) & 1);
      const uint32_t db = (((SB + OFF_B) >> 4) | (64u << 16)) + pa * 512;
      if constexpr (N == 192) wgmma_aug192(acc, au0, au1, db); else wgmma_aug256(acc, au0, au1, db);
      augB = g8 & 56; g8 += 8;
    }
    arrive_n(SB + BAR_LEAD + w * (BAR_DUMMY - BAR_LEAD), l0);
    tph ^= 1;
    if (ns > 0) wait_ahead(ns - 1);
    wg_wait<0>();
    arrive_2(SB + BAR_EMPTYB + curB, SB + BAR_EMPTYA + curA, l0);
    if (AUG) arrive_n(SB + BAR_EMPTYB + augB, l0);
    PROF_T(w, proft, 1);
  }
};

__device__ __forceinline__ uint32_t box_addr(uint32_t buf, uint32_t bo, int u) { return (buf + bo) ^ (u * 32); }

__device__ __forceinline__ float bf_round(float x) { return __bfloat162float(__float2bfloat16_rn(x)); }
__device__ __forceinline__ void own_rstd(int w, int wp, int lane, float (&rstd)[2]) {
#pragma unroll
  for (int hh = 0; hh < 2; hh++) rstd[hh] = __uint_as_float(lds32(SB + OFF_RSTD + (w * 72 + 8 + wp * 16 + (lane >> 2) + hh * 8) * 4));
}
__device__ __forceinline__ void stats_fetch(int w, int wp, int lane, uint32_t (&au)[2]) {
  const int g = lane >> 2, q4 = lane & 3;
  float rstd[2];
  own_rstd(w, wp, lane, rstd);
#pragma unroll
  for (int hh = 0; hh < 2; hh++) {
    const float m = __uint_as_float(lds32(SB + OFF_MEAN + (w * 64 + wp * 16 + g + hh * 8) * 4));
    const float v = q4 == 3 ? rcp(rstd[hh]) : -m;
    const float v1 = bf_round(v), v2 = bf_round(v - v1);
    const float p = q4 == 1 ? v2 : (q4 == 2 ? v - v1 - v2 : v1);
    au[hh] = pack_bf16(p, q4 == 3 ? v2 : p);
  }
}

__device__ __forceinline__ void halo_fetch(uint32_t slot, int w, const uint4* src, uint32_t bar) {
  asm volatile("{\n.reg .pred p;\nelect.sync _|p, 0xffffffff;\n@p mbarrier.arrive.expect_tx.shared::cta.b64 _, [%4], 2080;\n"
               "@p cp.async.bulk.shared::cluster.global.mbarrier::complete_tx::bytes [%0], [%2], 2048, [%4];\n"
               "@p cp.async.bulk.shared::cluster.global.mbarrier::complete_tx::bytes [%1], [%3], 32, [%4];\n}"
               ::"r"(slot), "r"(SB + OFF_RSTD + w * 288), "l"(src), "l"(src + 128), "r"(bar) : "memory");
}
struct Attn {
  uint32_t lo[24], hi[24], ha[16], hslot;
  float c[8][4], rstd[2];
  float2 rk[3];
  __device__ __forceinline__ void A(const float (&acc)[96], Pipe& M, int w, int wp, int r, uint4* halo_out) {
    const int lane = M.lane();
    M.signal_loader();
#pragma unroll
    for (int nb = 8; nb < 24; nb++) hi[nb] = pack_bf16(acc[4 * nb + 2], acc[4 * nb + 3]);
    hslot = M.ahead(3);
    const uint32_t hbuf = hslot + wp * 2048 + lane * 16;
#pragma unroll
    for (int nb = 16; nb < 24; nb++) hi[nb] = movm(hi[nb]);
    if (wp == 3) {
      if (r < 15) {
        const uint32_t rh = lds32(SB + OFF_RSTD + (w * 72 + 64 + (lane & 7)) * 4);
#pragma unroll
        for (int p = 0; p < 4; p++) halo_out[p * 32 + lane] = make_uint4(hi[8 + 4 * p] ? hi[8 + 4 * p] : 0x8000u, hi[9 + 4 * p], hi[10 + 4 * p], hi[11 + 4 * p]);
        if (lane < 8) reinterpret_cast<uint32_t*>(halo_out + 128)[lane] = rh ? rh : 0x80000000u;
      }
    } else {
#pragma unroll
      for (int p = 0; p < 4; p++)
        asm volatile("st.shared.v4.b32 [%0], {%1,%2,%3,%4};" ::"r"(hbuf + 2048 + p * 512), "r"(hi[8 + 4 * p]), "r"(hi[9 + 4 * p]), "r"(hi[10 + 4 * p]), "r"(hi[11 + 4 * p]) : "memory");
      __syncwarp();
      arrive_n(SB + BAR_HALO + w * 8, M.l0);
    }
#pragma unroll
    for (int nb = 23; nb >= 0; nb--) {
      asm volatile("cvt.rn.bf16x2.f32 %0, %1, %2;" : "=r"(lo[nb]) : "f"(acc[4 * nb + 1]), "f"(acc[4 * nb]));
      if (nb < 8) asm volatile("cvt.rn.bf16x2.f32 %0, %1, %2;" : "=r"(hi[nb]) : "f"(acc[4 * nb + 3]), "f"(acc[4 * nb + 2]));
      if (nb >= 16) lo[nb] = movm(lo[nb]);
    }
  }
  __device__ __forceinline__ void B(int w, int wp, int lane, uint32_t hph) {
    own_rstd(w, wp, lane, rstd);
    mbar_spin(SB + BAR_HALO + w * 8, hph);
#pragma unroll
    for (int p = 0; p < 4; p++)
      asm volatile("ld.shared.v4.b32 {%0,%1,%2,%3}, [%4];" : "=r"(ha[4 * p]), "=r"(ha[4 * p + 1]), "=r"(ha[4 * p + 2]), "=r"(ha[4 * p + 3]) : "r"(hslot + wp * 2048 + lane * 16 + p * 512) : "memory");
#pragma unroll
    for (int u = 0; u < 3; u++) rk[u] = lds64(SB + OFF_RSTD + (w * 72 + wp * 16 + u * 8 + 2 * (lane & 3)) * 4);
  }
  __device__ __forceinline__ void C(int wp, int r, int lane, uint32_t zero) {
    const int g = lane >> 2, q = lane & 3;
    const bool nohalo = (wp == 0) && (r == 0);
    const bool up0 = 2 * q > g, up1 = 2 * q + 1 > g;
    const float sc = 0.17677669529663687f * 1.4426950408889634f;
    const float kx0 = up0 ? rk[0].x : rk[1].x, kx1 = up1 ? rk[0].y : rk[1].y;
    const float ky0 = up0 ? rk[1].x : rk[2].x, ky1 = up1 ? rk[1].y : rk[2].y;
    const float fx = rstd[0] * sc, fy = rstd[1] * sc;
    float sm[2][4] = {}, s0[2][4] = {}, s1[2][4] = {};
#pragma unroll
    for (int ks = 0; ks < 2; ks++)
#pragma unroll
      for (int h = 0; h < 2; h++) {
        const int a = 4 * h + 2 * ks;
        mma16(s0[h], lo[a], hi[a], lo[a + 1], hi[a + 1], lo[8 + a], lo[9 + a]);
        mma16(s1[h], lo[a], hi[a], lo[a + 1], hi[a + 1], hi[8 + a], hi[9 + a]);
      }
#pragma unroll
    for (int u = 0; u < 4; u++) { const int a = 4 * (u & 1) + (u & 2); mma16(sm[u & 1], lo[a], hi[a], lo[a + 1], hi[a + 1], ha[a], ha[a + 1]); }
    uint32_t pf[2][4];
    const uint32_t um = (up0 ? 0xffffu : 0u) | (up1 ? 0xffff0000u : 0u);
#pragma unroll
    for (int h = 0; h < 2; h++) {
      if (nohalo) { sm[h][0] = -INFINITY; sm[h][1] = -INFINITY; }
      float x0 = (up0 ? sm[h][0] : s0[h][0]) * (kx0 * fx), x1 = (up1 ? sm[h][1] : s0[h][1]) * (kx1 * fx);
      float y0 = (up0 ? s0[h][2] : s1[h][2]) * (ky0 * fy), y1 = (up1 ? s0[h][3] : s1[h][3]) * (ky1 * fy);
      float mx = fmaxf(x0, x1), my = fmaxf(y0, y1);
      mx = fmaxf(mx, __shfl_xor_sync(~0u, mx, 1)); my = fmaxf(my, __shfl_xor_sync(~0u, my, 1));
      mx = fmaxf(mx, __shfl_xor_sync(~0u, mx, 2)); my = fmaxf(my, __shfl_xor_sync(~0u, my, 2));
      x0 = ex2(x0 - mx); x1 = ex2(x1 - mx); y0 = ex2(y0 - my); y1 = ex2(y1 - my);
      float sx = x0 + x1, sy = y0 + y1;
      x0 *= kx0; x1 *= kx1; y0 *= ky0; y1 *= ky1;
      sx += __shfl_xor_sync(~0u, sx, 1); sy += __shfl_xor_sync(~0u, sy, 1);
      sx += __shfl_xor_sync(~0u, sx, 2); sy += __shfl_xor_sync(~0u, sy, 2);
      sx = rcp(sx); sy = rcp(sy);
      x0 *= sx; x1 *= sx; y0 *= sy; y1 *= sy;
      const uint32_t px = pack_bf16(x0, x1), py = pack_bf16(y0, y1);
      pf[h][0] = px & um; pf[h][1] = px & ~um; pf[h][2] = py & um; pf[h][3] = py & ~um;
    }
#pragma unroll
    for (int u = 0; u < 4; u++) {
#pragma unroll
      for (int e = 0; e < 4; e++) { c[2 * u][e] = 0.f; c[2 * u + 1][e] = 0.f; }
      mma8(c[2 * u], ha[8 + 2 * u], ha[9 + 2 * u], pf[u >> 1][0]);
      mma8(c[2 * u + 1], lo[16 + 2 * u], lo[17 + 2 * u], pf[u >> 1][2]);
    }
#pragma unroll
    for (int u = 0; u < 4; u++) {
      mma8(c[2 * u], lo[16 + 2 * u], lo[17 + 2 * u], pf[u >> 1][1]);
      mma8(c[2 * u + 1], hi[16 + 2 * u], hi[17 + 2 * u], pf[u >> 1][3]);
    }
    uint32_t dep = 0;
#pragma unroll
    for (int u = 0; u < 8; u++) dep |= __float_as_uint(c[u][0]);
    asm volatile("bar.sync %0, 256;" ::"r"(3 + (dep & zero)) : "memory");
  }
  __device__ __forceinline__ void E(Pipe& M, bool urgent) {
#pragma unroll
    for (int u = 0; u < 4; u++)
      asm volatile("stmatrix.sync.aligned.m8n8.x4.trans.shared.b16 [%0], {%1, %2, %3, %4};" ::"r"(box_addr(hslot, M.bo, u)),
                   "r"(pack_bf16(c[2 * u][0], c[2 * u][1])), "r"(pack_bf16(c[2 * u + 1][0], c[2 * u + 1][1])),
                   "r"(pack_bf16(c[2 * u][2], c[2 * u][3])), "r"(pack_bf16(c[2 * u + 1][2], c[2 * u + 1][3])) : "memory");
    if (urgent) M.signal_loader(); else M.signal_server(1);
  }
};

__device__ __forceinline__ void epi_res(const float (&acc)[64], const float (&pre)[64], float sc0, float sc1, uint32_t (&xr)[32], Pipe& M, int wp) {
  Pipe T = M;
  const uint32_t buf0 = T.take(), buf1 = T.take();
#pragma unroll
  for (int u = 0; u < 8; u++) {
#pragma unroll
    for (int nb = 2 * u; nb < 2 * u + 2; nb++) {
      xr[2 * nb] = pack_bf16(fmaf(acc[4 * nb], sc0, pre[2 * nb]), fmaf(acc[4 * nb + 1], sc0, pre[32 + 2 * nb]));
      xr[2 * nb + 1] = pack_bf16(fmaf(acc[4 * nb + 2], sc1, pre[2 * nb + 1]), fmaf(acc[4 * nb + 3], sc1, pre[33 + 2 * nb]));
    }
    stsm4(box_addr(u < 4 ? buf0 : buf1, M.bo, u & 3), xr[4 * u], xr[4 * u + 1], xr[4 * u + 2], xr[4 * u + 3]);
    if (u == 3) M.signal_loader();
  }
  __syncwarp();
  arrive_n(SB + BAR_STG2 + M.w * 8, M.l0);
  fence_async_smem();
  wg_bar(M.w);
}
__device__ __forceinline__ void presum(float (&pre)[64], int lane, float usebias) {
  const uint32_t bias = SB + OFF_VEC + (lane & 3) * 8;
#pragma unroll
  for (int nb = 0; nb < 16; nb++) {
    const float2 b = lds64(bias + nb * 32);
#pragma unroll
    for (int u = 2 * nb; u < 2 * nb + 2; u++) {
      const uint32_t v = __float_as_uint(pre[u]);
      pre[32 + u] = fmaf(b.y, usebias, bf_hi(v)); pre[u] = fmaf(b.x, usebias, bf_lo(v));
    }
  }
}
template <int S, int Q> __device__ __forceinline__ void pack_relu(uint32_t (&o)[Q], const float (&acc)[S]) {
#pragma unroll
  for (int u = 0; u < Q; u++) asm("cvt.rn.relu.bf16x2.f32 %0, %1, %2;" : "=r"(o[u]) : "f"(acc[2 * u + 1]), "f"(acc[2 * u]));
}
__device__ __forceinline__ uint32_t sq_bf16x2(uint32_t a) { uint32_t d; asm("mul.rn.bf16x2 %0, %1, %1;" : "=r"(d) : "r"(a)); return d; }
template <int Q> __device__ __forceinline__ void ffn_stage(const uint32_t (&o)[Q], int i, Pipe& M) {
  i -= M.w;
  if (i == 1 || i == 4 || i == 7 || (Q == 64 && i == 10)) {
    const uint32_t buf = M.wait_ahead(2 - M.w);
#pragma unroll
    for (int b = 0; b < Q / 16; b++)
      if (i == 3 * b + 1) {
#pragma unroll
        for (int u = 4 * b; u < 4 * b + 4; u++)
          stsm4(box_addr(buf, M.bo, u & 3), sq_bf16x2(o[4 * u]), sq_bf16x2(o[4 * u + 1]), sq_bf16x2(o[4 * u + 2]), sq_bf16x2(o[4 * u + 3]));
      }
    M.signal_server((i & 1) ^ (Q == 64));
  }
}

__device__ __forceinline__ void wait_flags(const uint8_t* f, uint32_t tag, int lane) {
  const uint32_t t4 = (tag & 0xff) * 0x01010101u;
  const uint32_t* fp = reinterpret_cast<const uint32_t*>(f) + (lane & 3);
  while (__any_sync(~0u, __vsub4(ld_relaxed(fp), t4) & 0x80808080u)) {}
  asm volatile("fence.acquire.gpu;\nfence.proxy.async.global;" ::: "memory");
}
__device__ __forceinline__ uint32_t get_epoch() { mbar_spin(SB + BAR_EPOCH, 0); return __shfl_sync(~0u, lds32(SB + OFF_HOLD + 8), 0); }
__device__ __forceinline__ void aloader(const Params& P, const Ptrs& Q, int bid, int r, int j, int lane, int w, uint32_t e, uint32_t epoch) {
  const uint32_t abase = SB + OFF_A + w * NA * 8192, fbase = SB + BAR_FULLA + w * NA * 8, ebase = SB + BAR_EMPTYA + w * NA * 8;
  uint32_t slot = NPRO, ph = 1, nst = 0, hph = 0, npace = 0;
  int t = -1, kind = -1, a0 = 0, a1 = 0;
  const CUtensorMap* tmA = nullptr;
  uint64_t pol = 0;
  uint4* hin = Q.s->halo[0][0] + (r * 16 + j * 2 + w - 16) * 136;
  uint32_t* const pace = Q.s->pace[r >> 1];
  const uint8_t* const flags = Q.s->flags[r >> 1][w];
  auto adv = [&] { if (++slot == NA) { slot = 0; ph ^= 1; } };
#pragma unroll 1
  for (int g = NPRO; g <= NSTEP; g++) {
    const uint32_t cur = e;
    e = c_sched.v[j][g + 1];
    if (!(cur & E_RARE)) {
      if (cur & E_HAND) { mbar_spin(ebase + slot * 8, ph); e_arrive(fbase + slot * 8, 1); adv(); }
    } else {
      if (cur & F_NEW) {
        t++; kind = kind == 5 ? 0 : kind + 1;
        const bool narrow = kind == 2 || kind == 5;
        static_assert(TM_XIN == 0 && TM_X == 1 && TM_XA == 2 && TM_O == 3 && TM_H == 4, "map order");
        tmA = &P.tm[t < 2 ? 0 : (0x422311 >> (4 * kind)) & 15];
        pol = ((AEF >> t) & 1) ? 0x12F0000000000000ull : 0x1000000000000000ull;
        a0 = narrow ? 0 : w * 1024; a1 = narrow ? r * 128 + w * 64 : r * 64;
      }
      const bool xo = cur & E_XPUB0;
      uint32_t s = slot;
      if (cur & (E_HAND | E_ATTN | E_XPUB0)) {
        if (cur & E_KEEP) e_arrive(ebase + slot * 8, 4);
#pragma unroll 1
        for (int u = xo ? 0 : 1; u < 2; u++) { mbar_wait(ebase + slot * 8, ph); e_arrive(fbase + slot * 8, 1); adv(); }
      }
      uint32_t hold = 0;
      if ((xo && t < 12) || (cur & F_GATH)) {
        uint32_t v;
        do v = ld_relaxed(pace + npace + (lane & 15)); while (__any_sync(~0u, (v ^ (epoch * 16 + t - 1)) & 31));
        npace ^= 16;
        hold = min(__reduce_max_sync(~0u, (int)(v - __shfl_sync(~0u, v, bid & 15))), 4000) * 27 >> 4;
        asm volatile("st.shared.b32 [%0], %1;" ::"r"(SB + OFF_HOLD + w * 4), "r"(hold) : "memory");
      }
      if (cur & (E_ATTN | E_XPUB0)) {
        const uint32_t s2 = s == NA - 1 ? 0 : s + 1;
        constexpr int NP = NPREPX > NPREPO ? NPREPX : NPREPO;
        uint32_t pf[NP + 1], pk[NP + 1];
        const int np = t == 12 ? 0 : (xo ? NPREPX : NPREPO);
#pragma unroll
        for (int u = 0; u < NP; u++) {
          pf[u] = slot; pk[u] = a0 + sched_k(c_sched.v[j][g + 1 + xo + u]);
          if (u < np) {
            if (u == np - 1) mbar_spin(ebase + slot * 8, ph);
            adv();
          }
        }
        mbar_wait(SB + BAR_STG + w * 8, nst & 1);
        nst++;
        LT(0);
        const uint32_t c1 = clock32();
        e_store(tmA, a0 + sched_k(cur), a1, abase + s * 8192);
        if (xo) {
          mbar_spin(SB + BAR_STG2 + w * 8, ~t & 1);
          e_store(tmA, a0 + sched_k(cur) + 64, a1, abase + s2 * 8192);
        } else e_arrive(SB + BAR_OWN + w * 8, 1);
        LT(1);
        if (t == 12) break;
        spin_until(c1 + hold + (xo ? SDELAY : SDELAYO));
        LT(2);
#pragma unroll
        for (int u = 0; u < NP; u++)
          if (u < np) e_load(abase + pf[u] * 8192, tmA, pk[u], a1, fbase + pf[u] * 8);
        LT(5);
      }
      if (cur & E_SIG) {
        e_arrive(SB + BAR_SRV + w * 16, 4);
      }
      if (cur & E_REL) bulk_wait_all();
      if (cur & E_HALO) {
        mbar_spin(SB + BAR_STG + w * 8, nst & 1);
        nst++;
        const uint32_t hs = abase + (slot >= 3 ? slot - 3 : slot + 3) * 8192, ad = hs + lane * 32 + (lane & 4) * 4;
        if (r == 0) {
#pragma unroll
          for (int p = 0; p < 4; p++) sts128(hs + lane * 16 + p * 512, 0, 0, 0, 0);
          asm volatile("st.shared.b32 [%0], %1;" ::"r"(SB + OFF_RSTD + w * 288 + (lane & 7) * 4), "r"(0x3f800000) : "memory");
        } else {
          spin_until(clock32() + HDELAY);
          do {
            halo_fetch(hs, w, hin, SB + BAR_SPEC + 80 + w * 8);
            mbar_spin(SB + BAR_SPEC + 80 + w * 8, hph);
            hph ^= 1;
          } while (__any_sync(~0u, min(min(lds32(ad), lds32(ad + 1024)), lds32(SB + OFF_RSTD + w * 288)) == 0));
        }
        e_arrive(SB + BAR_HALO + w * 8, 1);
      }
      if ((cur & E_REL) && (kind == 1 || kind == 2) && r > 0) {
        uint4* hz = hin + lane;
        hin += 256 * 136;
#pragma unroll
        for (int p = 0; p < 4; p++) hz[p * 32] = make_uint4(0, 0, 0, 0);
        if (lane < 2) hz[128] = make_uint4(0, 0, 0, 0);
      }
      if (cur & E_WAIT) {
        wait_flags(flags + ((cur & E_PART1) ? 16 : 0), epoch * 16 + t, lane);
      }
    }
    if (!(cur & (F_AUG | F_NOA))) {
      mbar_wait(ebase + slot * 8, ph);
      e_load(abase + slot * 8192, tmA, a0 + sched_k(cur), a1, fbase + slot * 8, pol);
      adv();
      if ((cur & F_STAMP) && w == 0) {
        mbar_spin(SB + BAR_EMPTYB + ((g - 6) & 7) * 8, ((g - 6) >> 3) & 1);
        uint32_t stamp;
        asm volatile("mov.u32 %0, %%globaltimer_lo;" : "=r"(stamp));
        asm volatile("st.relaxed.gpu.global.u32 [%0], %1;" ::"l"(pace + npace + (bid & 15)), "r"((stamp & ~31u) | ((epoch * 16 + t) & 31)) : "memory");
      }
    }
  }
  bulk_wait_all();
}

__device__ __forceinline__ void bloader(const Params& P, const Ptrs& Q, bool aux, int j, int lane, uint32_t e, uint32_t epoch) {
  const uint32_t* const sched = c_sched.v[aux ? 8 : j];
  int kind = -1, c2 = 0, c3 = 0, na = 0;
  const CUtensorMap* tmB = nullptr;
  uint32_t sph = 0, efm = aux ? 0 : BEF * 2;
  uint64_t pol = 0;
#pragma unroll 1
  for (int g = aux ? 8 + (j & 1) : NPRO; g < (aux ? NSTEP_AUX : NSTEP); g += 1 + aux) {
    const uint32_t cur = e;
    e = sched[g + 1 + aux];
    if (cur & F_NEW) {
      kind = kind == 5 ? 0 : kind + ((cur >> 29) & 3);
      static_assert(TM_WQKV == 5 && TM_WO == 6 && TM_W1A == 7 && TM_W1B == 8 && TM_W2 == 9, "map order");
      tmB = &P.tm[(0x978655 >> (4 * kind)) & 15];
      efm >>= 1;
      pol = (efm & 1) ? 0x12F0000000000000ull : 0x1000000000000000ull;
      na = (0x243233 >> (4 * kind)) & 15;
      c2 = ((0x277200 >> (4 * kind)) & 15) * j + (kind == 4 ? 3 : 0);
      c3 = kind <= 1 ? kind * 8 + j : 0;
    }
    const int need = g - (int)((cur >> 5) & 15);
    const uint32_t dst = SB + OFF_B + (cur & 31) * 8192, bar = SB + BAR_FULLB + (g & 7) * 8;
    mbar_wait(SB + BAR_EMPTYB + (need & 7) * 8, (need >> 3) & 1);
    if (!(cur & F_AUG)) {
      asm volatile("{\n.reg .pred p;\nelect.sync _|p, 0xffffffff;\n@p mbarrier.arrive.expect_tx.shared::cta.b64 _, [%2], %7;\n"
                   "@p cp.async.bulk.tensor.4d.shared::cluster.global.mbarrier::complete_tx::bytes.L2::cache_hint [%0], [%1, {%3, %4, %5, %6}], [%2], %8;\n}"
                   ::"r"(dst), "l"(tmB), "r"(bar), "r"(0), "r"(sched_k(cur)), "r"(c2), "r"(c3), "r"(na * 8192), "l"(pol) : "memory");
    } else {
      const bool chk = g < NSTEP / 2;
      const uint32_t b2 = chk ? SB + BAR_AUG : bar, ad = dst + lane * 16 + (lane >> 3) * 4;
      while (true) {
        asm volatile("{\n.reg .pred p;\nelect.sync _|p, 0xffffffff;\n@p mbarrier.arrive.expect_tx.shared::cta.b64 _, [%2], 4096;\n"
                     "@p cp.async.bulk.shared::cluster.global.mbarrier::complete_tx::bytes [%0], [%1], 4096, [%2];\n}"
                     ::"r"(dst), "l"(Q.s->aug[epoch & 1][(kind - (kind >= 3)) * 8 + j]), "r"(b2) : "memory");
        if (!chk) break;
        mbar_spin(b2, sph);
        sph ^= 1;
        uint32_t mn = ~0u;
#pragma unroll
        for (int u = 0; u < 8; u++) mn = min(mn, lds32(ad + u * 512));
        if (!__any_sync(~0u, mn == 0)) { e_arrive(bar, 1); break; }
      }
      __syncwarp();
    }
  }
}

constexpr uint32_t job_slots(int layer) {
  const int pos[10] = {11, 26, 63, 73, 77, 81, 92, 96, 100, 104};
  uint32_t v = 0;
  for (int m = 0; m < 10; m++) v |= (uint32_t)((layer * 148 + pos[m]) % NA) << (3 * m);
  return v;
}
constexpr uint32_t JOB_SLOTS0 = job_slots(0), JOB_SLOTS1 = job_slots(1);
__device__ __forceinline__ void server(const Params& P, const Ptrs& Q, int bid, int r, int j, int lane, uint32_t epoch) {
  if (CPF) spin_until(clock32() + CPF);
  epoch += __shfl_sync(~0u, c_sched.v[j][lane < 18 ? lane * 16 : 0] >> 31, 0);
  {
    const uint2 b = reinterpret_cast<const uint2*>(Q.b2 + j * 128)[lane];
    sts128(SB + OFF_VEC + lane * 16, b.x << 16, b.x & 0xffff0000u, b.y << 16, b.y & 0xffff0000u);
  }
  int hl = 0;
  uint32_t fph = 0, pend = SB + BAR_DUMMY3;
#pragma unroll 1
  for (int n = 0; n < 20; n++) {
    const int layer = n >= 10, m = n - 10 * layer;
    const bool stat = m == 0 || m == 2;
    const uint32_t slot = ((layer ? JOB_SLOTS1 : JOB_SLOTS0) >> (m * 3)) & 7;
    auto fetch = [&](int w) {
      asm volatile("{\n.reg .pred p;\nelect.sync _|p, 0xffffffff;\n@p mbarrier.arrive.expect_tx.shared::cta.b64 _, [%2], 4096;\n"
                   "@p cp.async.bulk.shared::cluster.global.mbarrier::complete_tx::bytes [%0], [%1], 4096, [%2];\n}"
                   ::"r"(SB + OFF_A + (w * NA + slot) * 8192), "l"(&Q.s->stats[hl][r * 32 + w * 16][0][0]), "r"(SB + BAR_SPEC + 64 + w * 8) : "memory");
    };
#pragma unroll 1
    for (int w = 0; w < 2; w++) {
      mbar_spin(SB + BAR_SRV + w * 16 + (n & 1) * 8, (n >> 1) & 1);
      if (stat) fetch(w);
      else {
        e_store(&P.tm[m == 1 ? TM_O : TM_H], m == 1 ? j * 64 : 448 * j + (m - 3) * 64, r * 128 + w * 64, SB + OFF_A + (w * NA + slot) * 8192);
        bulk_wait_read<1>();
        e_arrive(pend, 4);
        pend = SB + BAR_EMPTYA + (w * NA + slot) * 8;
      }
    }
    if (stat) {
#pragma unroll 1
      for (int w = 0; w < 2; w++) {
        const uint32_t src = SB + OFF_A + (w * NA + slot) * 8192 + (lane >> 1) * 256 + ((lane >> 1) & 7) * 32 + (lane & 1) * 16;
        float ms[2], md[2], mq[2], m0[2];
        while (true) {
          mbar_spin(SB + BAR_SPEC + 64 + w * 8, (fph >> w) & 1);
          fph ^= 1u << w;
          uint32_t bad = 0;
          ms[0] = ms[1] = md[0] = md[1] = mq[0] = mq[1] = m0[0] = m0[1] = 0.f;
#pragma unroll 1
          for (int p = 0; p < 8; p += 2) {
            const float4 v2[2] = {lds128(src ^ (p * 32)), lds128(src ^ (p * 32) ^ 32)};
            if (p == 0) { m0[0] = v2[0].x; m0[1] = v2[0].z; }
#pragma unroll
            for (int z = 0; z < 2; z++) {
              const float4 v = v2[z];
              const float a = v.x - m0[0], b = v.z - m0[1];
              bad |= __float_as_uint(v.y) ^ epoch;
              ms[0] += a; md[0] = fmaf(a, a, md[0]); mq[0] += __uint_as_float(__float_as_uint(v.y) & ~63u);
              ms[1] += b; md[1] = fmaf(b, b, md[1]); mq[1] += v.w;
            }
          }
          if (!__any_sync(~0u, bad & 63)) break;
          fetch(w);
          __syncwarp();
        }
        e_arrive(SB + BAR_EMPTYA + (w * NA + slot) * 8, 4);
        const int row = (lane >> 3) * 16 + (lane & 7);
#pragma unroll
        for (int z = 0; z < 2; z++) {
          const float d = ms[z] * 0.125f;
          asm volatile("st.shared.f32 [%0], %1;" ::"r"(SB + OFF_MEAN + (w * 64 + row + z * 8) * 4), "f"(m0[z] + d) : "memory");
          asm volatile("st.shared.f32 [%0], %1;" ::"r"(SB + OFF_RSTD + (w * 72 + 8 + row + z * 8) * 4), "f"(rsq(fmaf(mq[z], 1.f / 1024.f, fmaxf(fmaf(md[z], 0.125f, -d * d), 0.f)) + 1e-5f)) : "memory");
        }
        e_arrive(SB + BAR_STAT + w * 8, 8);
      }
    }
    if (stat && n != 12) {
#pragma unroll 1
      for (int u = 0; u < (m ? 2 : 3); u++) {
        const uint32_t pitch = u == 2 ? 448 : 128;
        uint4* p = reinterpret_cast<uint4*>(u == 2 ? Q.s->h : (m ? Q.out : Q.s->x)) + (u == 2 ? 64 + j * 8 : j * 16 + u * 8) + ((r * 128 + (lane >> 3)) * pitch + (lane & 7));
#pragma unroll 1
        for (int k = 0; k < 32 / FUN; k++) {
#pragma unroll
          for (int z = 0; z < FUN; z++) {
            *p = make_uint4(~0u, ~0u, ~0u, ~0u);
            p += 4 * pitch;
            asm volatile("" : "+l"(p));
          }
        }
      }
      __syncwarp();
    }
    if ((0x222 >> m) & 1) {
      bulk_wait_all();
      e_arrive(pend, 4);
      pend = SB + BAR_DUMMY3;
      if (lane < 2) st_release8(&Q.s->flags[r >> 1][lane][(bid & 15) + (m == 9 ? 16 : 0)], epoch * 16 + layer * 6 + (m == 1 ? 2 : 5));
      __syncwarp();
    }
    hl += stat;
  }
}

__device__ __forceinline__ void aux_math(const Ptrs& Q, int bid, int jj, int warp, int lane) {
  const int g = lane >> 2, q = lane & 3, c0 = (warp & 3) * 2;
  uint32_t st = warp >> 2, bf[16][4] = {};
  const uint32_t ad0 = SB + ((lane >> 4) * 8 + (lane & 7)) * 128 + (((c0 + ((lane >> 3) & 1)) ^ (lane & 7)) << 4);
#pragma unroll 1
  for (int t = 0; t < 4; t++) {
    float acc[4][4] = {};
    uint32_t bias[8];
#pragma unroll
    for (int a = 0; a < 8; a++) bias[a] = t >= 2 ? reinterpret_cast<const uint32_t*>(Q.b1 + 448 * jj + (t - 2) * 192 + c0 * 8)[(a >> 1) * 32 + (a & 1) * 4 + q] : 0u;
#pragma unroll 1
    for (int i = 0; i < 16; i++, st += 2) {
      const uint32_t ad = ad0 + (c_sched.v[8][st] & 31) * 8192;
      mbar_spin(SB + BAR_FULLB + (st & 7) * 8, (st >> 3) & 1);
#pragma unroll
      for (int u = 0; u < 16; u++)
        asm volatile("{\n.reg .pred p;\nsetp.ne.u32 p, %5, 0;\n@p ldmatrix.sync.aligned.m8n8.x4.trans.shared.b16 {%0,%1,%2,%3}, [%4];\n}"
                     : "+r"(bf[u][0]), "+r"(bf[u][1]), "+r"(bf[u][2]), "+r"(bf[u][3])
                     : "r"(ad + (u & 3) * 8192 + (u >> 2) * 2048), "r"((u & 3) != 3 || t == 3 ? 1 : 0) : "memory");
      __syncwarp();
      e_arrive(SB + BAR_EMPTYB + (st & 7) * 8, 2);
#pragma unroll
      for (int u = 0; u < 16; u++) mma16(acc[u & 3], bf[u][0], bf[u][1], bf[u][2], bf[u][3], 0x3F803F80u, 0x3F803F80u);
    }
    const uint32_t epoch = lds32(SB + OFF_HOLD + 8);
    const uint32_t o = (t * 8 + jj) * 1024 + g * 32 + ((c0 ^ g) << 2) + q + (epoch & 1) * 32768;
    uint32_t *const p0 = Q.s->aug[0][0] + o, *const p1 = Q.s->aug[0][0] + (o ^ 4);
#pragma unroll
    for (int a = 0; a < 8; a++) {
      const float u = acc[a >> 1][(a & 1) * 2];
      uint32_t h = movm(pack_bf16(u, u - bf_round(u)));
      if (g >= 6) h = bias[a];
      ((a & 1) ? p1 : p0)[(a >> 1) * 256] = h ? h : 0x8000u;
    }
    uint4* const z = reinterpret_cast<uint4*>(Q.s->aug[~epoch & 1][t * 8 + jj]) + (threadIdx.x & 127);
    z[0] = z[128] = make_uint4(0, 0, 0, 0);
  }
}

template <bool BYSM> __global__ void __launch_bounds__(NTHREADS, 1) mega_kernel(const __grid_constant__ Ptrs Q, const __grid_constant__ Params P) {
  extern __shared__ __align__(1024) uint8_t smem_raw[];
  constexpr uint32_t sb = SB;
  const uint32_t centry = clock32();
  const int warp = __shfl_sync(~0u, threadIdx.x >> 5, 0), lane = threadIdx.x & 31;
  const int bid = BYSM ? work_id() : blockIdx.x;
  const bool aux = bid >= NMAIN;
  const int r = ((bid >> 4) << 1) | (bid & 1), j = (aux ? bid * 2 : bid >> 1) & 7;
  PRO(0);
  {
    const uint32_t b = sb + OFF_BAR + warp * 48, cnt = warp < 6 ? 1 : (warp < 10 ? 4 : 8);
    asm volatile("{\n.reg .pred p;\nelect.sync _|p, 0xffffffff;\n@p mbarrier.init.shared::cta.b64 [%0], %1;\n@p mbarrier.init.shared::cta.b64 [%0 + 8], %1;\n"
                 "@p mbarrier.init.shared::cta.b64 [%0 + 16], %1;\n@p mbarrier.init.shared::cta.b64 [%0 + 24], %1;\n"
                 "@p mbarrier.init.shared::cta.b64 [%0 + 32], %1;\n@p mbarrier.init.shared::cta.b64 [%0 + 40], %1;\nfence.mbarrier_init.release.cluster;\n}"
                 ::"r"(b), "r"(cnt) : "memory");
  }
  __syncthreads();
  {
    static_assert(NPRO == 4 && ROUND0 == 0, "prologue stages");
    const int st = ((11 - warp) * (aux ? 32 : 11)) >> 5, op = aux ? (st < 8) * 2 : 11 - warp - 3 * st, sd = aux ? st >> STGX : (op == 2 ? st : st & 2);
    const uint32_t bar0 = sb + OFF_BAR + (op * 6 + st) * 8;
    const int kc = aux ? (st >> 1) * 64 : (st & 2 ? (ROUND1 >> (4 * j)) & 15 : 0) * 128 + (st & 1) * 64;
    spin_until(centry + (sd ? STG0 + sd * STG1 : 0));
    if (op == 2) {
      asm volatile("{\n.reg .pred p;\nelect.sync _|p, 0xffffffff;\n@p mbarrier.arrive.expect_tx.shared::cta.b64 _, [%2], 24576;\n"
                   "@p cp.async.bulk.tensor.4d.shared::cluster.global.mbarrier::complete_tx::bytes [%0], [%1, {%3, %4, %3, %5}], [%2];\n}"
                   ::"r"(sb + OFF_B + (aux ? (st & 1) * 114688 + (st >> 1) * 24576 : (st + 1) * 24576)), "l"(&P.tm[TM_WQKV]), "r"(bar0), "r"(0), "r"(kc), "r"(j + (st & aux)) : "memory");
    } else if (!aux) e_load(sb + OFF_A + (op * 6 + st) * 8192, &P.tm[TM_XIN], op * 1024 + kc, r * 64, bar0);
    PRO(1);
    asm volatile("prefetch.tensormap [%0];" ::"l"(&P.tm[warp]) : "memory");
  }
  if (warp >= 8) {
    asm volatile("setmaxnreg.dec.sync.aligned.u32 24;");
    if (warp == 11) {
      if (smem_u32(smem_raw) != SB) __trap();
      const uint32_t epoch = __shfl_sync(~0u, ld_relaxed(&Q.s->epoch[bid]) + 1, 0);
      Q.s->epoch[bid] = epoch;
      asm volatile("st.shared.b32 [%0], %1;" ::"r"(sb + OFF_HOLD + 8), "r"(epoch) : "memory");
      e_arrive(sb + BAR_EPOCH, 1);
      PRO(2);
      if (!aux) server(P, Q, bid, r, j, lane, epoch);
    } else {
      const uint32_t e = c_sched.v[aux ? 8 : j][aux ? warp : NPRO];
      spin_until(centry + STGL + (e >> 31));
      PRO(2);
      const uint32_t epoch = get_epoch();
      PRO(3);
      if (warp <= 8 + aux) bloader(P, Q, aux, j + warp - 8, lane, e, epoch);
      else if (!aux) aloader(P, Q, bid, r, j, lane, warp - 9, e, epoch);
    }
  } else if (aux) aux_math(Q, bid, j + (warp >> 2), warp, lane);
  else {
    asm volatile("setmaxnreg.inc.sync.aligned.u32 240;");
    const int w = warp >> 2, wp = warp & 3;
    {
      uint32_t xr[32];
#pragma unroll
      for (int u = 0; u < 32; u++) xr[u] = 0;
      Pipe M;
      M.p = 0; M.g8 = 0; M.a8 = w * NA * 8; M.aph = 0; M.tph = 0; M.aend = (w + 1) * NA * 8;
      M.curB = M.curA = M.prevB = M.prevA = M.sph = 0; M.w = w; M.l0 = lane == 0;
      M.bo = (wp * 16 + (lane & 15)) * 128 + (((lane >> 4) ^ (lane & 7)) << 4);
      M.so = __shfl_sync(~0u, SB + OFF_A + wp * 2048 + lane * 32 + (lane >> 2) * 4, lane);
      M.bo = __shfl_sync(~0u, M.bo, lane);
      auto nop = [](int) {};
      const uint32_t zero = gridDim.y - 1;
      PROF_T(w, 0, 3);
      if (STARTC) spin_until(centry + STARTC);
#pragma unroll 1
      for (int hl = 0; hl < 4; hl++) {
        const int t0 = hl * 3;
        const bool ffn = hl & 1;
        float acc[96], acn[64];
        uint32_t au[2] = {0u, 0u};
        {
          const int d = hl ? 0 : ((OWNP * 2u) >> (4 * j)) & 15;
          auto own = [&](auto h, uint32_t dep = 0) {
#pragma unroll
            for (int u = 4 * h.v; u < 4 * h.v + 4; u++)
              asm volatile("ldmatrix.sync.aligned.m8n8.x4.shared.b16 {%0,%1,%2,%3}, [%4];" : "=r"(xr[4 * u]), "=r"(xr[4 * u + 1]), "=r"(xr[4 * u + 2]), "=r"(xr[4 * u + 3])
                           : "r"(box_addr(sb + OFF_A + M.a8 * 1024, M.bo + dep, u & 3)) : "memory");
          };
          M.begin<192>(acc, ffn ? 12 : 3, t0, [&](int) { if (hl + d == 0) own(IC<0>{}); });
          if (hl + d == 0) own(IC<1>{}, (xr[0] | xr[4] | xr[8] | xr[12]) & zero);
          float ss[2] = {0.f, 0.f}, sq[2] = {0.f, 0.f};
          auto part = [&](auto c0, auto n) {
#pragma unroll
            for (int v = 0; v < 4 * n.v; v++) {
              const int u = c0.v + v / n.v * 4 + v % n.v;
              float a, b;
              asm volatile("shl.b32 %0, %2, 16;\nand.b32 %1, %2, 0xffff0000;" : "=f"(a), "=f"(b) : "r"(xr[u]));
              ss[u & 1] += a + b; sq[u & 1] = fmaf(a, a, fmaf(b, b, sq[u & 1]));
            }
          };
          const uint64_t plan = hl ? PLAN1 : (d ? PLAN0 : PLANZ);
          auto todo = [&](int i) { uint64_t v; asm volatile("shr.u64 %0, %1, %2;" : "=l"(v) : "l"(plan), "r"((i + 1 - d) * 8)); return (uint32_t)v; };
          uint32_t m = todo(1);
          M.run<192, false>(acc, 1, 16, 1u << 10, 16 - (ffn ? LEAD3 : LEAD0), [&](int i, uint2 ok) {
           CT(0);
           if (m & 7) {
             if (m & 1) part(IC<0>{}, IC<2>{});
             if (m & 2) part(IC<2>{}, IC<2>{});
             if (m & 4) part(IC<16>{}, IC<1>{});
           }
           CT(1);
           M.ensure(ok);
           CT(3);
           M.validate(hl != 0, &P.tm[ffn ? TM_XA16 : TM_X16], w * 1024, r * 64, wp, j, [&] {
            if (m & 0xf8) {
              if (m & 128) { if (m & 1) own(IC<1>{}); else own(IC<0>{}); }
              if (m & 8) part(IC<17>{}, IC<1>{});
              if (m & 16) part(IC<18>{}, IC<1>{});
              if (m & 32) part(IC<19>{}, IC<1>{});
              if (m & 64) {
                const uint32_t epoch = lds32(sb + OFF_HOLD + 8);
#pragma unroll
                for (int o = 1; o < 4; o *= 2)
#pragma unroll
                  for (int z = 0; z < 2; z++) { ss[z] += __shfl_xor_sync(~0u, ss[z], o); sq[z] += __shfl_xor_sync(~0u, sq[z], o); }
                const float m0 = ss[0] * (1.f / 128.f), m1 = ss[1] * (1.f / 128.f);
                const int rowpair = r * 64 + w * 32 + wp * 8 + (M.lane() >> 2);
                if ((M.lane() & 3) == 0)
                  st_pkt(&Q.s->stats[hl][rowpair >> 1][j][rowpair & 1], __float_as_uint(m0), (__float_as_uint(fmaxf(fmaf(-ss[0], m0, sq[0]), 0.f)) & ~63u) | (epoch & 63),
                         __float_as_uint(m1), __float_as_uint(fmaxf(fmaf(-ss[1], m1, sq[1]), 0.f)));
              }
            }
            m = todo(i + 1);
            if (i == STATI) { mbar_spin(sb + BAR_STAT + w * 8, hl & 1); stats_fetch(w, wp, M.lane(), au); }
           });
           CT(4);
          });
          M.end<192, true>(acc, ffn ? 0 : 4, 15, au[0], au[1], t0);
          PROF_T(w, t0, 2);
        }
        if (!ffn) {
          Attn T;
#pragma unroll 1
          for (int wave = 0; wave < 2; wave++) {
            AP(9);
            uint4* const hp = Q.s->halo[0][0] + (uint32_t)(((hl + wave) * 256 + r * 16 + j * 2 + w) * 136);
            T.A(acc, M, w, wp, r, hp);
            AP(0);
            if (wave == 0) {
              M.begin<192, PACE2 & 1>(acc, 6, t0 + 1);
              M.run<192>(acc, 1, NH1, 4, -1, nop);
              T.B(w, wp, M.lane(), 0);
              M.drain();
            } else {
              M.begin<128, (PACE2 >> 1) & 1>(acn, 12, t0 + 2);
              M.run<128>(acn, 1, NH2, 4, -1, nop);
              T.B(w, wp, M.lane(), 1);
              M.drain();
#pragma unroll
              for (int z = 0; z < 64; z++) asm volatile("mov.b32 %0, %1;" : "=f"(acc[z]) : "f"(acn[z]));
#pragma unroll
              for (int z = 64; z < 96; z++) acc[z] = 0.f;
            }
            AP(2);
            T.C(wp, r, M.lane(), zero);
            AP(3);
            if (wave == 1) break;
            M.run<192>(acc, NH1, 16, 1u << 7, 16 - LEAD1, [&](int i) { if (i == NH1) T.E(M, false); });
            M.end<192, true>(acc, 4, 10, au[0], au[1], t0 + 1);
            PROF_T(w, t0 + 1, 2);
          }
#pragma unroll
          for (int z = 0; z < 64; z++) asm volatile("mov.b32 %0, %1;" : "=f"(acn[z]) : "f"(acc[z]));
          M.ensure(M.iss<128, false>(acn, false));
          T.E(M, true);
        } else {
          uint32_t pk[48], pk2[64];
          pack_relu(pk, acc);
          {
            float acc2[128];
            M.begin<256, (PACE2 >> 3) & 1>(acc2, 0, t0 + 1);
            M.run<256>(acc2, 1, 16, 0x248, 16 - LEAD4, [&](int i) { ffn_stage(pk, i, M); });
            M.end<256, true>(acc2, 0, 0, au[0], au[1], t0 + 1);
            pack_relu(pk2, acc2);
            PROF_T(w, t0 + 1, 2);
          }
          M.begin<128, (PACE2 >> 4) & 1>(acn, 2, t0 + 2);
          M.run<128>(acn, 1, 13, 0x1248, -1, [&](int i) { ffn_stage(pk2, i, M); });
        }
        {
          float pre[64], rstd[2] = {0.f, 0.f};
#pragma unroll
          for (int u = 0; u < 32; u++) { pre[u] = __uint_as_float(xr[u]); pre[32 + u] = 0.f; }
          const int ks = ffn ? 56 : 16, pause = ks - (ffn ? LEAD5 : LEAD2), vfrom = ffn ? 99 : 7;
          M.run<128>(acn, ffn ? 13 : NH2 + 1, ks, 0, pause, [&](int i) {
            if (i >= vfrom) {
              if (i == 7) mbar_spin(sb + BAR_OWN + w * 8, hl >> 1);
              M.validate(true, &P.tm[TM_O16], 0, r * 128 + w * 64, wp, j, [] {});
            }
          }, w ? (ffn ? (PRE5 ? PRE5 : pause) : (PRE2 ? PRE2 : pause)) : (ffn ? 20 : IPRE), [&](int) { presum(pre, M.lane(), ffn ? 1.f : 0.f); own_rstd(w, wp, M.lane(), rstd); });
          M.end<128, false>(acn, 2, 0, 0, 0, t0 + 2);
          epi_res(acn, pre, ffn ? rstd[0] * rstd[0] : 1.f, ffn ? rstd[1] * rstd[1] : 1.f, xr, M, wp);
          PROF_T(w, t0 + 2, 2);
        }
      }
    }
  }
}

typedef CUresult (*EncFn)(CUtensorMap*, CUtensorMapDataType, cuuint32_t, void*, const cuuint64_t*, const cuuint64_t*, const cuuint32_t*,
                          const cuuint32_t*, CUtensorMapInterleave, CUtensorMapSwizzle, CUtensorMapL2promotion, CUtensorMapFloatOOBfill);

void enc2(EncFn enc, CUtensorMap* tm, const void* p, uint64_t cols, uint64_t rows, uint32_t boxrows = 64, CUtensorMapL2promotion promo = CU_TENSOR_MAP_L2_PROMOTION_L2_128B) {
  cuuint64_t gd[2] = {cols, rows}, gs[1] = {cols * 2};
  cuuint32_t box[2] = {64, boxrows}, es[2] = {1, 1};
  enc(tm, CU_TENSOR_MAP_DATA_TYPE_BFLOAT16, 2, const_cast<void*>(p), gd, gs, box, es, CU_TENSOR_MAP_INTERLEAVE_NONE, CU_TENSOR_MAP_SWIZZLE_128B,
      promo, CU_TENSOR_MAP_FLOAT_OOB_FILL_NONE);
}
void enc4(EncFn enc, CUtensorMap* tm, const void* p, uint64_t K, uint64_t N, uint64_t d2, uint64_t s2, uint64_t d3, uint64_t s3, uint32_t na) {
  cuuint64_t gd[4] = {64, K, d2, d3}, gs[3] = {N * 2, s2, s3};
  cuuint32_t box[4] = {64, 64, na, 1}, es[4] = {1, 1, 1, 1};
  enc(tm, CU_TENSOR_MAP_DATA_TYPE_BFLOAT16, 4, const_cast<void*>(p), gd, gs, box, es, CU_TENSOR_MAP_INTERLEAVE_NONE, CU_TENSOR_MAP_SWIZZLE_128B,
      WPROMO, CU_TENSOR_MAP_FLOAT_OOB_FILL_NONE);
}

}

extern "C" void kernel_launch(void* const* d_in, const int* in_sizes, int n_in, void* d_out, int out_size) {
  static EncFn enc = nullptr;
  static Scratch* ps = nullptr;
  static void (*kernel)(Ptrs, Params) = mega_kernel<true>;
  if (!enc) {
    cudaDriverEntryPointQueryResult qr;
    cudaGetDriverEntryPoint("cuTensorMapEncodeTiled", (void**)&enc, cudaEnableDefault, &qr);
    int dev = 0, nsm = 0;
    cudaGetDevice(&dev);
    cudaDeviceGetAttribute(&nsm, cudaDevAttrMultiProcessorCount, dev);
    if (nsm != NMAIN + NAUX) kernel = mega_kernel<false>;
    cudaFuncSetAttribute(kernel, cudaFuncAttributeMaxDynamicSharedMemorySize, SMEM_BYTES);
    cudaGetSymbolAddress((void**)&ps, g_s);
  }
  Params P;
  Ptrs Q;
  Q.s = ps;
  void *p_h = ps->h, *p_x = ps->x;
  enc2(enc, &P.tm[TM_XIN], d_in[0], 2048, 1024, 64, XPROMO);
  enc2(enc, &P.tm[TM_X], d_out, 2048, 1024);
  enc2(enc, &P.tm[TM_XA], p_x, 2048, 1024);
  enc2(enc, &P.tm[TM_O], p_h, 3584, 2048);
  enc2(enc, &P.tm[TM_H], p_h, 3584, 2048);
  enc2(enc, &P.tm[TM_X16], d_out, 2048, 1024, 16);
  enc2(enc, &P.tm[TM_XA16], p_x, 2048, 1024, 16);
  enc2(enc, &P.tm[TM_O16], p_h, 3584, 2048, 16);
  enc4(enc, &P.tm[TM_WQKV], d_in[1], 1024, 3072, 3, 2048, 16, 128, 3);
  enc4(enc, &P.tm[TM_WO], d_in[2], 1024, 1024, 16, 128, 1, 128, 2);
  enc4(enc, &P.tm[TM_W1A], d_in[4], 1024, 3584, 56, 128, 1, 128, 4);
  enc4(enc, &P.tm[TM_W1B], d_in[4], 1024, 3584, 56, 128, 1, 128, 3);
  enc4(enc, &P.tm[TM_W2], d_in[6], 3584, 1024, 16, 128, 1, 128, 2);
  Q.out = (__nv_bfloat16*)d_out;
  Q.b1 = (const __nv_bfloat16*)d_in[5];
  Q.b2 = (const __nv_bfloat16*)d_in[7];
  kernel<<<NMAIN + NAUX, NTHREADS, SMEM_BYTES, cudaStreamPerThread>>>(Q, P);
}
```

```cpp
#include <cuda_runtime.h>
#include <cuda_bf16.h>
#include <cuda.h>
#include <stdint.h>

#define LEAD0 2
#define LEAD1 1
#define LEAD2 3
#define LEAD3 1
#define LEAD4 1
#define LEAD5 4
#define WPROMO CU_TENSOR_MAP_L2_PROMOTION_L2_128B
#define PLAN1 0x40201008070000ull
#define PLAN0 0x4030020c8180ull
#define PLANZ 0x40300a050000ull
#define VSKIP 1
#define ELA 1
#define LSO 1
#define STATI 13
#define PACE2 0x1a
#define ST2 14
#define STB 3
#define PROBE 4
#define OWNP 0x22221110
#define SIG0 14
#define STGX 2
#define STGM 3
#define NPRO 4
#define XPROMO CU_TENSOR_MAP_L2_PROMOTION_L2_256B
#define IPRE 7
#define FILLT 1
#define EARLYC 1
#define OWNDLY 0
#define EPW 0
#define CPF 5000
#define STG0 800
#define STG1 500
#define STGL (STG0 + 4 * STG1)
#define STGLX 0
#define STARTC 0
#define PRE5 0
#define PRE2 0
#define FUN 4
#define XEF 0
#define BEF 0xff8
#define AEF 0xdb6
#define SEF 0
#define NPREPX 0
#define NPREPO 0
#define SDELAYO 1000
#define SDELAY 300
#define HDELAY 450
#define Q44 1
#define FG 8
#define PRB 0
#define HPF 0
#define TAR 0
#define RSV 0
#define NWB 0
#define AGK 1
#define NOI 1
#define EFIRST 1
#define SDL0 0
#define AUGN 0
#define LEARLY 1
#define PG (Q44 ? 32 : 16)
#define NH1 6
#define NH2 3
namespace {

constexpr int NMAIN = 128, NAUX = 4, NTHREADS = 384;
constexpr uint32_t OFF_B = 0;
constexpr uint32_t OFF_A = 131072;
constexpr uint32_t OFF_VEC = 229376;
constexpr uint32_t OFF_BAR = 231424;
constexpr uint32_t OFF_RSTD = OFF_VEC + 512, OFF_MEAN = OFF_VEC + 1088, OFF_HOLD = OFF_VEC + 2032;
constexpr uint32_t SMEM_BYTES = OFF_BAR + 960;
constexpr uint32_t BAR_FULLA = OFF_BAR, BAR_FULLB = OFF_BAR + 96, BAR_OWN = OFF_BAR + 160, BAR_EPOCH = OFF_BAR + 176, BAR_AUG = OFF_BAR + 184, BAR_SPEC = OFF_BAR + 192,
                   BAR_EMPTYA = OFF_BAR + 288, BAR_STG = OFF_BAR + 384, BAR_SRV = OFF_BAR + 400, BAR_LEAD = OFF_BAR + 432, BAR_HALO = OFF_BAR + 440, BAR_STG2 = OFF_BAR + 456,
                   BAR_DUMMY3 = OFF_BAR + 472, BAR_EMPTYB = OFF_BAR + 480, BAR_STAT = OFF_BAR + 544, BAR_DUMMY = OFF_BAR + 560;
constexpr int NA = 6;
constexpr uint32_t SB = 1024;
constexpr uint32_t SPIN_LIMIT = 1u << 22;

enum { TM_XIN = 0, TM_X, TM_XA, TM_O, TM_H, TM_WQKV, TM_WO, TM_W1A, TM_W1B, TM_W2, TM_X16, TM_XA16, TM_O16, TM_COUNT };

struct Scratch;
struct Ptrs {
  Scratch* s;
  __nv_bfloat16* out;
  const __nv_bfloat16* b1;
  const __nv_bfloat16* b2;
};
struct Params { CUtensorMap tm[TM_COUNT]; };

constexpr int NSTEP = 280, NSTEP_AUX = 128;
enum : uint32_t { F_STAMP = 1u << 28, F_GATH = 1u << 15, F_NEW = 1u << 16, F_AUG = 1u << 17, F_NOA = 1u << 18, E_HAND = 1u << 19, E_ATTN = 1u << 20, E_XPUB0 = 1u << 21,
                  E_WAIT = 1u << 22, E_REL = 1u << 23, E_KEEP = 1u << 24, E_PART1 = 1u << 25, E_HALO = 1u << 26,
                  E_SIG = 1u << 27, E_RARE = F_NEW | E_KEEP | (0xfu << 20) | (3u << 26) };
constexpr int own_round(int j) { return (OWNP >> (4 * j)) & 15; }
constexpr uint32_t first_order(int j) {
  uint32_t used = 0, v = 0;
  for (int p = 0; p < 8; p++) {
    int c = own_round(j) == p ? j : -1;
    for (int u = 0; u < 8 && c < 0; u++) if (u != j && !((used >> u) & 1) && own_round(u) < p) c = u;
    if (c < 0 && own_round(j ^ 1) == p) c = j ^ 1;
    for (int u = 0; u < 8 && c < 0; u++) { const int x = (u + (j & 6)) & 7; if (x != j && own_round(x) == p) c = x; }
    used |= 1u << c; v |= (uint32_t)c << (4 * p);
  }
  return v;
}
constexpr uint32_t first_round(int p) { uint32_t v = 0; for (int j = 0; j < 8; j++) v |= ((first_order(j) >> (4 * p)) & 15) << (4 * j); return v; }
constexpr uint32_t ROUND0 = first_round(0), ROUND1 = first_round(1);
struct Sched { uint32_t v[9][NSTEP + 8]; };
constexpr Sched make_sched() {
  Sched T{};
  for (int j = 0; j < 8; j++) {
    int owner[16] = {};
    for (int i = 0; i < 16; i++) owner[i] = -100;
    int p = 0, g = 0;
    for (int t = 0; t < 12; t++) {
      const int kind = t % 6, ks = kind == 5 ? 56 : (kind == 2 ? 16 : 17);
      for (int i = 0; i < ks; i++) {
        const bool augs = ks == 17 && i == 16;
        const int na = (kind == 2 || kind == 5) ? 2 : (augs ? 1 : (kind == 4 ? 4 : 3));
        if (i == 0) p = (0x20cc63 >> (4 * kind)) & 15;
        if (augs) p = (0x0f0af >> (4 * kind)) & 15;
        if (p + na > 16) p = 0;
        int need = g - 8;
        for (int a = p; a < p + na; a++) { if (owner[a] > need) need = owner[a]; owner[a] = g; }
        if (g == 16 && need < AUGN) need = AUGN;
        uint32_t k = i, f = i == (t ? 0 : NPRO) ? F_NEW | (1u << 29) : 0;
        if (augs) { k = 0; f |= F_AUG; }
        else if (kind == 0 || kind == 3) {
          const int o = i - 2;
          if (t == 0) k = ((first_order(j) >> (4 * (i >> 1))) & 15) * 2 + (i & 1);
          else if (i < 2) { k = 2 * j + i; f |= F_NOA | (i == 0 ? E_XPUB0 : 0); }
          else { const int half = o >= 7; int u = o - 7 * half; u += u >= j; k = 2 * u + half; if (i == 6) f |= E_REL; if (i < 2 + NPREPX) f |= F_NOA; }
          if (i == 11) f |= E_HAND;
          if (i == (t ? 11 : SIG0)) f |= E_SIG;
        } else if (kind == 1 || kind == 4) {
          if (kind == 1) f |= i == 3 ? E_HAND : (i == 8 ? E_HAND | E_KEEP : (i == 5 ? E_HALO : 0));
          if (kind == 1) f |= i == 13 ? E_REL : 0;
          else if (i == 4 || i == 7 || i == 10) f |= E_HAND;
        } else if (kind == 2) {
          f |= i == 0 ? E_WAIT : (i == 3 ? E_HAND : (i == 5 ? E_HALO : 0));
          if (i == 8) { k = 8 + j; f |= E_ATTN | E_KEEP | F_NOA; }
          if (i > 8) k = i - 1 + (i - 9 >= j);
          if (i > 8 && i < 9 + NPREPO) f |= F_NOA;
          if (i == 11) f |= E_REL;
        } else {
          k = i < 24 ? (i / 3) * 7 + i % 3 : ((i - 24) / 4) * 7 + 3 + (i - 24) % 4;
          if (i == 4 || i == 7 || i == 10 || i == 13) f |= E_HAND;
          f |= i == 0 ? E_WAIT : (i == 24 ? E_WAIT | E_PART1 : 0);
        }
        if ((kind == 2 || kind == 5) && t < 11 && i == ks - (kind == 2 ? 1 : STB)) f |= F_STAMP;
        if (((PACE2 >> kind) & 1) && i == ST2) f |= F_STAMP;
        if (i == 0 && t && ((PACE2 >> ((t - 1) % 6)) & 1)) f |= F_GATH;
        T.v[j][g] = p | ((g - need) << 5) | (k << 9) | f;
        p += na; g++;
      }
    }
    T.v[j][NSTEP] = F_NEW | F_NOA | E_XPUB0 | (2 * j << 9);
  }
  for (int w = 0; w < 2; w++) {
    int owner[14] = {};
    for (int i = 0; i < 14; i++) owner[i] = -100;
    for (int g = w, p = 0; g < NSTEP_AUX; g += 2) {
      const int na = g < 96 ? 3 : 4;
      if (p + na > 14) p = 0;
      int need = g - 8;
      for (int a = p; a < p + na; a++) { if (owner[a] > need) need = owner[a]; owner[a] = g; }
      T.v[8][g] = (p + 14 * w) | ((g - need) << 5) | ((g & 31) >> 1 << 9) | ((g & 30) && g - w != 8 ? 0 : F_NEW | (g - w == 64 ? 2u : 1u) << 29);
      p += na;
    }
  }
  return T;
}
__constant__ Sched c_sched = make_sched();
__device__ __forceinline__ int sched_k(uint32_t e) { return (e >> 3) & 0xfc0; }

struct Scratch {
  __nv_bfloat16 x[2048 * 1024];
  __nv_bfloat16 h[2048 * 3584];
  uint32_t epoch[160];
  uint8_t flags[16][2][64];
  uint32_t pace[8][32];
  uint32_t aug[2][32][1024];
  uint4 stats[4][512][8][2];
  uint4 halo[4][256][136];
};
__device__ __align__(1024) Scratch g_s;
#define PROF_T(w, t, i)
#define PRO(i)
#define LT(i)
#define CT(n)
#define ST(i)
#define AP(i)

__device__ __forceinline__ int work_id() {
  uint32_t smid;
  asm volatile("mov.u32 %0, %%smid;" : "=r"(smid));
  const int t = smid >> 1, u = t - 32, d = (u * 37) >> 8;
  int id = (t & 7) * 16 + (t >> 3) * 2;
  if (t >= 32) id = (1 + u - 7 * d) * 16 + (4 + d) * 2;
  if (t >= 60) id = t < 62 ? t * 2 + 8 : t * 2 - 116;
  return id + (smid & 1);
}

__device__ __forceinline__ uint32_t smem_u32(const void* p) { return (uint32_t)__cvta_generic_to_shared(p); }
__device__ __forceinline__ void mbar_init(uint32_t bar, int cnt) { asm volatile("mbarrier.init.shared::cta.b64 [%0], %1;" ::"r"(bar), "r"(cnt)); }
__device__ __forceinline__ void mbar_expect_tx(uint32_t bar, uint32_t bytes) { asm volatile("mbarrier.arrive.expect_tx.shared::cta.b64 _, [%0], %1;" ::"r"(bar), "r"(bytes) : "memory"); }
__device__ __forceinline__ void mbar_arrive(uint32_t bar, uint32_t cnt) { asm volatile("mbarrier.arrive.shared::cta.b64 _, [%0], %1;" ::"r"(bar), "r"(cnt) : "memory"); }
__device__ __forceinline__ void arrive_n(uint32_t bar, bool) { asm volatile("{\n.reg .pred p;\nelect.sync _|p, 0xffffffff;\n@p mbarrier.arrive.shared::cta.b64 _, [%0];\n}" ::"r"(bar) : "memory"); }
__device__ __forceinline__ void arrive_2(uint32_t b0, uint32_t b1, bool) {
  asm volatile("{\n.reg .pred p;\nelect.sync _|p, 0xffffffff;\n@p mbarrier.arrive.shared::cta.b64 _, [%0];\n@p mbarrier.arrive.shared::cta.b64 _, [%1];\n}" ::"r"(b0), "r"(b1) : "memory");
}
__device__ __forceinline__ void mbar_wait(uint32_t bar, uint32_t parity) {
  asm volatile(
      "{\n.reg .pred p;\n.reg .u32 c;\nmov.u32 c, 0;\n"
      "LAB_WAIT:\nmbarrier.try_wait.parity.shared::cta.b64 p, [%0], %1;\n@p bra.uni DONE;\n"
      "add.u32 c, c, 1;\nsetp.lt.u32 p, c, 4000000;\n@p bra.uni LAB_WAIT;\ntrap;\nDONE:\n}" ::"r"(bar), "r"(parity) : "memory");
}
__device__ __forceinline__ void mbar_spin(uint32_t bar, uint32_t parity) {
  asm volatile("{\n.reg .pred p;\nLAB_WAIT:\nmbarrier.try_wait.parity.shared::cta.b64 p, [%0], %1;\n@!p pmevent 7;\n@!p bra.uni LAB_WAIT;\n}" ::"r"(bar), "r"(parity) : "memory");
}
__device__ __forceinline__ bool elect_one() {
  uint32_t p;
  asm volatile("{\n.reg .pred P;\nelect.sync _|P, 0xffffffff;\nselp.u32 %0, 1, 0, P;\n}" : "=r"(p));
  return p != 0;
}
__device__ __forceinline__ bool mbar_test(uint32_t bar, uint32_t parity) {
  uint32_t ok;
  asm volatile("{\n.reg .pred p;\nmbarrier.test_wait.parity.shared::cta.b64 p, [%1], %2;\nselp.u32 %0, 1, 0, p;\n}" : "=r"(ok) : "r"(bar), "r"(parity) : "memory");
  return ok != 0;
}
__device__ __forceinline__ void tma_ld2(uint32_t dst, const CUtensorMap* tm, int c0, int c1, uint32_t bar) {
  asm volatile("cp.async.bulk.tensor.2d.shared::cluster.global.mbarrier::complete_tx::bytes [%0], [%1, {%3, %4}], [%2];" ::"r"(dst), "l"(tm), "r"(bar), "r"(c0), "r"(c1) : "memory");
}
__device__ __forceinline__ void tma_ld4(uint32_t dst, const CUtensorMap* tm, int c1, int c2, int c3, uint32_t bar, uint64_t pol = 0x1000000000000000ull) {
  asm volatile("cp.async.bulk.tensor.4d.shared::cluster.global.mbarrier::complete_tx::bytes.L2::cache_hint [%0], [%1, {%3, %4, %5, %6}], [%2], %7;" ::"r"(dst), "l"(tm), "r"(bar), "r"(0), "r"(c1), "r"(c2), "r"(c3), "l"(pol) : "memory");
}
__device__ __forceinline__ void tma_st2(const CUtensorMap* tm, int c0, int c1, uint32_t src) {
  asm volatile("cp.async.bulk.tensor.2d.global.shared::cta.bulk_group [%0, {%2, %3}], [%1];" ::"l"(tm), "r"(src), "r"(c0), "r"(c1) : "memory");
}
__device__ __forceinline__ void bulk_ld(uint32_t dst, const void* src, uint32_t bytes, uint32_t bar) {
  asm volatile("cp.async.bulk.shared::cluster.global.mbarrier::complete_tx::bytes [%0], [%1], %2, [%3];" ::"r"(dst), "l"(src), "r"(bytes), "r"(bar) : "memory");
}
__device__ __forceinline__ void e_arrive(uint32_t bar, uint32_t cnt) {
  if (cnt == 1) asm volatile("{\n.reg .pred p;\nelect.sync _|p, 0xffffffff;\n@p mbarrier.arrive.shared::cta.b64 _, [%0];\n}" ::"r"(bar) : "memory");
  else asm volatile("{\n.reg .pred p;\nelect.sync _|p, 0xffffffff;\n@p mbarrier.arrive.shared::cta.b64 _, [%0], %1;\n}" ::"r"(bar), "r"(cnt) : "memory");
}
template <int BYTES = 8192> __device__ __forceinline__ void e_load(uint32_t dst, const CUtensorMap* tm, int c0, int c1, uint32_t bar, uint64_t pol = 0x1000000000000000ull) {
  asm volatile("{\n.reg .pred p;\nelect.sync _|p, 0xffffffff;\n@p mbarrier.arrive.expect_tx.shared::cta.b64 _, [%2], %5;\n"
               "@p cp.async.bulk.tensor.2d.shared::cluster.global.mbarrier::complete_tx::bytes.L2::cache_hint [%0], [%1, {%3, %4}], [%2], %6;\n}"
               ::"r"(dst), "l"(tm), "r"(bar), "r"(c0), "r"(c1), "n"(BYTES), "l"(pol) : "memory");
}
__device__ __forceinline__ void e_store(const CUtensorMap* tm, int c0, int c1, uint32_t src) {
  asm volatile("{\n.reg .pred p;\nfence.proxy.async.shared::cta;\nelect.sync _|p, 0xffffffff;\n"
               "@p cp.async.bulk.tensor.2d.global.shared::cta.bulk_group [%0, {%2, %3}], [%1];\ncp.async.bulk.commit_group;\n}"
               ::"l"(tm), "r"(src), "r"(c0), "r"(c1) : "memory");
}
__device__ __forceinline__ void bulk_commit() { asm volatile("cp.async.bulk.commit_group;" ::: "memory"); }
template <int N> __device__ __forceinline__ void bulk_wait_read() { asm volatile("cp.async.bulk.wait_group.read %0;" ::"n"(N) : "memory"); }
__device__ __forceinline__ void bulk_wait_all() { asm volatile("cp.async.bulk.wait_group 0;" ::: "memory"); }
__device__ __forceinline__ void fence_async_smem() { asm volatile("fence.proxy.async.shared::cta;" ::: "memory"); }
__device__ __forceinline__ void wg_fence() { asm volatile("wgmma.fence.sync.aligned;" ::: "memory"); }
__device__ __forceinline__ void wg_commit() { asm volatile("wgmma.commit_group.sync.aligned;" ::: "memory"); }
template <int N> __device__ __forceinline__ void wg_wait() { asm volatile("wgmma.wait_group.sync.aligned %0;" ::"n"(N) : "memory"); }
__device__ __forceinline__ void wg_bar(int w) { asm volatile("bar.sync %0, 128;" ::"r"(w + 1) : "memory"); }
__device__ __forceinline__ uint32_t ld_acquire(const uint32_t* p) { uint32_t v; asm volatile("ld.acquire.gpu.global.u32 %0, [%1];" : "=r"(v) : "l"(p) : "memory"); return v; }
__device__ __forceinline__ uint4 ld_relaxed4(const uint32_t* p) {
  uint4 v; asm volatile("ld.relaxed.gpu.global.v4.u32 {%0,%1,%2,%3}, [%4];" : "=r"(v.x), "=r"(v.y), "=r"(v.z), "=r"(v.w) : "l"(p) : "memory"); return v;
}
__device__ __forceinline__ void st_release8(uint8_t* p, uint32_t v) { asm volatile("st.release.gpu.global.u8 [%0], %1;" ::"l"(p), "r"(v) : "memory"); }
__device__ __forceinline__ uint32_t ld_relaxed(const uint32_t* p) { uint32_t v; asm volatile("ld.relaxed.gpu.global.u32 %0, [%1];" : "=r"(v) : "l"(p) : "memory"); return v; }
__device__ __forceinline__ void st_release(uint32_t* p, uint32_t v) { asm volatile("st.release.gpu.global.u32 [%0], %1;" ::"l"(p), "r"(v) : "memory"); }
__device__ __forceinline__ void st_pkt(uint4* p, uint32_t a, uint32_t b, uint32_t c, uint32_t d) {
  asm volatile("{\n.reg .b64 lo, hi;\n.reg .b128 v;\nmov.b64 lo, {%1, %2};\nmov.b64 hi, {%3, %4};\nmov.b128 v, {lo, hi};\nst.relaxed.gpu.global.b128 [%0], v;\n}" ::"l"(p), "r"(a), "r"(b), "r"(c), "r"(d) : "memory");
}
__device__ __forceinline__ uint4 ld_pkt(const uint4* p) {
  uint4 r;
  asm volatile("{\n.reg .b64 lo, hi;\n.reg .b128 v;\nld.relaxed.gpu.global.b128 v, [%4];\nmov.b128 {lo, hi}, v;\nmov.b64 {%0, %1}, lo;\nmov.b64 {%2, %3}, hi;\n}" : "=r"(r.x), "=r"(r.y), "=r"(r.z), "=r"(r.w) : "l"(p) : "memory");
  return r;
}
__device__ __forceinline__ uint32_t pack_bf16(float lo, float hi) { uint32_t d; asm("cvt.rn.bf16x2.f32 %0, %1, %2;" : "=r"(d) : "f"(hi), "f"(lo)); return d; }
__device__ __forceinline__ float ex2(float x) { float y; asm("ex2.approx.ftz.f32 %0, %1;" : "=f"(y) : "f"(x)); return y; }
__device__ __forceinline__ float rsq(float x) { float y; asm("rsqrt.approx.ftz.f32 %0, %1;" : "=f"(y) : "f"(x)); return y; }
__device__ __forceinline__ float rcp(float x) { float y; asm("rcp.approx.ftz.f32 %0, %1;" : "=f"(y) : "f"(x)); return y; }
__device__ __forceinline__ float bf_lo(uint32_t v) { return __uint_as_float(v << 16); }
__device__ __forceinline__ float bf_hi(uint32_t v) { return __uint_as_float(v & 0xffff0000u); }
__device__ __forceinline__ void stsm4(uint32_t addr, uint32_t a, uint32_t b, uint32_t c, uint32_t d) {
  asm volatile("stmatrix.sync.aligned.m8n8.x4.shared.b16 [%0], {%1, %2, %3, %4};" ::"r"(addr), "r"(a), "r"(b), "r"(c), "r"(d) : "memory");
}
__device__ __forceinline__ uint32_t movm(uint32_t a) { uint32_t d; asm volatile("movmatrix.sync.aligned.m8n8.trans.b16 %0, %1;" : "=r"(d) : "r"(a)); return d; }
__device__ __forceinline__ void mma16(float (&c)[4], uint32_t a0, uint32_t a1, uint32_t a2, uint32_t a3, uint32_t b0, uint32_t b1) {
  asm volatile("mma.sync.aligned.m16n8k16.row.col.f32.bf16.bf16.f32 {%0,%1,%2,%3}, {%4,%5,%6,%7}, {%8,%9}, {%0,%1,%2,%3};"
               : "+f"(c[0]), "+f"(c[1]), "+f"(c[2]), "+f"(c[3]) : "r"(a0), "r"(a1), "r"(a2), "r"(a3), "r"(b0), "r"(b1));
}
__device__ __forceinline__ void mma8(float (&c)[4], uint32_t a0, uint32_t a1, uint32_t b0) {
  asm volatile("mma.sync.aligned.m16n8k8.row.col.f32.bf16.bf16.f32 {%0,%1,%2,%3}, {%4,%5}, {%6}, {%0,%1,%2,%3};"
               : "+f"(c[0]), "+f"(c[1]), "+f"(c[2]), "+f"(c[3]) : "r"(a0), "r"(a1), "r"(b0));
}
__device__ __forceinline__ void sts128(uint32_t a, uint32_t x, uint32_t y, uint32_t z, uint32_t w) {
  asm volatile("st.shared.v4.b32 [%0], {%1,%2,%3,%4};" ::"r"(a), "r"(x), "r"(y), "r"(z), "r"(w) : "memory");
}
__device__ __forceinline__ float2 lds64(uint32_t a) { float2 v; asm volatile("ld.shared.v2.f32 {%0,%1}, [%2];" : "=f"(v.x), "=f"(v.y) : "r"(a)); return v; }
__device__ __forceinline__ float4 lds128(uint32_t a) { float4 v; asm volatile("ld.shared.v4.f32 {%0,%1,%2,%3}, [%4];" : "=f"(v.x), "=f"(v.y), "=f"(v.z), "=f"(v.w) : "r"(a)); return v; }
__device__ __forceinline__ uint32_t lds32(uint32_t a) { uint32_t v; asm volatile("ld.shared.b32 %0, [%1];" : "=r"(v) : "r"(a)); return v; }
template <int S> __device__ __forceinline__ void wgmma_first128(float (&d)[S], uint32_t da, uint32_t db) {
  asm volatile("{\n.reg .b64 a, b;\n.reg .b32 t, u, h;\n.reg .pred p, q;\nmov.b32 h, 0x40000040;\nwgmma.fence.sync.aligned;\n"
    "add.u32 t, %64, 0;\nadd.u32 u, %65, 0;\nmov.b64 a, {t, h};\nmov.b64 b, {u, h};\n"
    "wgmma.mma_async.sync.aligned.m64n128k16.f32.bf16.bf16 "
    "{%0, %1, %2, %3, %4, %5, %6, %7, %8, %9, %10, %11, %12, %13, %14, %15, %16, %17, %18, %19, %20, %21, %22, %23, %24, %25, %26, %27, %28, %29, %30, %31, %32, %33, %34, %35, %36, %37, %38, %39, %40, %41, %42, %43, %44, %45, %46, %47, %48, %49, %50, %51, %52, %53, %54, %55, %56, %57, %58, %59, %60, %61, %62, %63}, "
    "a, b, 0, 1, 1, 0, 1;\n"
    "add.u32 t, %64, 2;\nadd.u32 u, %65, 128;\nmov.b64 a, {t, h};\nmov.b64 b, {u, h};\n"
    "wgmma.mma_async.sync.aligned.m64n128k16.f32.bf16.bf16 "
    "{%0, %1, %2, %3, %4, %5, %6, %7, %8, %9, %10, %11, %12, %13, %14, %15, %16, %17, %18, %19, %20, %21, %22, %23, %24, %25, %26, %27, %28, %29, %30, %31, %32, %33, %34, %35, %36, %37, %38, %39, %40, %41, %42, %43, %44, %45, %46, %47, %48, %49, %50, %51, %52, %53, %54, %55, %56, %57, %58, %59, %60, %61, %62, %63}, "
    "a, b, 1, 1, 1, 0, 1;\n"
    "add.u32 t, %64, 4;\nadd.u32 u, %65, 256;\nmov.b64 a, {t, h};\nmov.b64 b, {u, h};\n"
    "wgmma.mma_async.sync.aligned.m64n128k16.f32.bf16.bf16 "
    "{%0, %1, %2, %3, %4, %5, %6, %7, %8, %9, %10, %11, %12, %13, %14, %15, %16, %17, %18, %19, %20, %21, %22, %23, %24, %25, %26, %27, %28, %29, %30, %31, %32, %33, %34, %35, %36, %37, %38, %39, %40, %41, %42, %43, %44, %45, %46, %47, %48, %49, %50, %51, %52, %53, %54, %55, %56, %57, %58, %59, %60, %61, %62, %63}, "
    "a, b, 1, 1, 1, 0, 1;\n"
    "add.u32 t, %64, 6;\nadd.u32 u, %65, 384;\nmov.b64 a, {t, h};\nmov.b64 b, {u, h};\n"
    "wgmma.mma_async.sync.aligned.m64n128k16.f32.bf16.bf16 "
    "{%0, %1, %2, %3, %4, %5, %6, %7, %8, %9, %10, %11, %12, %13, %14, %15, %16, %17, %18, %19, %20, %21, %22, %23, %24, %25, %26, %27, %28, %29, %30, %31, %32, %33, %34, %35, %36, %37, %38, %39, %40, %41, %42, %43, %44, %45, %46, %47, %48, %49, %50, %51, %52, %53, %54, %55, %56, %57, %58, %59, %60, %61, %62, %63}, "
    "a, b, 1, 1, 1, 0, 1;\n"
    "wgmma.commit_group.sync.aligned;\n}"
    : "=f"(d[0]), "=f"(d[1]), "=f"(d[2]), "=f"(d[3]), "=f"(d[4]), "=f"(d[5]), "=f"(d[6]), "=f"(d[7]), "=f"(d[8]), "=f"(d[9]), "=f"(d[10]), "=f"(d[11]), "=f"(d[12]), "=f"(d[13]), "=f"(d[14]), "=f"(d[15]), "=f"(d[16]), "=f"(d[17]), "=f"(d[18]), "=f"(d[19]), "=f"(d[20]), "=f"(d[21]), "=f"(d[22]), "=f"(d[23]), "=f"(d[24]), "=f"(d[25]), "=f"(d[26]), "=f"(d[27]), "=f"(d[28]), "=f"(d[29]), "=f"(d[30]), "=f"(d[31]), "=f"(d[32]), "=f"(d[33]), "=f"(d[34]), "=f"(d[35]), "=f"(d[36]), "=f"(d[37]), "=f"(d[38]), "=f"(d[39]), "=f"(d[40]), "=f"(d[41]), "=f"(d[42]), "=f"(d[43]), "=f"(d[44]), "=f"(d[45]), "=f"(d[46]), "=f"(d[47]), "=f"(d[48]), "=f"(d[49]), "=f"(d[50]), "=f"(d[51]), "=f"(d[52]), "=f"(d[53]), "=f"(d[54]), "=f"(d[55]), "=f"(d[56]), "=f"(d[57]), "=f"(d[58]), "=f"(d[59]), "=f"(d[60]), "=f"(d[61]), "=f"(d[62]), "=f"(d[63])
    : "r"(da), "r"(db) : "memory");
}
template <int S> __device__ __forceinline__ uint2 wgmma_probe128(float (&d)[S], uint32_t da, uint32_t db, uint32_t b0, uint32_t p0, uint32_t b1, uint32_t p1) {
  uint2 ok;
  asm volatile("{\n.reg .b64 a, b;\n.reg .b32 t, u, h;\n.reg .pred p, q;\nmov.b32 h, 0x40000040;\nwgmma.fence.sync.aligned;\n"
    "add.u32 t, %66, 0;\nadd.u32 u, %67, 0;\nmov.b64 a, {t, h};\nmov.b64 b, {u, h};\n"
    "wgmma.mma_async.sync.aligned.m64n128k16.f32.bf16.bf16 "
    "{%2, %3, %4, %5, %6, %7, %8, %9, %10, %11, %12, %13, %14, %15, %16, %17, %18, %19, %20, %21, %22, %23, %24, %25, %26, %27, %28, %29, %30, %31, %32, %33, %34, %35, %36, %37, %38, %39, %40, %41, %42, %43, %44, %45, %46, %47, %48, %49, %50, %51, %52, %53, %54, %55, %56, %57, %58, %59, %60, %61, %62, %63, %64, %65}, "
    "a, b, 1, 1, 1, 0, 1;\n"
    "add.u32 t, %66, 2;\nadd.u32 u, %67, 128;\nmov.b64 a, {t, h};\nmov.b64 b, {u, h};\n"
    "wgmma.mma_async.sync.aligned.m64n128k16.f32.bf16.bf16 "
    "{%2, %3, %4, %5, %6, %7, %8, %9, %10, %11, %12, %13, %14, %15, %16, %17, %18, %19, %20, %21, %22, %23, %24, %25, %26, %27, %28, %29, %30, %31, %32, %33, %34, %35, %36, %37, %38, %39, %40, %41, %42, %43, %44, %45, %46, %47, %48, %49, %50, %51, %52, %53, %54, %55, %56, %57, %58, %59, %60, %61, %62, %63, %64, %65}, "
    "a, b, 1, 1, 1, 0, 1;\n"
    "mbarrier.test_wait.parity.shared::cta.b64 p, [%68], %69;\nmbarrier.test_wait.parity.shared::cta.b64 q, [%70], %71;\n"
    "add.u32 t, %66, 4;\nadd.u32 u, %67, 256;\nmov.b64 a, {t, h};\nmov.b64 b, {u, h};\n"
    "wgmma.mma_async.sync.aligned.m64n128k16.f32.bf16.bf16 "
    "{%2, %3, %4, %5, %6, %7, %8, %9, %10, %11, %12, %13, %14, %15, %16, %17, %18, %19, %20, %21, %22, %23, %24, %25, %26, %27, %28, %29, %30, %31, %32, %33, %34, %35, %36, %37, %38, %39, %40, %41, %42, %43, %44, %45, %46, %47, %48, %49, %50, %51, %52, %53, %54, %55, %56, %57, %58, %59, %60, %61, %62, %63, %64, %65}, "
    "a, b, 1, 1, 1, 0, 1;\n"
    "add.u32 t, %66, 6;\nadd.u32 u, %67, 384;\nmov.b64 a, {t, h};\nmov.b64 b, {u, h};\n"
    "wgmma.mma_async.sync.aligned.m64n128k16.f32.bf16.bf16 "
    "{%2, %3, %4, %5, %6, %7, %8, %9, %10, %11, %12, %13, %14, %15, %16, %17, %18, %19, %20, %21, %22, %23, %24, %25, %26, %27, %28, %29, %30, %31, %32, %33, %34, %35, %36, %37, %38, %39, %40, %41, %42, %43, %44, %45, %46, %47, %48, %49, %50, %51, %52, %53, %54, %55, %56, %57, %58, %59, %60, %61, %62, %63, %64, %65}, "
    "a, b, 1, 1, 1, 0, 1;\n"
    "wgmma.commit_group.sync.aligned;\nselp.u32 %0, 1, 0, p;\nselp.u32 %1, 1, 0, q;\n}"
    : "=r"(ok.x), "=r"(ok.y), "+f"(d[0]), "+f"(d[1]), "+f"(d[2]), "+f"(d[3]), "+f"(d[4]), "+f"(d[5]), "+f"(d[6]), "+f"(d[7]), "+f"(d[8]), "+f"(d[9]), "+f"(d[10]), "+f"(d[11]), "+f"(d[12]), "+f"(d[13]), "+f"(d[14]), "+f"(d[15]), "+f"(d[16]), "+f"(d[17]), "+f"(d[18]), "+f"(d[19]), "+f"(d[20]), "+f"(d[21]), "+f"(d[22]), "+f"(d[23]), "+f"(d[24]), "+f"(d[25]), "+f"(d[26]), "+f"(d[27]), "+f"(d[28]), "+f"(d[29]), "+f"(d[30]), "+f"(d[31]), "+f"(d[32]), "+f"(d[33]), "+f"(d[34]), "+f"(d[35]), "+f"(d[36]), "+f"(d[37]), "+f"(d[38]), "+f"(d[39]), "+f"(d[40]), "+f"(d[41]), "+f"(d[42]), "+f"(d[43]), "+f"(d[44]), "+f"(d[45]), "+f"(d[46]), "+f"(d[47]), "+f"(d[48]), "+f"(d[49]), "+f"(d[50]), "+f"(d[51]), "+f"(d[52]), "+f"(d[53]), "+f"(d[54]), "+f"(d[55]), "+f"(d[56]), "+f"(d[57]), "+f"(d[58]), "+f"(d[59]), "+f"(d[60]), "+f"(d[61]), "+f"(d[62]), "+f"(d[63])
    : "r"(da), "r"(db), "r"(b0), "r"(p0), "r"(b1), "r"(p1) : "memory");
  return ok;
}
template <int S> __device__ __forceinline__ void wgmma_first192(float (&d)[S], uint32_t da, uint32_t db) {
  asm volatile("{\n.reg .b64 a, b;\n.reg .b32 t, u, h;\n.reg .pred p, q;\nmov.b32 h, 0x40000040;\nwgmma.fence.sync.aligned;\n"
    "add.u32 t, %96, 0;\nadd.u32 u, %97, 0;\nmov.b64 a, {t, h};\nmov.b64 b, {u, h};\n"
    "wgmma.mma_async.sync.aligned.m64n192k16.f32.bf16.bf16 "
    "{%0, %1, %2, %3, %4, %5, %6, %7, %8, %9, %10, %11, %12, %13, %14, %15, %16, %17, %18, %19, %20, %21, %22, %23, %24, %25, %26, %27, %28, %29, %30, %31, %32, %33, %34, %35, %36, %37, %38, %39, %40, %41, %42, %43, %44, %45, %46, %47, %48, %49, %50, %51, %52, %53, %54, %55, %56, %57, %58, %59, %60, %61, %62, %63, %64, %65, %66, %67, %68, %69, %70, %71, %72, %73, %74, %75, %76, %77, %78, %79, %80, %81, %82, %83, %84, %85, %86, %87, %88, %89, %90, %91, %92, %93, %94, %95}, "
    "a, b, 0, 1, 1, 0, 1;\n"
    "add.u32 t, %96, 2;\nadd.u32 u, %97, 128;\nmov.b64 a, {t, h};\nmov.b64 b, {u, h};\n"
    "wgmma.mma_async.sync.aligned.m64n192k16.f32.bf16.bf16 "
    "{%0, %1, %2, %3, %4, %5, %6, %7, %8, %9, %10, %11, %12, %13, %14, %15, %16, %17, %18, %19, %20, %21, %22, %23, %24, %25, %26, %27, %28, %29, %30, %31, %32, %33, %34, %35, %36, %37, %38, %39, %40, %41, %42, %43, %44, %45, %46, %47, %48, %49, %50, %51, %52, %53, %54, %55, %56, %57, %58, %59, %60, %61, %62, %63, %64, %65, %66, %67, %68, %69, %70, %71, %72, %73, %74, %75, %76, %77, %78, %79, %80, %81, %82, %83, %84, %85, %86, %87, %88, %89, %90, %91, %92, %93, %94, %95}, "
    "a, b, 1, 1, 1, 0, 1;\n"
    "add.u32 t, %96, 4;\nadd.u32 u, %97, 256;\nmov.b64 a, {t, h};\nmov.b64 b, {u, h};\n"
    "wgmma.mma_async.sync.aligned.m64n192k16.f32.bf16.bf16 "
    "{%0, %1, %2, %3, %4, %5, %6, %7, %8, %9, %10, %11, %12, %13, %14, %15, %16, %17, %18, %19, %20, %21, %22, %23, %24, %25, %26, %27, %28, %29, %30, %31, %32, %33, %34, %35, %36, %37, %38, %39, %40, %41, %42, %43, %44, %45, %46, %47, %48, %49, %50, %51, %52, %53, %54, %55, %56, %57, %58, %59, %60, %61, %62, %63, %64, %65, %66, %67, %68, %69, %70, %71, %72, %73, %74, %75, %76, %77, %78, %79, %80, %81, %82, %83, %84, %85, %86, %87, %88, %89, %90, %91, %92, %93, %94, %95}, "
    "a, b, 1, 1, 1, 0, 1;\n"
    "add.u32 t, %96, 6;\nadd.u32 u, %97, 384;\nmov.b64 a, {t, h};\nmov.b64 b, {u, h};\n"
    "wgmma.mma_async.sync.aligned.m64n192k16.f32.bf16.bf16 "
    "{%0, %1, %2, %3, %4, %5, %6, %7, %8, %9, %10, %11, %12, %13, %14, %15, %16, %17, %18, %19, %20, %21, %22, %23, %24, %25, %26, %27, %28, %29, %30, %31, %32, %33, %34, %35, %36, %37, %38, %39, %40, %41, %42, %43, %44, %45, %46, %47, %48, %49, %50, %51, %52, %53, %54, %55, %56, %57, %58, %59, %60, %61, %62, %63, %64, %65, %66, %67, %68, %69, %70, %71, %72, %73, %74, %75, %76, %77, %78, %79, %80, %81, %82, %83, %84, %85, %86, %87, %88, %89, %90, %91, %92, %93, %94, %95}, "
    "a, b, 1, 1, 1, 0, 1;\n"
    "wgmma.commit_group.sync.aligned;\n}"
    : "=f"(d[0]), "=f"(d[1]), "=f"(d[2]), "=f"(d[3]), "=f"(d[4]), "=f"(d[5]), "=f"(d[6]), "=f"(d[7]), "=f"(d[8]), "=f"(d[9]), "=f"(d[10]), "=f"(d[11]), "=f"(d[12]), "=f"(d[13]), "=f"(d[14]), "=f"(d[15]), "=f"(d[16]), "=f"(d[17]), "=f"(d[18]), "=f"(d[19]), "=f"(d[20]), "=f"(d[21]), "=f"(d[22]), "=f"(d[23]), "=f"(d[24]), "=f"(d[25]), "=f"(d[26]), "=f"(d[27]), "=f"(d[28]), "=f"(d[29]), "=f"(d[30]), "=f"(d[31]), "=f"(d[32]), "=f"(d[33]), "=f"(d[34]), "=f"(d[35]), "=f"(d[36]), "=f"(d[37]), "=f"(d[38]), "=f"(d[39]), "=f"(d[40]), "=f"(d[41]), "=f"(d[42]), "=f"(d[43]), "=f"(d[44]), "=f"(d[45]), "=f"(d[46]), "=f"(d[47]), "=f"(d[48]), "=f"(d[49]), "=f"(d[50]), "=f"(d[51]), "=f"(d[52]), "=f"(d[53]), "=f"(d[54]), "=f"(d[55]), "=f"(d[56]), "=f"(d[57]), "=f"(d[58]), "=f"(d[59]), "=f"(d[60]), "=f"(d[61]), "=f"(d[62]), "=f"(d[63]), "=f"(d[64]), "=f"(d[65]), "=f"(d[66]), "=f"(d[67]), "=f"(d[68]), "=f"(d[69]), "=f"(d[70]), "=f"(d[71]), "=f"(d[72]), "=f"(d[73]), "=f"(d[74]), "=f"(d[75]), "=f"(d[76]), "=f"(d[77]), "=f"(d[78]), "=f"(d[79]), "=f"(d[80]), "=f"(d[81]), "=f"(d[82]), "=f"(d[83]), "=f"(d[84]), "=f"(d[85]), "=f"(d[86]), "=f"(d[87]), "=f"(d[88]), "=f"(d[89]), "=f"(d[90]), "=f"(d[91]), "=f"(d[92]), "=f"(d[93]), "=f"(d[94]), "=f"(d[95])
    : "r"(da), "r"(db) : "memory");
}
template <int S> __device__ __forceinline__ uint2 wgmma_probe192(float (&d)[S], uint32_t da, uint32_t db, uint32_t b0, uint32_t p0, uint32_t b1, uint32_t p1) {
  uint2 ok;
  asm volatile("{\n.reg .b64 a, b;\n.reg .b32 t, u, h;\n.reg .pred p, q;\nmov.b32 h, 0x40000040;\nwgmma.fence.sync.aligned;\n"
    "add.u32 t, %98, 0;\nadd.u32 u, %99, 0;\nmov.b64 a, {t, h};\nmov.b64 b, {u, h};\n"
    "wgmma.mma_async.sync.aligned.m64n192k16.f32.bf16.bf16 "
    "{%2, %3, %4, %5, %6, %7, %8, %9, %10, %11, %12, %13, %14, %15, %16, %17, %18, %19, %20, %21, %22, %23, %24, %25, %26, %27, %28, %29, %30, %31, %32, %33, %34, %35, %36, %37, %38, %39, %40, %41, %42, %43, %44, %45, %46, %47, %48, %49, %50, %51, %52, %53, %54, %55, %56, %57, %58, %59, %60, %61, %62, %63, %64, %65, %66, %67, %68, %69, %70, %71, %72, %73, %74, %75, %76, %77, %78, %79, %80, %81, %82, %83, %84, %85, %86, %87, %88, %89, %90, %91, %92, %93, %94, %95, %96, %97}, "
    "a, b, 1, 1, 1, 0, 1;\n"
    "add.u32 t, %98, 2;\nadd.u32 u, %99, 128;\nmov.b64 a, {t, h};\nmov.b64 b, {u, h};\n"
    "wgmma.mma_async.sync.aligned.m64n192k16.f32.bf16.bf16 "
    "{%2, %3, %4, %5, %6, %7, %8, %9, %10, %11, %12, %13, %14, %15, %16, %17, %18, %19, %20, %21, %22, %23, %24, %25, %26, %27, %28, %29, %30, %31, %32, %33, %34, %35, %36, %37, %38, %39, %40, %41, %42, %43, %44, %45, %46, %47, %48, %49, %50, %51, %52, %53, %54, %55, %56, %57, %58, %59, %60, %61, %62, %63, %64, %65, %66, %67, %68, %69, %70, %71, %72, %73, %74, %75, %76, %77, %78, %79, %80, %81, %82, %83, %84, %85, %86, %87, %88, %89, %90, %91, %92, %93, %94, %95, %96, %97}, "
    "a, b, 1, 1, 1, 0, 1;\n"
    "mbarrier.test_wait.parity.shared::cta.b64 p, [%100], %101;\nmbarrier.test_wait.parity.shared::cta.b64 q, [%102], %103;\n"
    "add.u32 t, %98, 4;\nadd.u32 u, %99, 256;\nmov.b64 a, {t, h};\nmov.b64 b, {u, h};\n"
    "wgmma.mma_async.sync.aligned.m64n192k16.f32.bf16.bf16 "
    "{%2, %3, %4, %5, %6, %7, %8, %9, %10, %11, %12, %13, %14, %15, %16, %17, %18, %19, %20, %21, %22, %23, %24, %25, %26, %27, %28, %29, %30, %31, %32, %33, %34, %35, %36, %37, %38, %39, %40, %41, %42, %43, %44, %45, %46, %47, %48, %49, %50, %51, %52, %53, %54, %55, %56, %57, %58, %59, %60, %61, %62, %63, %64, %65, %66, %67, %68, %69, %70, %71, %72, %73, %74, %75, %76, %77, %78, %79, %80, %81, %82, %83, %84, %85, %86, %87, %88, %89, %90, %91, %92, %93, %94, %95, %96, %97}, "
    "a, b, 1, 1, 1, 0, 1;\n"
    "add.u32 t, %98, 6;\nadd.u32 u, %99, 384;\nmov.b64 a, {t, h};\nmov.b64 b, {u, h};\n"
    "wgmma.mma_async.sync.aligned.m64n192k16.f32.bf16.bf16 "
    "{%2, %3, %4, %5, %6, %7, %8, %9, %10, %11, %12, %13, %14, %15, %16, %17, %18, %19, %20, %21, %22, %23, %24, %25, %26, %27, %28, %29, %30, %31, %32, %33, %34, %35, %36, %37, %38, %39, %40, %41, %42, %43, %44, %45, %46, %47, %48, %49, %50, %51, %52, %53, %54, %55, %56, %57, %58, %59, %60, %61, %62, %63, %64, %65, %66, %67, %68, %69, %70, %71, %72, %73, %74, %75, %76, %77, %78, %79, %80, %81, %82, %83, %84, %85, %86, %87, %88, %89, %90, %91, %92, %93, %94, %95, %96, %97}, "
    "a, b, 1, 1, 1, 0, 1;\n"
    "wgmma.commit_group.sync.aligned;\nselp.u32 %0, 1, 0, p;\nselp.u32 %1, 1, 0, q;\n}"
    : "=r"(ok.x), "=r"(ok.y), "+f"(d[0]), "+f"(d[1]), "+f"(d[2]), "+f"(d[3]), "+f"(d[4]), "+f"(d[5]), "+f"(d[6]), "+f"(d[7]), "+f"(d[8]), "+f"(d[9]), "+f"(d[10]), "+f"(d[11]), "+f"(d[12]), "+f"(d[13]), "+f"(d[14]), "+f"(d[15]), "+f"(d[16]), "+f"(d[17]), "+f"(d[18]), "+f"(d[19]), "+f"(d[20]), "+f"(d[21]), "+f"(d[22]), "+f"(d[23]), "+f"(d[24]), "+f"(d[25]), "+f"(d[26]), "+f"(d[27]), "+f"(d[28]), "+f"(d[29]), "+f"(d[30]), "+f"(d[31]), "+f"(d[32]), "+f"(d[33]), "+f"(d[34]), "+f"(d[35]), "+f"(d[36]), "+f"(d[37]), "+f"(d[38]), "+f"(d[39]), "+f"(d[40]), "+f"(d[41]), "+f"(d[42]), "+f"(d[43]), "+f"(d[44]), "+f"(d[45]), "+f"(d[46]), "+f"(d[47]), "+f"(d[48]), "+f"(d[49]), "+f"(d[50]), "+f"(d[51]), "+f"(d[52]), "+f"(d[53]), "+f"(d[54]), "+f"(d[55]), "+f"(d[56]), "+f"(d[57]), "+f"(d[58]), "+f"(d[59]), "+f"(d[60]), "+f"(d[61]), "+f"(d[62]), "+f"(d[63]), "+f"(d[64]), "+f"(d[65]), "+f"(d[66]), "+f"(d[67]), "+f"(d[68]), "+f"(d[69]), "+f"(d[70]), "+f"(d[71]), "+f"(d[72]), "+f"(d[73]), "+f"(d[74]), "+f"(d[75]), "+f"(d[76]), "+f"(d[77]), "+f"(d[78]), "+f"(d[79]), "+f"(d[80]), "+f"(d[81]), "+f"(d[82]), "+f"(d[83]), "+f"(d[84]), "+f"(d[85]), "+f"(d[86]), "+f"(d[87]), "+f"(d[88]), "+f"(d[89]), "+f"(d[90]), "+f"(d[91]), "+f"(d[92]), "+f"(d[93]), "+f"(d[94]), "+f"(d[95])
    : "r"(da), "r"(db), "r"(b0), "r"(p0), "r"(b1), "r"(p1) : "memory");
  return ok;
}
template <int S> __device__ __forceinline__ void wgmma_first256(float (&d)[S], uint32_t da, uint32_t db) {
  asm volatile("{\n.reg .b64 a, b;\n.reg .b32 t, u, h;\n.reg .pred p, q;\nmov.b32 h, 0x40000040;\nwgmma.fence.sync.aligned;\n"
    "add.u32 t, %128, 0;\nadd.u32 u, %129, 0;\nmov.b64 a, {t, h};\nmov.b64 b, {u, h};\n"
    "wgmma.mma_async.sync.aligned.m64n256k16.f32.bf16.bf16 "
    "{%0, %1, %2, %3, %4, %5, %6, %7, %8, %9, %10, %11, %12, %13, %14, %15, %16, %17, %18, %19, %20, %21, %22, %23, %24, %25, %26, %27, %28, %29, %30, %31, %32, %33, %34, %35, %36, %37, %38, %39, %40, %41, %42, %43, %44, %45, %46, %47, %48, %49, %50, %51, %52, %53, %54, %55, %56, %57, %58, %59, %60, %61, %62, %63, %64, %65, %66, %67, %68, %69, %70, %71, %72, %73, %74, %75, %76, %77, %78, %79, %80, %81, %82, %83, %84, %85, %86, %87, %88, %89, %90, %91, %92, %93, %94, %95, %96, %97, %98, %99, %100, %101, %102, %103, %104, %105, %106, %107, %108, %109, %110, %111, %112, %113, %114, %115, %116, %117, %118, %119, %120, %121, %122, %123, %124, %125, %126, %127}, "
    "a, b, 0, 1, 1, 0, 1;\n"
    "add.u32 t, %128, 2;\nadd.u32 u, %129, 128;\nmov.b64 a, {t, h};\nmov.b64 b, {u, h};\n"
    "wgmma.mma_async.sync.aligned.m64n256k16.f32.bf16.bf16 "
    "{%0, %1, %2, %3, %4, %5, %6, %7, %8, %9, %10, %11, %12, %13, %14, %15, %16, %17, %18, %19, %20, %21, %22, %23, %24, %25, %26, %27, %28, %29, %30, %31, %32, %33, %34, %35, %36, %37, %38, %39, %40, %41, %42, %43, %44, %45, %46, %47, %48, %49, %50, %51, %52, %53, %54, %55, %56, %57, %58, %59, %60, %61, %62, %63, %64, %65, %66, %67, %68, %69, %70, %71, %72, %73, %74, %75, %76, %77, %78, %79, %80, %81, %82, %83, %84, %85, %86, %87, %88, %89, %90, %91, %92, %93, %94, %95, %96, %97, %98, %99, %100, %101, %102, %103, %104, %105, %106, %107, %108, %109, %110, %111, %112, %113, %114, %115, %116, %117, %118, %119, %120, %121, %122, %123, %124, %125, %126, %127}, "
    "a, b, 1, 1, 1, 0, 1;\n"
    "add.u32 t, %128, 4;\nadd.u32 u, %129, 256;\nmov.b64 a, {t, h};\nmov.b64 b, {u, h};\n"
    "wgmma.mma_async.sync.aligned.m64n256k16.f32.bf16.bf16 "
    "{%0, %1, %2, %3, %4, %5, %6, %7, %8, %9, %10, %11, %12, %13, %14, %15, %16, %17, %18, %19, %20, %21, %22, %23, %24, %25, %26, %27, %28, %29, %30, %31, %32, %33, %34, %35, %36, %37, %38, %39, %40, %41, %42, %43, %44, %45, %46, %47, %48, %49, %50, %51, %52, %53, %54, %55, %56, %57, %58, %59, %60, %61, %62, %63, %64, %65, %66, %67, %68, %69, %70, %71, %72, %73, %74, %75, %76, %77, %78, %79, %80, %81, %82, %83, %84, %85, %86, %87, %88, %89, %90, %91, %92, %93, %94, %95, %96, %97, %98, %99, %100, %101, %102, %103, %104, %105, %106, %107, %108, %109, %110, %111, %112, %113, %114, %115, %116, %117, %118, %119, %120, %121, %122, %123, %124, %125, %126, %127}, "
    "a, b, 1, 1, 1, 0, 1;\n"
    "add.u32 t, %128, 6;\nadd.u32 u, %129, 384;\nmov.b64 a, {t, h};\nmov.b64 b, {u, h};\n"
    "wgmma.mma_async.sync.aligned.m64n256k16.f32.bf16.bf16 "
    "{%0, %1, %2, %3, %4, %5, %6, %7, %8, %9, %10, %11, %12, %13, %14, %15, %16, %17, %18, %19, %20, %21, %22, %23, %24, %25, %26, %27, %28, %29, %30, %31, %32, %33, %34, %35, %36, %37, %38, %39, %40, %41, %42, %43, %44, %45, %46, %47, %48, %49, %50, %51, %52, %53, %54, %55, %56, %57, %58, %59, %60, %61, %62, %63, %64, %65, %66, %67, %68, %69, %70, %71, %72, %73, %74, %75, %76, %77, %78, %79, %80, %81, %82, %83, %84, %85, %86, %87, %88, %89, %90, %91, %92, %93, %94, %95, %96, %97, %98, %99, %100, %101, %102, %103, %104, %105, %106, %107, %108, %109, %110, %111, %112, %113, %114, %115, %116, %117, %118, %119, %120, %121, %122, %123, %124, %125, %126, %127}, "
    "a, b, 1, 1, 1, 0, 1;\n"
    "wgmma.commit_group.sync.aligned;\n}"
    : "=f"(d[0]), "=f"(d[1]), "=f"(d[2]), "=f"(d[3]), "=f"(d[4]), "=f"(d[5]), "=f"(d[6]), "=f"(d[7]), "=f"(d[8]), "=f"(d[9]), "=f"(d[10]), "=f"(d[11]), "=f"(d[12]), "=f"(d[13]), "=f"(d[14]), "=f"(d[15]), "=f"(d[16]), "=f"(d[17]), "=f"(d[18]), "=f"(d[19]), "=f"(d[20]), "=f"(d[21]), "=f"(d[22]), "=f"(d[23]), "=f"(d[24]), "=f"(d[25]), "=f"(d[26]), "=f"(d[27]), "=f"(d[28]), "=f"(d[29]), "=f"(d[30]), "=f"(d[31]), "=f"(d[32]), "=f"(d[33]), "=f"(d[34]), "=f"(d[35]), "=f"(d[36]), "=f"(d[37]), "=f"(d[38]), "=f"(d[39]), "=f"(d[40]), "=f"(d[41]), "=f"(d[42]), "=f"(d[43]), "=f"(d[44]), "=f"(d[45]), "=f"(d[46]), "=f"(d[47]), "=f"(d[48]), "=f"(d[49]), "=f"(d[50]), "=f"(d[51]), "=f"(d[52]), "=f"(d[53]), "=f"(d[54]), "=f"(d[55]), "=f"(d[56]), "=f"(d[57]), "=f"(d[58]), "=f"(d[59]), "=f"(d[60]), "=f"(d[61]), "=f"(d[62]), "=f"(d[63]), "=f"(d[64]), "=f"(d[65]), "=f"(d[66]), "=f"(d[67]), "=f"(d[68]), "=f"(d[69]), "=f"(d[70]), "=f"(d[71]), "=f"(d[72]), "=f"(d[73]), "=f"(d[74]), "=f"(d[75]), "=f"(d[76]), "=f"(d[77]), "=f"(d[78]), "=f"(d[79]), "=f"(d[80]), "=f"(d[81]), "=f"(d[82]), "=f"(d[83]), "=f"(d[84]), "=f"(d[85]), "=f"(d[86]), "=f"(d[87]), "=f"(d[88]), "=f"(d[89]), "=f"(d[90]), "=f"(d[91]), "=f"(d[92]), "=f"(d[93]), "=f"(d[94]), "=f"(d[95]), "=f"(d[96]), "=f"(d[97]), "=f"(d[98]), "=f"(d[99]), "=f"(d[100]), "=f"(d[101]), "=f"(d[102]), "=f"(d[103]), "=f"(d[104]), "=f"(d[105]), "=f"(d[106]), "=f"(d[107]), "=f"(d[108]), "=f"(d[109]), "=f"(d[110]), "=f"(d[111]), "=f"(d[112]), "=f"(d[113]), "=f"(d[114]), "=f"(d[115]), "=f"(d[116]), "=f"(d[117]), "=f"(d[118]), "=f"(d[119]), "=f"(d[120]), "=f"(d[121]), "=f"(d[122]), "=f"(d[123]), "=f"(d[124]), "=f"(d[125]), "=f"(d[126]), "=f"(d[127])
    : "r"(da), "r"(db) : "memory");
}
template <int S> __device__ __forceinline__ void wgmma_acc256(float (&d)[S], uint32_t da, uint32_t db) {
  asm volatile("{\n.reg .b64 a, b;\n.reg .b32 t, u, h;\n.reg .pred p, q;\nmov.b32 h, 0x40000040;\nwgmma.fence.sync.aligned;\n"
    "add.u32 t, %128, 0;\nadd.u32 u, %129, 0;\nmov.b64 a, {t, h};\nmov.b64 b, {u, h};\n"
    "wgmma.mma_async.sync.aligned.m64n256k16.f32.bf16.bf16 "
    "{%0, %1, %2, %3, %4, %5, %6, %7, %8, %9, %10, %11, %12, %13, %14, %15, %16, %17, %18, %19, %20, %21, %22, %23, %24, %25, %26, %27, %28, %29, %30, %31, %32, %33, %34, %35, %36, %37, %38, %39, %40, %41, %42, %43, %44, %45, %46, %47, %48, %49, %50, %51, %52, %53, %54, %55, %56, %57, %58, %59, %60, %61, %62, %63, %64, %65, %66, %67, %68, %69, %70, %71, %72, %73, %74, %75, %76, %77, %78, %79, %80, %81, %82, %83, %84, %85, %86, %87, %88, %89, %90, %91, %92, %93, %94, %95, %96, %97, %98, %99, %100, %101, %102, %103, %104, %105, %106, %107, %108, %109, %110, %111, %112, %113, %114, %115, %116, %117, %118, %119, %120, %121, %122, %123, %124, %125, %126, %127}, "
    "a, b, 1, 1, 1, 0, 1;\n"
    "add.u32 t, %128, 2;\nadd.u32 u, %129, 128;\nmov.b64 a, {t, h};\nmov.b64 b, {u, h};\n"
    "wgmma.mma_async.sync.aligned.m64n256k16.f32.bf16.bf16 "
    "{%0, %1, %2, %3, %4, %5, %6, %7, %8, %9, %10, %11, %12, %13, %14, %15, %16, %17, %18, %19, %20, %21, %22, %23, %24, %25, %26, %27, %28, %29, %30, %31, %32, %33, %34, %35, %36, %37, %38, %39, %40, %41, %42, %43, %44, %45, %46, %47, %48, %49, %50, %51, %52, %53, %54, %55, %56, %57, %58, %59, %60, %61, %62, %63, %64, %65, %66, %67, %68, %69, %70, %71, %72, %73, %74, %75, %76, %77, %78, %79, %80, %81, %82, %83, %84, %85, %86, %87, %88, %89, %90, %91, %92, %93, %94, %95, %96, %97, %98, %99, %100, %101, %102, %103, %104, %105, %106, %107, %108, %109, %110, %111, %112, %113, %114, %115, %116, %117, %118, %119, %120, %121, %122, %123, %124, %125, %126, %127}, "
    "a, b, 1, 1, 1, 0, 1;\n"
    "add.u32 t, %128, 4;\nadd.u32 u, %129, 256;\nmov.b64 a, {t, h};\nmov.b64 b, {u, h};\n"
    "wgmma.mma_async.sync.aligned.m64n256k16.f32.bf16.bf16 "
    "{%0, %1, %2, %3, %4, %5, %6, %7, %8, %9, %10, %11, %12, %13, %14, %15, %16, %17, %18, %19, %20, %21, %22, %23, %24, %25, %26, %27, %28, %29, %30, %31, %32, %33, %34, %35, %36, %37, %38, %39, %40, %41, %42, %43, %44, %45, %46, %47, %48, %49, %50, %51, %52, %53, %54, %55, %56, %57, %58, %59, %60, %61, %62, %63, %64, %65, %66, %67, %68, %69, %70, %71, %72, %73, %74, %75, %76, %77, %78, %79, %80, %81, %82, %83, %84, %85, %86, %87, %88, %89, %90, %91, %92, %93, %94, %95, %96, %97, %98, %99, %100, %101, %102, %103, %104, %105, %106, %107, %108, %109, %110, %111, %112, %113, %114, %115, %116, %117, %118, %119, %120, %121, %122, %123, %124, %125, %126, %127}, "
    "a, b, 1, 1, 1, 0, 1;\n"
    "add.u32 t, %128, 6;\nadd.u32 u, %129, 384;\nmov.b64 a, {t, h};\nmov.b64 b, {u, h};\n"
    "wgmma.mma_async.sync.aligned.m64n256k16.f32.bf16.bf16 "
    "{%0, %1, %2, %3, %4, %5, %6, %7, %8, %9, %10, %11, %12, %13, %14, %15, %16, %17, %18, %19, %20, %21, %22, %23, %24, %25, %26, %27, %28, %29, %30, %31, %32, %33, %34, %35, %36, %37, %38, %39, %40, %41, %42, %43, %44, %45, %46, %47, %48, %49, %50, %51, %52, %53, %54, %55, %56, %57, %58, %59, %60, %61, %62, %63, %64, %65, %66, %67, %68, %69, %70, %71, %72, %73, %74, %75, %76, %77, %78, %79, %80, %81, %82, %83, %84, %85, %86, %87, %88, %89, %90, %91, %92, %93, %94, %95, %96, %97, %98, %99, %100, %101, %102, %103, %104, %105, %106, %107, %108, %109, %110, %111, %112, %113, %114, %115, %116, %117, %118, %119, %120, %121, %122, %123, %124, %125, %126, %127}, "
    "a, b, 1, 1, 1, 0, 1;\n"
    "wgmma.commit_group.sync.aligned;\n}"
    : "+f"(d[0]), "+f"(d[1]), "+f"(d[2]), "+f"(d[3]), "+f"(d[4]), "+f"(d[5]), "+f"(d[6]), "+f"(d[7]), "+f"(d[8]), "+f"(d[9]), "+f"(d[10]), "+f"(d[11]), "+f"(d[12]), "+f"(d[13]), "+f"(d[14]), "+f"(d[15]), "+f"(d[16]), "+f"(d[17]), "+f"(d[18]), "+f"(d[19]), "+f"(d[20]), "+f"(d[21]), "+f"(d[22]), "+f"(d[23]), "+f"(d[24]), "+f"(d[25]), "+f"(d[26]), "+f"(d[27]), "+f"(d[28]), "+f"(d[29]), "+f"(d[30]), "+f"(d[31]), "+f"(d[32]), "+f"(d[33]), "+f"(d[34]), "+f"(d[35]), "+f"(d[36]), "+f"(d[37]), "+f"(d[38]), "+f"(d[39]), "+f"(d[40]), "+f"(d[41]), "+f"(d[42]), "+f"(d[43]), "+f"(d[44]), "+f"(d[45]), "+f"(d[46]), "+f"(d[47]), "+f"(d[48]), "+f"(d[49]), "+f"(d[50]), "+f"(d[51]), "+f"(d[52]), "+f"(d[53]), "+f"(d[54]), "+f"(d[55]), "+f"(d[56]), "+f"(d[57]), "+f"(d[58]), "+f"(d[59]), "+f"(d[60]), "+f"(d[61]), "+f"(d[62]), "+f"(d[63]), "+f"(d[64]), "+f"(d[65]), "+f"(d[66]), "+f"(d[67]), "+f"(d[68]), "+f"(d[69]), "+f"(d[70]), "+f"(d[71]), "+f"(d[72]), "+f"(d[73]), "+f"(d[74]), "+f"(d[75]), "+f"(d[76]), "+f"(d[77]), "+f"(d[78]), "+f"(d[79]), "+f"(d[80]), "+f"(d[81]), "+f"(d[82]), "+f"(d[83]), "+f"(d[84]), "+f"(d[85]), "+f"(d[86]), "+f"(d[87]), "+f"(d[88]), "+f"(d[89]), "+f"(d[90]), "+f"(d[91]), "+f"(d[92]), "+f"(d[93]), "+f"(d[94]), "+f"(d[95]), "+f"(d[96]), "+f"(d[97]), "+f"(d[98]), "+f"(d[99]), "+f"(d[100]), "+f"(d[101]), "+f"(d[102]), "+f"(d[103]), "+f"(d[104]), "+f"(d[105]), "+f"(d[106]), "+f"(d[107]), "+f"(d[108]), "+f"(d[109]), "+f"(d[110]), "+f"(d[111]), "+f"(d[112]), "+f"(d[113]), "+f"(d[114]), "+f"(d[115]), "+f"(d[116]), "+f"(d[117]), "+f"(d[118]), "+f"(d[119]), "+f"(d[120]), "+f"(d[121]), "+f"(d[122]), "+f"(d[123]), "+f"(d[124]), "+f"(d[125]), "+f"(d[126]), "+f"(d[127])
    : "r"(da), "r"(db) : "memory");
}
template <int S> __device__ __forceinline__ void wgmma_aug192(float (&d)[S], uint32_t a0, uint32_t a1, uint32_t db) {
  asm volatile("{\n.reg .b64 b;\n.reg .b32 h, z;\nmov.b32 h, 0x40000000;\nmov.b32 z, 0;\n"
    "mov.b64 b, {%98, h};\nwgmma.fence.sync.aligned;\n"
    "wgmma.mma_async.sync.aligned.m64n192k16.f32.bf16.bf16 "
    "{%0, %1, %2, %3, %4, %5, %6, %7, %8, %9, %10, %11, %12, %13, %14, %15, %16, %17, %18, %19, %20, %21, %22, %23, %24, %25, %26, %27, %28, %29, %30, %31, %32, %33, %34, %35, %36, %37, %38, %39, %40, %41, %42, %43, %44, %45, %46, %47, %48, %49, %50, %51, %52, %53, %54, %55, %56, %57, %58, %59, %60, %61, %62, %63, %64, %65, %66, %67, %68, %69, %70, %71, %72, %73, %74, %75, %76, %77, %78, %79, %80, %81, %82, %83, %84, %85, %86, %87, %88, %89, %90, %91, %92, %93, %94, %95}, "
    "{%96, %97, z, z}, b, 1, 1, 1, 1;\n"
    "wgmma.commit_group.sync.aligned;\n}"
    : "+f"(d[0]), "+f"(d[1]), "+f"(d[2]), "+f"(d[3]), "+f"(d[4]), "+f"(d[5]), "+f"(d[6]), "+f"(d[7]), "+f"(d[8]), "+f"(d[9]), "+f"(d[10]), "+f"(d[11]), "+f"(d[12]), "+f"(d[13]), "+f"(d[14]), "+f"(d[15]), "+f"(d[16]), "+f"(d[17]), "+f"(d[18]), "+f"(d[19]), "+f"(d[20]), "+f"(d[21]), "+f"(d[22]), "+f"(d[23]), "+f"(d[24]), "+f"(d[25]), "+f"(d[26]), "+f"(d[27]), "+f"(d[28]), "+f"(d[29]), "+f"(d[30]), "+f"(d[31]), "+f"(d[32]), "+f"(d[33]), "+f"(d[34]), "+f"(d[35]), "+f"(d[36]), "+f"(d[37]), "+f"(d[38]), "+f"(d[39]), "+f"(d[40]), "+f"(d[41]), "+f"(d[42]), "+f"(d[43]), "+f"(d[44]), "+f"(d[45]), "+f"(d[46]), "+f"(d[47]), "+f"(d[48]), "+f"(d[49]), "+f"(d[50]), "+f"(d[51]), "+f"(d[52]), "+f"(d[53]), "+f"(d[54]), "+f"(d[55]), "+f"(d[56]), "+f"(d[57]), "+f"(d[58]), "+f"(d[59]), "+f"(d[60]), "+f"(d[61]), "+f"(d[62]), "+f"(d[63]), "+f"(d[64]), "+f"(d[65]), "+f"(d[66]), "+f"(d[67]), "+f"(d[68]), "+f"(d[69]), "+f"(d[70]), "+f"(d[71]), "+f"(d[72]), "+f"(d[73]), "+f"(d[74]), "+f"(d[75]), "+f"(d[76]), "+f"(d[77]), "+f"(d[78]), "+f"(d[79]), "+f"(d[80]), "+f"(d[81]), "+f"(d[82]), "+f"(d[83]), "+f"(d[84]), "+f"(d[85]), "+f"(d[86]), "+f"(d[87]), "+f"(d[88]), "+f"(d[89]), "+f"(d[90]), "+f"(d[91]), "+f"(d[92]), "+f"(d[93]), "+f"(d[94]), "+f"(d[95])
    : "r"(a0), "r"(a1), "r"(db) : "memory");
}
template <int S> __device__ __forceinline__ void wgmma_aug256(float (&d)[S], uint32_t a0, uint32_t a1, uint32_t db) {
  asm volatile("{\n.reg .b64 b;\n.reg .b32 h, z;\nmov.b32 h, 0x40000000;\nmov.b32 z, 0;\n"
    "mov.b64 b, {%130, h};\nwgmma.fence.sync.aligned;\n"
    "wgmma.mma_async.sync.aligned.m64n256k16.f32.bf16.bf16 "
    "{%0, %1, %2, %3, %4, %5, %6, %7, %8, %9, %10, %11, %12, %13, %14, %15, %16, %17, %18, %19, %20, %21, %22, %23, %24, %25, %26, %27, %28, %29, %30, %31, %32, %33, %34, %35, %36, %37, %38, %39, %40, %41, %42, %43, %44, %45, %46, %47, %48, %49, %50, %51, %52, %53, %54, %55, %56, %57, %58, %59, %60, %61, %62, %63, %64, %65, %66, %67, %68, %69, %70, %71, %72, %73, %74, %75, %76, %77, %78, %79, %80, %81, %82, %83, %84, %85, %86, %87, %88, %89, %90, %91, %92, %93, %94, %95, %96, %97, %98, %99, %100, %101, %102, %103, %104, %105, %106, %107, %108, %109, %110, %111, %112, %113, %114, %115, %116, %117, %118, %119, %120, %121, %122, %123, %124, %125, %126, %127}, "
    "{%128, %129, z, z}, b, 1, 1, 1, 1;\n"
    "wgmma.commit_group.sync.aligned;\n}"
    : "+f"(d[0]), "+f"(d[1]), "+f"(d[2]), "+f"(d[3]), "+f"(d[4]), "+f"(d[5]), "+f"(d[6]), "+f"(d[7]), "+f"(d[8]), "+f"(d[9]), "+f"(d[10]), "+f"(d[11]), "+f"(d[12]), "+f"(d[13]), "+f"(d[14]), "+f"(d[15]), "+f"(d[16]), "+f"(d[17]), "+f"(d[18]), "+f"(d[19]), "+f"(d[20]), "+f"(d[21]), "+f"(d[22]), "+f"(d[23]), "+f"(d[24]), "+f"(d[25]), "+f"(d[26]), "+f"(d[27]), "+f"(d[28]), "+f"(d[29]), "+f"(d[30]), "+f"(d[31]), "+f"(d[32]), "+f"(d[33]), "+f"(d[34]), "+f"(d[35]), "+f"(d[36]), "+f"(d[37]), "+f"(d[38]), "+f"(d[39]), "+f"(d[40]), "+f"(d[41]), "+f"(d[42]), "+f"(d[43]), "+f"(d[44]), "+f"(d[45]), "+f"(d[46]), "+f"(d[47]), "+f"(d[48]), "+f"(d[49]), "+f"(d[50]), "+f"(d[51]), "+f"(d[52]), "+f"(d[53]), "+f"(d[54]), "+f"(d[55]), "+f"(d[56]), "+f"(d[57]), "+f"(d[58]), "+f"(d[59]), "+f"(d[60]), "+f"(d[61]), "+f"(d[62]), "+f"(d[63]), "+f"(d[64]), "+f"(d[65]), "+f"(d[66]), "+f"(d[67]), "+f"(d[68]), "+f"(d[69]), "+f"(d[70]), "+f"(d[71]), "+f"(d[72]), "+f"(d[73]), "+f"(d[74]), "+f"(d[75]), "+f"(d[76]), "+f"(d[77]), "+f"(d[78]), "+f"(d[79]), "+f"(d[80]), "+f"(d[81]), "+f"(d[82]), "+f"(d[83]), "+f"(d[84]), "+f"(d[85]), "+f"(d[86]), "+f"(d[87]), "+f"(d[88]), "+f"(d[89]), "+f"(d[90]), "+f"(d[91]), "+f"(d[92]), "+f"(d[93]), "+f"(d[94]), "+f"(d[95]), "+f"(d[96]), "+f"(d[97]), "+f"(d[98]), "+f"(d[99]), "+f"(d[100]), "+f"(d[101]), "+f"(d[102]), "+f"(d[103]), "+f"(d[104]), "+f"(d[105]), "+f"(d[106]), "+f"(d[107]), "+f"(d[108]), "+f"(d[109]), "+f"(d[110]), "+f"(d[111]), "+f"(d[112]), "+f"(d[113]), "+f"(d[114]), "+f"(d[115]), "+f"(d[116]), "+f"(d[117]), "+f"(d[118]), "+f"(d[119]), "+f"(d[120]), "+f"(d[121]), "+f"(d[122]), "+f"(d[123]), "+f"(d[124]), "+f"(d[125]), "+f"(d[126]), "+f"(d[127])
    : "r"(a0), "r"(a1), "r"(db) : "memory");
}

__device__ __forceinline__ uint32_t clock32() { uint32_t c; asm volatile("mov.u32 %0, %%clock;" : "=r"(c)); return c; }
__device__ __forceinline__ void spin_until(uint32_t c) {
  asm volatile("{\n.reg .pred p;\n.reg .s32 t;\nLAB_WAIT:\nmov.u32 t, %%clock;\nsub.s32 t, t, %0;\nsetp.lt.s32 p, t, 0;\n@p bra.uni LAB_WAIT;\n}" ::"r"(c) : "memory");
}
struct Nop { __device__ __forceinline__ void operator()(int) const {} };
template <int V> struct IC { static constexpr int v = V; };
struct Pipe {
  uint32_t p, g8, a8, aph, tph, aend, curB, curA, prevB, prevA, bo, so, sph, hold;
  uint2 nx;
  int w; bool l0;
  __device__ __forceinline__ int lane() const { return LSO ? (so >> 5) & 31 : threadIdx.x & 31; }
  __device__ __forceinline__ void adv_a() { a8 += 8; if (a8 == aend) { a8 -= NA * 8; aph ^= 1; } }
  __device__ __forceinline__ uint32_t take() { const uint32_t a = SB + OFF_A + a8 * 1024; adv_a(); return a; }
  __device__ __forceinline__ uint32_t ahead(int d) const { uint32_t ls = a8 + d * 8; if (ls >= aend) ls -= NA * 8; return SB + OFF_A + ls * 1024; }
  __device__ __forceinline__ uint32_t wait_ahead(int d) {
    uint32_t ls = a8 + d * 8, lp = aph;
    if (ls >= aend) { ls -= NA * 8; lp ^= 1; }
    mbar_spin(SB + BAR_FULLA + ls, lp);
    return SB + OFF_A + ls * 1024;
  }
  template <int N, bool FIRST, int S> __device__ __forceinline__ uint2 iss(float (&acc)[S], bool skip) {
    if (p + N / 64 > 16) p = 0;
    const uint32_t da = (((SB + OFF_A) >> 4) | (1u << 16)) + a8 * 64;
    const uint32_t db = (((SB + OFF_B) >> 4) | (512u << 16)) + p * 512;
    prevB = curB; prevA = curA;
    curB = g8 & 56; curA = a8;
    p += N / 64; g8 += 8;
    a8 += skip ? 16 : 8;
    if (a8 >= aend) { a8 -= NA * 8; aph ^= 1; }
    uint2 ok = make_uint2(0, 0);
    if constexpr (N == 128) {
      if (FIRST) wgmma_first128(acc, da, db);
      else ok = wgmma_probe128(acc, da, db, SB + BAR_FULLB + (g8 & 56), (g8 >> 6) & 1, SB + BAR_FULLA + a8, aph);
    }
    if constexpr (N == 192) {
      if (FIRST) wgmma_first192(acc, da, db);
      else ok = wgmma_probe192(acc, da, db, SB + BAR_FULLB + (g8 & 56), (g8 >> 6) & 1, SB + BAR_FULLA + a8, aph);
    }
    if constexpr (N == 256) { if (FIRST) wgmma_first256(acc, da, db); else wgmma_acc256(acc, da, db); }
    return ok;
  }
  __device__ __forceinline__ void ensure(uint2 ok) {
    asm volatile(
        "{\n.reg .pred p, q;\nsetp.ne.u32 p, %4, 0;\nsetp.ne.u32 q, %5, 0;\n@!p bra.uni LAB_WAIT;\n@q bra.uni DONE;\n"
        "LAB_WAIT:\nmbarrier.try_wait.parity.shared::cta.b64 p, [%0], %1;\nmbarrier.try_wait.parity.shared::cta.b64 q, [%2], %3;\n"
        "and.pred p, p, q;\n@!p bra.uni LAB_WAIT;\nDONE:\n}" ::"r"(SB + BAR_FULLB + (g8 & 56)), "r"((g8 >> 6) & 1), "r"(SB + BAR_FULLA + a8), "r"(aph), "r"(ok.x), "r"(ok.y) : "memory");
  }
  template <class Hook> __device__ __forceinline__ void validate(bool check, const CUtensorMap* tm16, int c0, int c1, int wp, int j, Hook hook) {
    const uint32_t rows = SB + OFF_A + a8 * 1024 + wp * 2048, ad = a8 * 1024 + so;
    uint32_t v0 = 0, v1 = 0;
    asm volatile("{\n.reg .pred p;\nsetp.ne.u32 p, %3, 0;\n@p ld.shared.b32 %0, [%2];\n@p ld.shared.b32 %1, [%2 + 1024];\n}" : "+r"(v0), "+r"(v1) : "r"(ad), "r"((uint32_t)check));
    check = true;
    hook();
    while (__any_sync(~0u, check && max(v0, v1) == 0xffffffffu)) {
      const uint32_t bar = SB + BAR_SPEC + (w * 4 + wp) * 8;
      e_load<2048>(rows, tm16, c0 + sched_k(c_sched.v[j][g8 >> 3]), c1 + wp * 16, bar);
      mbar_spin(bar, sph);
      sph ^= 1;
      v0 = lds32(ad); v1 = lds32(ad + 1024);
    }
  }
  __device__ __forceinline__ void drain() {
    wg_wait<0>();
    arrive_2(SB + BAR_EMPTYB + curB, SB + BAR_EMPTYA + curA, l0);
    curB = BAR_DUMMY - BAR_EMPTYB; curA = BAR_DUMMY - BAR_EMPTYA;
  }
  __device__ __forceinline__ void signal_server(uint32_t odd) { __syncwarp(); arrive_n(SB + BAR_SRV + w * 16 + odd * 8, l0); }
  __device__ __forceinline__ void signal_loader() { __syncwarp(); arrive_n(SB + BAR_STG + w * 8, l0); }
  template <int N, bool HOLD = false, int S, class Pre = Nop> __device__ __forceinline__ void begin(float (&acc)[S], uint32_t p0, int proft, Pre pre = Pre()) {
    p = p0;
    const uint32_t c1 = HOLD && !HPF ? clock32() : 0;
    if (HOLD && HPF)
      asm volatile("{\n.reg .pred p;\n.reg .s32 t, c;\nsetp.lt.u32 p, %0, 48;\n@p bra.uni DONE;\nmov.u32 c, %%clock;\nadd.s32 c, c, %0;\n"
                   "LAB_WAIT:\nmov.u32 t, %%clock;\nsub.s32 t, t, c;\nsetp.lt.s32 p, t, 0;\n@p bra.uni LAB_WAIT;\nDONE:\n}" ::"r"(hold) : "memory");
    ensure(PRB ? nx : make_uint2(0, 0));
    if (HOLD && !HPF) spin_until(c1 + lds32(SB + OFF_HOLD + w * 4));
    pre(0);
    PROF_T(w, proft, 0);
    ensure(iss<N, true>(acc, false));
  }
  template <int N, bool ENSURE = true, int S, class Hook, class Mid = Nop> __device__ __forceinline__ void run(float (&acc)[S], int i0, int i1, uint32_t skips, int pause, Hook hook, int imid = -1, Mid mid = Mid()) {
    int i = i0, ev = imid >= 0 ? imid : (w ? pause : -1);
#pragma unroll 1
    while (true) {
      const uint2 ok = iss<N, false>(acc, (skips >> i) & 1);
      wg_wait<1>();
      arrive_2(SB + BAR_EMPTYB + prevB, SB + BAR_EMPTYA + prevA, l0);
      if (pause >= 0 && i + 1 == i1) { nx = ok; break; }
      if constexpr (ENSURE) { ensure(ok); hook(i); } else hook(i, ok);
      i++;
      if (pause < 0 && i == i1) break;
      if (i == ev) {
        const bool ps = w && i == pause;
        if (ps) drain();
        if (i == imid) mid(i);
        if (ps) mbar_spin(SB + BAR_LEAD, tph);
        ev = pause;
      }
    }
  }
  template <int N, bool AUG, int S> __device__ __forceinline__ void end(float (&acc)[S], int ns, uint32_t pa, uint32_t au0, uint32_t au1, int proft) {
    uint32_t augB = 0;
    if (LEARLY) arrive_n(SB + BAR_LEAD + w * (BAR_DUMMY - BAR_LEAD), l0);
    if constexpr (AUG) {
      if (AGK && N == 192)
        asm volatile("{\n.reg .pred p;\nsetp.ne.u32 p, %2, 0;\n@p bra.uni DONE;\nLAB_WAIT:\nmbarrier.try_wait.parity.shared::cta.b64 p, [%0], %1;\n@!p bra.uni LAB_WAIT;\nDONE:\n}"
                     ::"r"(SB + BAR_FULLB + (g8 & 56)), "r"((g8 >> 6) & 1), "r"(nx.x) : "memory");
      else mbar_spin(SB + BAR_FULLB + (g8 & 56), (g8 >> 6) & 1);
      const uint32_t db = (((SB + OFF_B) >> 4) | (64u << 16)) + pa * 512;
      if constexpr (N == 192) wgmma_aug192(acc, au0, au1, db); else wgmma_aug256(acc, au0, au1, db);
      augB = g8 & 56; g8 += 8;
    }
    if (!LEARLY) arrive_n(SB + BAR_LEAD + w * (BAR_DUMMY - BAR_LEAD), l0);
    tph ^= 1;
    if (ns > 0) wait_ahead(ns - 1);
    if (PRB) nx = make_uint2(mbar_test(SB + BAR_FULLB + (g8 & 56), (g8 >> 6) & 1), AUG ? mbar_test(SB + BAR_FULLA + a8, aph) : 1);
    if (HPF && AUG) hold = lds32(SB + OFF_HOLD + w * 4);
    wg_wait<0>();
    arrive_2(SB + BAR_EMPTYB + curB, SB + BAR_EMPTYA + curA, l0);
    if (AUG) arrive_n(SB + BAR_EMPTYB + augB, l0);
    PROF_T(w, proft, 1);
  }
};

__device__ __forceinline__ uint32_t box_addr(uint32_t buf, uint32_t bo, int u) { return (buf + bo) ^ (u * 32); }

__device__ __forceinline__ float bf_round(float x) { return __bfloat162float(__float2bfloat16_rn(x)); }
__device__ __forceinline__ void own_rstd(int w, int wp, int lane, float (&rstd)[2]) {
#pragma unroll
  for (int hh = 0; hh < 2; hh++) rstd[hh] = __uint_as_float(lds32(SB + OFF_RSTD + (w * 72 + 8 + wp * 16 + (lane >> 2) + hh * 8) * 4));
}
__device__ __forceinline__ void stats_fetch(int w, int wp, int lane, uint32_t (&au)[2]) {
  const int g = lane >> 2, q4 = lane & 3;
  float rstd[2];
  own_rstd(w, wp, lane, rstd);
#pragma unroll
  for (int hh = 0; hh < 2; hh++) {
    const float m = __uint_as_float(lds32(SB + OFF_MEAN + (w * 64 + wp * 16 + g + hh * 8) * 4));
    const float v = q4 == 3 ? rcp(rstd[hh]) : -m;
    const float v1 = bf_round(v), v2 = bf_round(v - v1);
    const float p = q4 == 1 ? v2 : (q4 == 2 ? v - v1 - v2 : v1);
    au[hh] = pack_bf16(p, q4 == 3 ? v2 : p);
  }
}

__device__ __forceinline__ void halo_fetch(uint32_t slot, int w, const uint4* src, uint32_t bar) {
  asm volatile("{\n.reg .pred p;\nelect.sync _|p, 0xffffffff;\n@p mbarrier.arrive.expect_tx.shared::cta.b64 _, [%4], 2080;\n"
               "@p cp.async.bulk.shared::cluster.global.mbarrier::complete_tx::bytes [%0], [%2], 2048, [%4];\n"
               "@p cp.async.bulk.shared::cluster.global.mbarrier::complete_tx::bytes [%1], [%3], 32, [%4];\n}"
               ::"r"(slot), "r"(SB + OFF_RSTD + w * 288), "l"(src), "l"(src + 128), "r"(bar) : "memory");
}
struct Attn {
  uint32_t lo[24], hi[24], ha[16], hslot;
  float c[8][4], rstd[2];
  float2 rk[3];
  __device__ __forceinline__ void A(const float (&acc)[96], Pipe& M, int w, int wp, int r, uint4* halo_out) {
    const int lane = M.lane();
    M.signal_loader();
    auto cvt = [&](uint32_t& d, int u) { asm volatile("cvt.rn.bf16x2.f32 %0, %1, %2;" : "=r"(d) : "f"(acc[u + 1]), "f"(acc[u])); };
    auto rest = [&] {
#pragma unroll
      for (int nb = 23; nb >= 0; nb--) {
        cvt(lo[nb], 4 * nb);
        if (nb < 8) cvt(hi[nb], 4 * nb + 2);
        if (nb >= 16) lo[nb] = movm(lo[nb]);
      }
    };
#pragma unroll
    for (int nb = 8; nb < 24; nb++) hi[nb] = pack_bf16(acc[4 * nb + 2], acc[4 * nb + 3]);
    hslot = M.ahead(3);
    const uint32_t hbuf = hslot + wp * 2048 + lane * 16;
#pragma unroll
    for (int nb = 16; nb < 24; nb++) hi[nb] = movm(hi[nb]);
    if (TAR) rest();
    if (wp == 3) {
      if (r < 15) {
#pragma unroll
        for (int p = 0; p < 4; p++) halo_out[p * 32 + lane] = make_uint4(hi[8 + 4 * p] ? hi[8 + 4 * p] : 0x8000u, hi[9 + 4 * p], hi[10 + 4 * p], hi[11 + 4 * p]);
        if (!RSV) {
          const uint32_t rh = lds32(SB + OFF_RSTD + (w * 72 + 64 + (lane & 7)) * 4);
          if (lane < 8) reinterpret_cast<uint32_t*>(halo_out + 128)[lane] = rh ? rh : 0x80000000u;
        }
      }
    } else {
#pragma unroll
      for (int p = 0; p < 4; p++)
        asm volatile("st.shared.v4.b32 [%0], {%1,%2,%3,%4};" ::"r"(hbuf + 2048 + p * 512), "r"(hi[8 + 4 * p]), "r"(hi[9 + 4 * p]), "r"(hi[10 + 4 * p]), "r"(hi[11 + 4 * p]) : "memory");
      __syncwarp();
      arrive_n(SB + BAR_HALO + w * 8, M.l0);
    }
    if (!TAR) rest();
  }
  __device__ __forceinline__ void B(int w, int wp, int lane, uint32_t hph) {
    own_rstd(w, wp, lane, rstd);
    mbar_spin(SB + BAR_HALO + w * 8, hph);
#pragma unroll
    for (int p = 0; p < 4; p++)
      asm volatile("ld.shared.v4.b32 {%0,%1,%2,%3}, [%4];" : "=r"(ha[4 * p]), "=r"(ha[4 * p + 1]), "=r"(ha[4 * p + 2]), "=r"(ha[4 * p + 3]) : "r"(hslot + wp * 2048 + lane * 16 + p * 512) : "memory");
#pragma unroll
    for (int u = 0; u < 3; u++) rk[u] = lds64(SB + OFF_RSTD + (w * 72 + wp * 16 + u * 8 + 2 * (lane & 3)) * 4);
  }
  template <class F> __device__ __forceinline__ void C(int wp, int r, int lane, uint32_t zero, F last) {
    const int g = lane >> 2, q = lane & 3;
    const bool nohalo = (wp == 0) && (r == 0);
    const bool up0 = 2 * q > g, up1 = 2 * q + 1 > g;
    const float sc = 0.17677669529663687f * 1.4426950408889634f;
    const float kx0 = up0 ? rk[0].x : rk[1].x, kx1 = up1 ? rk[0].y : rk[1].y;
    const float ky0 = up0 ? rk[1].x : rk[2].x, ky1 = up1 ? rk[1].y : rk[2].y;
    const float fx = rstd[0] * sc, fy = rstd[1] * sc;
    float sm[2][4] = {}, s0[2][4] = {}, s1[2][4] = {};
#pragma unroll
    for (int ks = 0; ks < 2; ks++)
#pragma unroll
      for (int h = 0; h < 2; h++) {
        const int a = 4 * h + 2 * ks;
        mma16(s0[h], lo[a], hi[a], lo[a + 1], hi[a + 1], lo[8 + a], lo[9 + a]);
        mma16(s1[h], lo[a], hi[a], lo[a + 1], hi[a + 1], hi[8 + a], hi[9 + a]);
      }
#pragma unroll
    for (int u = 0; u < 4; u++) { const int a = 4 * (u & 1) + (u & 2); mma16(sm[u & 1], lo[a], hi[a], lo[a + 1], hi[a + 1], ha[a], ha[a + 1]); }
    uint32_t pf[2][4];
    const uint32_t um = (up0 ? 0xffffu : 0u) | (up1 ? 0xffff0000u : 0u);
#pragma unroll
    for (int h = 0; h < 2; h++) {
      if (nohalo) { sm[h][0] = -INFINITY; sm[h][1] = -INFINITY; }
      float x0 = (up0 ? sm[h][0] : s0[h][0]) * (kx0 * fx), x1 = (up1 ? sm[h][1] : s0[h][1]) * (kx1 * fx);
      float y0 = (up0 ? s0[h][2] : s1[h][2]) * (ky0 * fy), y1 = (up1 ? s0[h][3] : s1[h][3]) * (ky1 * fy);
      float mx = fmaxf(x0, x1), my = fmaxf(y0, y1);
      mx = fmaxf(mx, __shfl_xor_sync(~0u, mx, 1)); my = fmaxf(my, __shfl_xor_sync(~0u, my, 1));
      mx = fmaxf(mx, __shfl_xor_sync(~0u, mx, 2)); my = fmaxf(my, __shfl_xor_sync(~0u, my, 2));
      x0 = ex2(x0 - mx); x1 = ex2(x1 - mx); y0 = ex2(y0 - my); y1 = ex2(y1 - my);
      float sx = x0 + x1, sy = y0 + y1;
      x0 *= kx0; x1 *= kx1; y0 *= ky0; y1 *= ky1;
      sx += __shfl_xor_sync(~0u, sx, 1); sy += __shfl_xor_sync(~0u, sy, 1);
      sx += __shfl_xor_sync(~0u, sx, 2); sy += __shfl_xor_sync(~0u, sy, 2);
      sx = rcp(sx); sy = rcp(sy);
      x0 *= sx; x1 *= sx; y0 *= sy; y1 *= sy;
      const uint32_t px = pack_bf16(x0, x1), py = pack_bf16(y0, y1);
      pf[h][0] = px & um; pf[h][1] = px & ~um; pf[h][2] = py & um; pf[h][3] = py & ~um;
    }
#pragma unroll
    for (int u = 0; u < 4; u++) {
#pragma unroll
      for (int e = 0; e < 4; e++) { c[2 * u][e] = 0.f; c[2 * u + 1][e] = 0.f; }
      mma8(c[2 * u], ha[8 + 2 * u], ha[9 + 2 * u], pf[u >> 1][0]);
      mma8(c[2 * u + 1], lo[16 + 2 * u], lo[17 + 2 * u], pf[u >> 1][2]);
    }
#pragma unroll
    for (int u = 0; u < 4; u++) {
      mma8(c[2 * u], lo[16 + 2 * u], lo[17 + 2 * u], pf[u >> 1][1]);
      mma8(c[2 * u + 1], hi[16 + 2 * u], hi[17 + 2 * u], pf[u >> 1][3]);
    }
    uint32_t dep = 0;
    last();
#pragma unroll
    for (int u = 0; u < (EFIRST == 3 ? 0 : 8); u++) dep |= __float_as_uint(c[u][0]);
    asm volatile("bar.sync %0, 256;" ::"r"(3 + (dep & zero)) : "memory");
  }
  __device__ __forceinline__ void E(Pipe& M, bool urgent) {
#pragma unroll
    for (int u = 0; u < 4; u++)
      asm volatile("stmatrix.sync.aligned.m8n8.x4.trans.shared.b16 [%0], {%1, %2, %3, %4};" ::"r"(box_addr(hslot, M.bo, u)),
                   "r"(pack_bf16(c[2 * u][0], c[2 * u][1])), "r"(pack_bf16(c[2 * u + 1][0], c[2 * u + 1][1])),
                   "r"(pack_bf16(c[2 * u][2], c[2 * u][3])), "r"(pack_bf16(c[2 * u + 1][2], c[2 * u + 1][3])) : "memory");
    __syncwarp();
    arrive_n(SB + (urgent ? BAR_STG + M.w * 8 : BAR_SRV + M.w * 16 + 8), M.l0);
  }
};

__device__ __forceinline__ void epi_res(const float (&acc)[64], const float (&pre)[64], float sc0, float sc1, uint32_t (&xr)[32], Pipe& M, int wp) {
  Pipe T = M;
  const uint32_t buf0 = T.take(), buf1 = T.take();
#pragma unroll
  for (int u = 0; u < 8; u++) {
#pragma unroll
    for (int nb = 2 * u; nb < 2 * u + 2; nb++) {
      xr[2 * nb] = pack_bf16(fmaf(acc[4 * nb], sc0, pre[2 * nb]), fmaf(acc[4 * nb + 1], sc0, pre[32 + 2 * nb]));
      xr[2 * nb + 1] = pack_bf16(fmaf(acc[4 * nb + 2], sc1, pre[2 * nb + 1]), fmaf(acc[4 * nb + 3], sc1, pre[33 + 2 * nb]));
    }
    stsm4(box_addr(u < 4 ? buf0 : buf1, M.bo, u & 3), xr[4 * u], xr[4 * u + 1], xr[4 * u + 2], xr[4 * u + 3]);
    if (u == 3) M.signal_loader();
  }
  __syncwarp();
  arrive_n(SB + BAR_STG2 + M.w * 8, M.l0);
  fence_async_smem();
  if (!NWB) wg_bar(M.w);
}
__device__ __forceinline__ void presum(float (&pre)[64], int lane, float usebias) {
  const uint32_t bias = SB + OFF_VEC + (lane & 3) * 8;
#pragma unroll
  for (int nb = 0; nb < 16; nb++) {
    const float2 b = lds64(bias + nb * 32);
#pragma unroll
    for (int u = 2 * nb; u < 2 * nb + 2; u++) {
      const uint32_t v = __float_as_uint(pre[u]);
      pre[32 + u] = fmaf(b.y, usebias, bf_hi(v)); pre[u] = fmaf(b.x, usebias, bf_lo(v));
    }
  }
}
template <int S, int Q> __device__ __forceinline__ void pack_relu(uint32_t (&o)[Q], const float (&acc)[S]) {
#pragma unroll
  for (int u = 0; u < Q; u++) asm("cvt.rn.relu.bf16x2.f32 %0, %1, %2;" : "=r"(o[u]) : "f"(acc[2 * u + 1]), "f"(acc[2 * u]));
}
__device__ __forceinline__ uint32_t sq_bf16x2(uint32_t a) { uint32_t d; asm("mul.rn.bf16x2 %0, %1, %1;" : "=r"(d) : "r"(a)); return d; }
template <int Q> __device__ __forceinline__ void ffn_stage(const uint32_t (&o)[Q], int i, Pipe& M) {
  i -= M.w;
  if (i == 1 || i == 4 || i == 7 || (Q == 64 && i == 10)) {
    const uint32_t buf = M.wait_ahead(2 - M.w);
#pragma unroll
    for (int b = 0; b < Q / 16; b++)
      if (i == 3 * b + 1) {
#pragma unroll
        for (int u = 4 * b; u < 4 * b + 4; u++)
          stsm4(box_addr(buf, M.bo, u & 3), sq_bf16x2(o[4 * u]), sq_bf16x2(o[4 * u + 1]), sq_bf16x2(o[4 * u + 2]), sq_bf16x2(o[4 * u + 3]));
      }
    M.signal_server((i & 1) ^ (Q == 64));
  }
}

__device__ __forceinline__ void wait_flags(const uint8_t* f, uint32_t tag, int lane) {
  const uint32_t t4 = (tag & 0xff) * 0x01010101u;
  const uint32_t* fp = reinterpret_cast<const uint32_t*>(f) + (lane & (FG / 4 - 1));
  while (__any_sync(~0u, __vsub4(ld_relaxed(fp), t4) & 0x80808080u)) {}
  asm volatile("fence.acquire.gpu;\nfence.proxy.async.global;" ::: "memory");
}
__device__ __forceinline__ uint32_t get_epoch() { mbar_spin(SB + BAR_EPOCH, 0); return __shfl_sync(~0u, lds32(SB + OFF_HOLD + 8), 0); }
__device__ __forceinline__ void aloader(const Params& P, const Ptrs& Q, int bid, int r, int j, int lane, int w, uint32_t e, uint32_t epoch) {
  const uint32_t abase = SB + OFF_A + w * NA * 8192, fbase = SB + BAR_FULLA + w * NA * 8, ebase = SB + BAR_EMPTYA + w * NA * 8;
  uint32_t slot = NPRO, ph = 1, nst = 0, hph = 0, npace = 0;
  int t = -1, kind = -1, a0 = 0, a1 = 0;
  const CUtensorMap* tmA = nullptr;
  uint64_t pol = 0;
  uint4* hin = Q.s->halo[0][0] + (r * 16 + j * 2 + w - 16) * 136;
  uint32_t* const pace = Q.s->pace[0] + (bid & -PG) * 2;
  const uint8_t* const flags = Q.s->flags[r / (FG / 8)][w];
  auto adv = [&] { if (++slot == NA) { slot = 0; ph ^= 1; } };
#pragma unroll 1
  for (int g = NPRO; g <= NSTEP; g++) {
    const uint32_t cur = e;
    e = c_sched.v[j][g + 1];
    if (!(cur & E_RARE)) {
      if (cur & E_HAND) { mbar_spin(ebase + slot * 8, ph); e_arrive(fbase + slot * 8, 1); adv(); }
    } else {
      if (cur & F_NEW) {
        t++; kind = kind == 5 ? 0 : kind + 1;
        const bool narrow = kind == 2 || kind == 5;
        static_assert(TM_XIN == 0 && TM_X == 1 && TM_XA == 2 && TM_O == 3 && TM_H == 4, "map order");
        tmA = &P.tm[t < 2 ? 0 : (0x422311 >> (4 * kind)) & 15];
        pol = ((AEF >> t) & 1) ? 0x12F0000000000000ull : 0x1000000000000000ull;
        a0 = narrow ? 0 : w * 1024; a1 = narrow ? r * 128 + w * 64 : r * 64;
      }
      const bool xo = cur & E_XPUB0;
      uint32_t s = slot;
      if (cur & (E_HAND | E_ATTN | E_XPUB0)) {
        if (cur & E_KEEP) e_arrive(ebase + slot * 8, 4);
#pragma unroll 1
        for (int u = xo ? 0 : 1; u < 2; u++) { mbar_wait(ebase + slot * 8, ph); e_arrive(fbase + slot * 8, 1); adv(); }
      }
      uint32_t hold = 0;
      if ((xo && t < 12) || (cur & F_GATH)) {
        uint32_t v;
        do v = ld_relaxed(pace + npace + (lane & (PG - 1))); while (__any_sync(~0u, (v ^ (epoch * 16 + t - 1)) & 31));
        npace ^= PG;
        hold = min(__reduce_max_sync(~0u, (int)(v - __shfl_sync(~0u, v, bid & (PG - 1)))), 4000) * 27 >> 4;
        asm volatile("st.shared.b32 [%0], %1;" ::"r"(SB + OFF_HOLD + w * 4), "r"(hold) : "memory");
      }
      if (cur & (E_ATTN | E_XPUB0)) {
        const uint32_t s2 = s == NA - 1 ? 0 : s + 1;
        constexpr int NP = NPREPX > NPREPO ? NPREPX : NPREPO;
        uint32_t pf[NP + 1], pk[NP + 1];
        const int np = t == 12 ? 0 : (xo ? NPREPX : NPREPO);
#pragma unroll
        for (int u = 0; u < NP; u++) {
          pf[u] = slot; pk[u] = a0 + sched_k(c_sched.v[j][g + 1 + xo + u]);
          if (u < np) {
            if (u == np - 1) mbar_spin(ebase + slot * 8, ph);
            adv();
          }
        }
        mbar_wait(SB + BAR_STG + w * 8, nst & 1);
        nst++;
        LT(0);
        const uint32_t c1 = clock32();
        e_store(tmA, a0 + sched_k(cur), a1, abase + s * 8192);
        if (xo) {
          mbar_spin(SB + BAR_STG2 + w * 8, ~t & 1);
          e_store(tmA, a0 + sched_k(cur) + 64, a1, abase + s2 * 8192);
        } else e_arrive(SB + BAR_OWN + w * 8, 1);
        LT(1);
        if (t == 12) break;
        spin_until(c1 + hold + (xo ? SDELAY : SDELAYO + (t < 6 ? SDL0 : 0)));
        LT(2);
#pragma unroll
        for (int u = 0; u < NP; u++)
          if (u < np) e_load(abase + pf[u] * 8192, tmA, pk[u], a1, fbase + pf[u] * 8);
        LT(5);
      }
      if (cur & E_SIG) {
        e_arrive(SB + BAR_SRV + w * 16, 4);
      }
      if (cur & E_REL) bulk_wait_all();
      if (cur & E_HALO) {
        mbar_spin(SB + BAR_STG + w * 8, nst & 1);
        nst++;
        const uint32_t hs = abase + (slot >= 3 ? slot - 3 : slot + 3) * 8192, ad = hs + lane * 32 + (lane & 4) * 4;
        if (r == 0) {
#pragma unroll
          for (int p = 0; p < 4; p++) sts128(hs + lane * 16 + p * 512, 0, 0, 0, 0);
          asm volatile("st.shared.b32 [%0], %1;" ::"r"(SB + OFF_RSTD + w * 288 + (lane & 7) * 4), "r"(0x3f800000) : "memory");
        } else {
          spin_until(clock32() + HDELAY);
          do {
            halo_fetch(hs, w, hin, SB + BAR_SPEC + 80 + w * 8);
            mbar_spin(SB + BAR_SPEC + 80 + w * 8, hph);
            hph ^= 1;
          } while (__any_sync(~0u, min(min(lds32(ad), lds32(ad + 1024)), lds32(SB + OFF_RSTD + w * 288)) == 0));
        }
        e_arrive(SB + BAR_HALO + w * 8, 1);
      }
      if ((cur & E_REL) && (kind == 1 || kind == 2) && r > 0) {
        uint4* hz = hin + lane;
        hin += 256 * 136;
#pragma unroll
        for (int p = 0; p < 4; p++) hz[p * 32] = make_uint4(0, 0, 0, 0);
        if (lane < 2) hz[128] = make_uint4(0, 0, 0, 0);
      }
      if (cur & E_WAIT) {
        wait_flags(flags + ((cur & E_PART1) ? FG : 0), epoch * 16 + t, lane);
      }
    }
    if (!(cur & (F_AUG | F_NOA))) {
      mbar_wait(ebase + slot * 8, ph);
      e_load(abase + slot * 8192, tmA, a0 + sched_k(cur), a1, fbase + slot * 8, pol);
      adv();
      if ((cur & F_STAMP) && w == 0) {
        mbar_spin(SB + BAR_EMPTYB + ((g - 6) & 7) * 8, ((g - 6) >> 3) & 1);
        uint32_t stamp;
        asm volatile("mov.u32 %0, %%globaltimer_lo;" : "=r"(stamp));
        asm volatile("st.relaxed.gpu.global.u32 [%0], %1;" ::"l"(pace + npace + (bid & (PG - 1))), "r"((stamp & ~31u) | ((epoch * 16 + t) & 31)) : "memory");
      }
    }
  }
  bulk_wait_all();
}

__device__ __forceinline__ void bloader(const Params& P, const Ptrs& Q, bool aux, int j, int lane, uint32_t e, uint32_t epoch) {
  const uint32_t* const sched = c_sched.v[aux ? 8 : j];
  int kind = -1, c2 = 0, c3 = 0, na = 0;
  const CUtensorMap* tmB = nullptr;
  uint32_t sph = 0, efm = aux ? 0 : BEF * 2;
  uint64_t pol = 0;
#pragma unroll 1
  for (int g = aux ? 8 + (j & 1) : NPRO; g < (aux ? NSTEP_AUX : NSTEP); g += 1 + aux) {
    const uint32_t cur = e;
    e = sched[g + 1 + aux];
    if (cur & F_NEW) {
      kind = kind == 5 ? 0 : kind + ((cur >> 29) & 3);
      static_assert(TM_WQKV == 5 && TM_WO == 6 && TM_W1A == 7 && TM_W1B == 8 && TM_W2 == 9, "map order");
      tmB = &P.tm[(0x978655 >> (4 * kind)) & 15];
      efm >>= 1;
      pol = (efm & 1) ? 0x12F0000000000000ull : 0x1000000000000000ull;
      na = (0x243233 >> (4 * kind)) & 15;
      c2 = ((0x277200 >> (4 * kind)) & 15) * j + (kind == 4 ? 3 : 0);
      c3 = kind <= 1 ? kind * 8 + j : 0;
    }
    const int need = g - (int)((cur >> 5) & 15);
    const uint32_t dst = SB + OFF_B + (cur & 31) * 8192, bar = SB + BAR_FULLB + (g & 7) * 8;
    mbar_wait(SB + BAR_EMPTYB + (need & 7) * 8, (need >> 3) & 1);
    if (!(cur & F_AUG)) {
      asm volatile("{\n.reg .pred p;\nelect.sync _|p, 0xffffffff;\n@p mbarrier.arrive.expect_tx.shared::cta.b64 _, [%2], %7;\n"
                   "@p cp.async.bulk.tensor.4d.shared::cluster.global.mbarrier::complete_tx::bytes.L2::cache_hint [%0], [%1, {%3, %4, %5, %6}], [%2], %8;\n}"
                   ::"r"(dst), "l"(tmB), "r"(bar), "r"(0), "r"(sched_k(cur)), "r"(c2), "r"(c3), "r"(na * 8192), "l"(pol) : "memory");
    } else {
      const bool chk = g < NSTEP / 2;
      const uint32_t b2 = chk ? SB + BAR_AUG : bar, ad = dst + lane * 16 + (lane >> 3) * 4;
      while (true) {
        asm volatile("{\n.reg .pred p;\nelect.sync _|p, 0xffffffff;\n@p mbarrier.arrive.expect_tx.shared::cta.b64 _, [%2], 4096;\n"
                     "@p cp.async.bulk.shared::cluster.global.mbarrier::complete_tx::bytes [%0], [%1], 4096, [%2];\n}"
                     ::"r"(dst), "l"(Q.s->aug[epoch & 1][(kind - (kind >= 3)) * 8 + j]), "r"(b2) : "memory");
        if (!chk) break;
        mbar_spin(b2, sph);
        sph ^= 1;
        uint32_t mn = ~0u;
#pragma unroll
        for (int u = 0; u < 8; u++) mn = min(mn, lds32(ad + u * 512));
        if (!__any_sync(~0u, mn == 0)) { e_arrive(bar, 1); break; }
      }
      __syncwarp();
    }
  }
}

constexpr uint32_t job_slots(int layer) {
  const int pos[10] = {11, 26, 63, 73, 77, 81, 92, 96, 100, 104};
  uint32_t v = 0;
  for (int m = 0; m < 10; m++) v |= (uint32_t)((layer * 148 + pos[m]) % NA) << (3 * m);
  return v;
}
constexpr uint32_t JOB_SLOTS0 = job_slots(0), JOB_SLOTS1 = job_slots(1);
__device__ __forceinline__ void server(const Params& P, const Ptrs& Q, int bid, int r, int j, int lane, uint32_t epoch) {
  if (CPF) spin_until(clock32() + CPF);
  epoch += __shfl_sync(~0u, c_sched.v[j][lane < 18 ? lane * 16 : 0] >> 31, 0);
  {
    const uint2 b = reinterpret_cast<const uint2*>(Q.b2 + j * 128)[lane];
    sts128(SB + OFF_VEC + lane * 16, b.x << 16, b.x & 0xffff0000u, b.y << 16, b.y & 0xffff0000u);
  }
  int hl = 0;
  uint32_t fph = 0, pend = SB + BAR_DUMMY3;
#pragma unroll 1
  for (int n = 0; n < 20; n++) {
    const int layer = n >= 10, m = n - 10 * layer;
    const bool stat = m == 0 || m == 2;
    const uint32_t slot = ((layer ? JOB_SLOTS1 : JOB_SLOTS0) >> (m * 3)) & 7;
    auto fetch = [&](int w) {
      asm volatile("{\n.reg .pred p;\nelect.sync _|p, 0xffffffff;\n@p mbarrier.arrive.expect_tx.shared::cta.b64 _, [%2], 4096;\n"
                   "@p cp.async.bulk.shared::cluster.global.mbarrier::complete_tx::bytes [%0], [%1], 4096, [%2];\n}"
                   ::"r"(SB + OFF_A + (w * NA + slot) * 8192), "l"(&Q.s->stats[hl][r * 32 + w * 16][0][0]), "r"(SB + BAR_SPEC + 64 + w * 8) : "memory");
    };
#pragma unroll 1
    for (int w = 0; w < 2; w++) {
      mbar_spin(SB + BAR_SRV + w * 16 + (n & 1) * 8, (n >> 1) & 1);
      if (stat) fetch(w);
      else {
        e_store(&P.tm[m == 1 ? TM_O : TM_H], m == 1 ? j * 64 : 448 * j + (m - 3) * 64, r * 128 + w * 64, SB + OFF_A + (w * NA + slot) * 8192);
        bulk_wait_read<1>();
        e_arrive(pend, 4);
        pend = SB + BAR_EMPTYA + (w * NA + slot) * 8;
      }
    }
    if (stat) {
#pragma unroll 1
      for (int w = 0; w < 2; w++) {
        const uint32_t src = SB + OFF_A + (w * NA + slot) * 8192 + (lane >> 1) * 256 + ((lane >> 1) & 7) * 32 + (lane & 1) * 16;
        float ms[2], md[2], mq[2], m0[2];
        while (true) {
          mbar_spin(SB + BAR_SPEC + 64 + w * 8, (fph >> w) & 1);
          fph ^= 1u << w;
          uint32_t bad = 0;
          ms[0] = ms[1] = md[0] = md[1] = mq[0] = mq[1] = m0[0] = m0[1] = 0.f;
#pragma unroll 1
          for (int p = 0; p < 8; p += 2) {
            const float4 v2[2] = {lds128(src ^ (p * 32)), lds128(src ^ (p * 32) ^ 32)};
            if (p == 0) { m0[0] = v2[0].x; m0[1] = v2[0].z; }
#pragma unroll
            for (int z = 0; z < 2; z++) {
              const float4 v = v2[z];
              const float a = v.x - m0[0], b = v.z - m0[1];
              bad |= __float_as_uint(v.y) ^ epoch;
              ms[0] += a; md[0] = fmaf(a, a, md[0]); mq[0] += __uint_as_float(__float_as_uint(v.y) & ~63u);
              ms[1] += b; md[1] = fmaf(b, b, md[1]); mq[1] += v.w;
            }
          }
          if (!__any_sync(~0u, bad & 63)) break;
          fetch(w);
          __syncwarp();
        }
        e_arrive(SB + BAR_EMPTYA + (w * NA + slot) * 8, 4);
        const int row = (lane >> 3) * 16 + (lane & 7);
#pragma unroll
        for (int z = 0; z < 2; z++) {
          const float d = ms[z] * 0.125f;
          asm volatile("st.shared.f32 [%0], %1;" ::"r"(SB + OFF_MEAN + (w * 64 + row + z * 8) * 4), "f"(m0[z] + d) : "memory");
          const float rs = rsq(fmaf(mq[z], 1.f / 1024.f, fmaxf(fmaf(md[z], 0.125f, -d * d), 0.f)) + 1e-5f);
          asm volatile("st.shared.f32 [%0], %1;" ::"r"(SB + OFF_RSTD + (w * 72 + 8 + row + z * 8) * 4), "f"(rs) : "memory");
          if (RSV && z && !m && lane >= 24) {
            float* const h = reinterpret_cast<float*>(Q.s->halo[0][0] + 122) + (uint32_t)((hl * 256 + r * 16 + j * 2 + w) * 544 + lane);
            h[0] = h[256 * 544] = rs != 0.f ? rs : -0.f;
          }
        }
        e_arrive(SB + BAR_STAT + w * 8, 8);
      }
    }
    if (stat && n != 12) {
#pragma unroll 1
      for (int u = 0; u < (m ? 2 : 3); u++) {
        const uint32_t pitch = u == 2 ? 448 : 128;
        uint4* p = reinterpret_cast<uint4*>(u == 2 ? Q.s->h : (m ? Q.out : Q.s->x)) + (u == 2 ? 64 + j * 8 : j * 16 + u * 8) + ((r * 128 + (lane >> 3)) * pitch + (lane & 7));
#pragma unroll 1
        for (int k = 0; k < 32 / FUN; k++) {
#pragma unroll
          for (int z = 0; z < FUN; z++) {
            *p = make_uint4(~0u, ~0u, ~0u, ~0u);
            p += 4 * pitch;
            asm volatile("" : "+l"(p));
          }
        }
      }
      __syncwarp();
    }
    if ((0x222 >> m) & 1) {
      bulk_wait_all();
      e_arrive(pend, 4);
      pend = SB + BAR_DUMMY3;
      if (lane < 2) st_release8(&Q.s->flags[r / (FG / 8)][lane][(r & (FG / 8 - 1)) * 8 + j + (m == 9 ? FG : 0)], epoch * 16 + layer * 6 + (m == 1 ? 2 : 5));
      __syncwarp();
    }
    hl += stat;
  }
}

__device__ __forceinline__ void aux_math(const Ptrs& Q, int bid, int jj, int warp, int lane) {
  const int g = lane >> 2, q = lane & 3, c0 = (warp & 3) * 2;
  uint32_t st = warp >> 2, bf[16][4] = {};
  const uint32_t ad0 = SB + ((lane >> 4) * 8 + (lane & 7)) * 128 + (((c0 + ((lane >> 3) & 1)) ^ (lane & 7)) << 4);
#pragma unroll 1
  for (int t = 0; t < 4; t++) {
    float acc[4][4] = {};
    uint32_t bias[8];
#pragma unroll
    for (int a = 0; a < 8; a++) bias[a] = t >= 2 ? reinterpret_cast<const uint32_t*>(Q.b1 + 448 * jj + (t - 2) * 192 + c0 * 8)[(a >> 1) * 32 + (a & 1) * 4 + q] : 0u;
#pragma unroll 1
    for (int i = 0; i < 16; i++, st += 2) {
      const uint32_t ad = ad0 + (c_sched.v[8][st] & 31) * 8192;
      mbar_spin(SB + BAR_FULLB + (st & 7) * 8, (st >> 3) & 1);
#pragma unroll
      for (int u = 0; u < 16; u++)
        asm volatile("{\n.reg .pred p;\nsetp.ne.u32 p, %5, 0;\n@p ldmatrix.sync.aligned.m8n8.x4.trans.shared.b16 {%0,%1,%2,%3}, [%4];\n}"
                     : "+r"(bf[u][0]), "+r"(bf[u][1]), "+r"(bf[u][2]), "+r"(bf[u][3])
                     : "r"(ad + (u & 3) * 8192 + (u >> 2) * 2048), "r"((u & 3) != 3 || t == 3 ? 1 : 0) : "memory");
      __syncwarp();
      e_arrive(SB + BAR_EMPTYB + (st & 7) * 8, 2);
#pragma unroll
      for (int u = 0; u < 16; u++) mma16(acc[u & 3], bf[u][0], bf[u][1], bf[u][2], bf[u][3], 0x3F803F80u, 0x3F803F80u);
    }
    const uint32_t epoch = lds32(SB + OFF_HOLD + 8);
    const uint32_t o = (t * 8 + jj) * 1024 + g * 32 + ((c0 ^ g) << 2) + q + (epoch & 1) * 32768;
    uint32_t *const p0 = Q.s->aug[0][0] + o, *const p1 = Q.s->aug[0][0] + (o ^ 4);
#pragma unroll
    for (int a = 0; a < 8; a++) {
      const float u = acc[a >> 1][(a & 1) * 2];
      uint32_t h = movm(pack_bf16(u, u - bf_round(u)));
      if (g >= 6) h = bias[a];
      ((a & 1) ? p1 : p0)[(a >> 1) * 256] = h ? h : 0x8000u;
    }
    uint4* const z = reinterpret_cast<uint4*>(Q.s->aug[~epoch & 1][t * 8 + jj]) + (threadIdx.x & 127);
    z[0] = z[128] = make_uint4(0, 0, 0, 0);
  }
}

template <bool BYSM> __global__ void __launch_bounds__(NTHREADS, 1) mega_kernel(const __grid_constant__ Ptrs Q, const __grid_constant__ Params P) {
  extern __shared__ __align__(1024) uint8_t smem_raw[];
  constexpr uint32_t sb = SB;
  const uint32_t centry = clock32();
  const int warp = __shfl_sync(~0u, threadIdx.x >> 5, 0), lane = threadIdx.x & 31;
  const int bid = BYSM ? work_id() : blockIdx.x;
  const bool aux = bid >= NMAIN;
  const int r = Q44 ? ((bid >> 5) << 2) | (bid & 3) : ((bid >> 4) << 1) | (bid & 1), j = (aux ? bid * 2 : bid >> (1 + Q44)) & 7;
  PRO(0);
  {
    const uint32_t b = sb + OFF_BAR + warp * 48, cnt = warp < 6 ? 1 : (warp < 10 ? 4 : 8);
    asm volatile("{\n.reg .pred p;\nelect.sync _|p, 0xffffffff;\n@p mbarrier.init.shared::cta.b64 [%0], %1;\n@p mbarrier.init.shared::cta.b64 [%0 + 8], %1;\n"
                 "@p mbarrier.init.shared::cta.b64 [%0 + 16], %1;\n@p mbarrier.init.shared::cta.b64 [%0 + 24], %1;\n"
                 "@p mbarrier.init.shared::cta.b64 [%0 + 32], %1;\n@p mbarrier.init.shared::cta.b64 [%0 + 40], %1;\nfence.mbarrier_init.release.cluster;\n}"
                 ::"r"(b), "r"(cnt) : "memory");
  }
  __syncthreads();
  {
    static_assert(NPRO == 4 && ROUND0 == 0, "prologue stages");
    const int st = ((11 - warp) * (aux ? 32 : 11)) >> 5, op = aux ? (st < 8) * 2 : 11 - warp - 3 * st, sd = aux ? st >> STGX : (op == 2 ? st : st & 2);
    const uint32_t bar0 = sb + OFF_BAR + (op * 6 + st) * 8;
    const int kc = aux ? (st >> 1) * 64 : (st & 2 ? (ROUND1 >> (4 * j)) & 15 : 0) * 128 + (st & 1) * 64;
    spin_until(centry + (sd ? STG0 + sd * STG1 : 0));
    if (op == 2) {
      asm volatile("{\n.reg .pred p;\nelect.sync _|p, 0xffffffff;\n@p mbarrier.arrive.expect_tx.shared::cta.b64 _, [%2], 24576;\n"
                   "@p cp.async.bulk.tensor.4d.shared::cluster.global.mbarrier::complete_tx::bytes [%0], [%1, {%3, %4, %3, %5}], [%2];\n}"
                   ::"r"(sb + OFF_B + (aux ? (st & 1) * 114688 + (st >> 1) * 24576 : (st + 1) * 24576)), "l"(&P.tm[TM_WQKV]), "r"(bar0), "r"(0), "r"(kc), "r"(j + (st & aux)) : "memory");
    } else if (!aux) e_load(sb + OFF_A + (op * 6 + st) * 8192, &P.tm[TM_XIN], op * 1024 + kc, r * 64, bar0);
    PRO(1);
    asm volatile("prefetch.tensormap [%0];" ::"l"(&P.tm[warp]) : "memory");
  }
  if (warp >= 8) {
    asm volatile("setmaxnreg.dec.sync.aligned.u32 24;");
    if (warp == 11) {
      if (smem_u32(smem_raw) != SB) __trap();
      const uint32_t epoch = __shfl_sync(~0u, ld_relaxed(&Q.s->epoch[bid]) + 1, 0);
      Q.s->epoch[bid] = epoch;
      asm volatile("st.shared.b32 [%0], %1;" ::"r"(sb + OFF_HOLD + 8), "r"(epoch) : "memory");
      e_arrive(sb + BAR_EPOCH, 1);
      PRO(2);
      if (!aux) server(P, Q, bid, r, j, lane, epoch);
    } else {
      const uint32_t e = c_sched.v[aux ? 8 : j][aux ? warp : NPRO];
      spin_until(centry + STGL + (e >> 31));
      PRO(2);
      const uint32_t epoch = get_epoch();
      PRO(3);
      if (warp <= 8 + aux) bloader(P, Q, aux, j + warp - 8, lane, e, epoch);
      else if (!aux) aloader(P, Q, bid, r, j, lane, warp - 9, e, epoch);
    }
  } else if (aux) aux_math(Q, bid, j + (warp >> 2), warp, lane);
  else {
    asm volatile("setmaxnreg.inc.sync.aligned.u32 240;");
    const int w = warp >> 2, wp = warp & 3;
    {
      uint32_t xr[32];
#pragma unroll
      for (int u = 0; u < 32; u++) if (NOI) asm volatile("" : "=r"(xr[u])); else xr[u] = 0;
      Pipe M;
      M.p = 0; M.g8 = 0; M.a8 = w * NA * 8; M.aph = 0; M.tph = 0; M.aend = (w + 1) * NA * 8;
      M.curB = M.curA = M.prevB = M.prevA = M.sph = 0; M.nx = make_uint2(0, 0); M.w = w; M.l0 = lane == 0;
      M.bo = (wp * 16 + (lane & 15)) * 128 + (((lane >> 4) ^ (lane & 7)) << 4);
      M.so = __shfl_sync(~0u, SB + OFF_A + wp * 2048 + lane * 32 + (lane >> 2) * 4, lane);
      M.bo = __shfl_sync(~0u, M.bo, lane);
      auto nop = [](int) {};
      const uint32_t zero = gridDim.y - 1;
      PROF_T(w, 0, 3);
      if (STARTC) spin_until(centry + STARTC);
#pragma unroll 1
      for (int hl = 0; hl < 4; hl++) {
        const int t0 = hl * 3;
        const bool ffn = hl & 1;
        float acc[96], acn[64];
        uint32_t au[2] = {0u, 0u};
        {
          const int d = hl ? 0 : ((OWNP * 2u) >> (4 * j)) & 15;
          auto own = [&](auto h, uint32_t dep = 0) {
#pragma unroll
            for (int u = 4 * h.v; u < 4 * h.v + 4; u++)
              asm volatile("ldmatrix.sync.aligned.m8n8.x4.shared.b16 {%0,%1,%2,%3}, [%4];" : "=r"(xr[4 * u]), "=r"(xr[4 * u + 1]), "=r"(xr[4 * u + 2]), "=r"(xr[4 * u + 3])
                           : "r"(box_addr(sb + OFF_A + M.a8 * 1024, M.bo + dep, u & 3)) : "memory");
          };
          M.begin<192>(acc, ffn ? 12 : 3, t0, [&](int) { if (hl + d == 0) own(IC<0>{}); });
          if (hl + d == 0) own(IC<1>{}, (xr[0] | xr[4] | xr[8] | xr[12]) & zero);
          float ss[2] = {0.f, 0.f}, sq[2] = {0.f, 0.f};
          auto part = [&](auto c0, auto n) {
#pragma unroll
            for (int v = 0; v < 4 * n.v; v++) {
              const int u = c0.v + v / n.v * 4 + v % n.v;
              float a, b;
              asm volatile("shl.b32 %0, %2, 16;\nand.b32 %1, %2, 0xffff0000;" : "=f"(a), "=f"(b) : "r"(xr[u]));
              ss[u & 1] += a + b; sq[u & 1] = fmaf(a, a, fmaf(b, b, sq[u & 1]));
            }
          };
          const uint64_t plan = hl ? PLAN1 : (d ? PLAN0 : PLANZ);
          auto todo = [&](int i) { uint64_t v; asm volatile("shr.u64 %0, %1, %2;" : "=l"(v) : "l"(plan), "r"((i + 1 - d) * 8)); return (uint32_t)v; };
          uint32_t m = todo(1);
          M.run<192, false>(acc, 1, 16, 1u << 10, 16 - (ffn ? LEAD3 : LEAD0), [&](int i, uint2 ok) {
           CT(0);
           if (m & 7) {
             if (m & 1) part(IC<0>{}, IC<2>{});
             if (m & 2) part(IC<2>{}, IC<2>{});
             if (m & 4) part(IC<16>{}, IC<1>{});
           }
           CT(1);
           M.ensure(ok);
           CT(3);
           M.validate(hl != 0, &P.tm[ffn ? TM_XA16 : TM_X16], w * 1024, r * 64, wp, j, [&] {
            if (m & 0xf8) {
              if (m & 128) { if (m & 1) own(IC<1>{}); else own(IC<0>{}); }
              if (m & 8) part(IC<17>{}, IC<1>{});
              if (m & 16) part(IC<18>{}, IC<1>{});
              if (m & 32) part(IC<19>{}, IC<1>{});
              if (m & 64) {
                const uint32_t epoch = lds32(sb + OFF_HOLD + 8);
#pragma unroll
                for (int o = 1; o < 4; o *= 2)
#pragma unroll
                  for (int z = 0; z < 2; z++) { ss[z] += __shfl_xor_sync(~0u, ss[z], o); sq[z] += __shfl_xor_sync(~0u, sq[z], o); }
                const float m0 = ss[0] * (1.f / 128.f), m1 = ss[1] * (1.f / 128.f);
                const int rowpair = r * 64 + w * 32 + wp * 8 + (M.lane() >> 2);
                if ((M.lane() & 3) == 0)
                  st_pkt(&Q.s->stats[hl][rowpair >> 1][j][rowpair & 1], __float_as_uint(m0), (__float_as_uint(fmaxf(fmaf(-ss[0], m0, sq[0]), 0.f)) & ~63u) | (epoch & 63),
                         __float_as_uint(m1), __float_as_uint(fmaxf(fmaf(-ss[1], m1, sq[1]), 0.f)));
              }
            }
            m = todo(i + 1);
            if (i == STATI) { mbar_spin(sb + BAR_STAT + w * 8, hl & 1); stats_fetch(w, wp, M.lane(), au); }
           });
           CT(4);
          });
          M.end<192, true>(acc, ffn ? 0 : 4, 15, au[0], au[1], t0);
          PROF_T(w, t0, 2);
        }
        if (!ffn) {
          Attn T;
#pragma unroll 1
          for (int wave = 0; wave < 2; wave++) {
            AP(9);
            uint4* const hp = Q.s->halo[0][0] + (uint32_t)(((hl + wave) * 256 + r * 16 + j * 2 + w) * 136);
            T.A(acc, M, w, wp, r, hp);
            AP(0);
            if (wave == 0) {
              M.begin<192, PACE2 & 1>(acc, 6, t0 + 1);
              M.run<192>(acc, 1, NH1, 4, -1, nop);
              T.B(w, wp, M.lane(), 0);
              M.drain();
            } else {
              M.begin<128, (PACE2 >> 1) & 1>(acn, 12, t0 + 2);
              M.run<128>(acn, 1, NH2, 4, -1, nop);
              T.B(w, wp, M.lane(), 1);
              M.drain();
#pragma unroll
              for (int z = 0; z < 64; z++) asm volatile("mov.b32 %0, %1;" : "=f"(acc[z]) : "f"(acn[z]));
#pragma unroll
              for (int z = 64; z < 96; z++) acc[z] = 0.f;
            }
            AP(2);
            T.C(wp, r, M.lane(), zero, [&] { if (EFIRST == 3 || (EFIRST == 2 && wave)) T.E(M, wave); });
            AP(3);
            if (wave == 1) break;
            M.run<192>(acc, NH1, 16, 1u << 7, 16 - LEAD1, [&](int i) { if (EFIRST < 3 && i == NH1) T.E(M, false); });
            M.end<192, true>(acc, 4, 10, au[0], au[1], t0 + 1);
            PROF_T(w, t0 + 1, 2);
          }
#pragma unroll
          for (int z = 0; z < 64; z++) asm volatile("mov.b32 %0, %1;" : "=f"(acn[z]) : "f"(acc[z]));
          if (EFIRST == 1) T.E(M, true);
          else if (!EFIRST) {
            M.ensure(M.iss<128, false>(acn, false));
            T.E(M, true);
          }
        } else {
          uint32_t pk[48], pk2[64];
          pack_relu(pk, acc);
          {
            float acc2[128];
            M.begin<256, (PACE2 >> 3) & 1>(acc2, 0, t0 + 1);
            M.run<256>(acc2, 1, 16, 0x248, 16 - LEAD4, [&](int i) { ffn_stage(pk, i, M); });
            M.end<256, true>(acc2, 0, 0, au[0], au[1], t0 + 1);
            pack_relu(pk2, acc2);
            PROF_T(w, t0 + 1, 2);
          }
          M.begin<128, (PACE2 >> 4) & 1>(acn, 2, t0 + 2);
          M.run<128>(acn, 1, 13, 0x1248, -1, [&](int i) { ffn_stage(pk2, i, M); });
        }
        {
          float pre[64], rstd[2] = {0.f, 0.f};
#pragma unroll
          for (int u = 0; u < 32; u++) { pre[u] = __uint_as_float(xr[u]); if (!NOI) pre[32 + u] = 0.f; }
          if (NOI) {
#pragma unroll
            for (int u = 32; u < 64; u += 4) { const float4 v = lds128(sb + OFF_VEC); pre[u] = v.x; pre[u + 1] = v.y; pre[u + 2] = v.z; pre[u + 3] = v.w; }
          }
          const int ks = ffn ? 56 : 16, pause = ks - (ffn ? LEAD5 : LEAD2), vfrom = ffn ? 99 : 7;
          M.run<128>(acn, ffn ? 13 : NH2 + !EFIRST, ks, 0, pause, [&](int i) {
            if (i >= vfrom) {
              if (i == 7) mbar_spin(sb + BAR_OWN + w * 8, hl >> 1);
              M.validate(true, &P.tm[TM_O16], 0, r * 128 + w * 64, wp, j, [] {});
            }
          }, w ? (ffn ? (PRE5 ? PRE5 : pause) : (PRE2 ? PRE2 : pause)) : (ffn ? 20 : IPRE), [&](int) { presum(pre, M.lane(), ffn ? 1.f : 0.f); own_rstd(w, wp, M.lane(), rstd); });
          M.end<128, false>(acn, 2, 0, 0, 0, t0 + 2);
          epi_res(acn, pre, ffn ? rstd[0] * rstd[0] : 1.f, ffn ? rstd[1] * rstd[1] : 1.f, xr, M, wp);
          PROF_T(w, t0 + 2, 2);
        }
      }
    }
  }
}

typedef CUresult (*EncFn)(CUtensorMap*, CUtensorMapDataType, cuuint32_t, void*, const cuuint64_t*, const cuuint64_t*, const cuuint32_t*,
                          const cuuint32_t*, CUtensorMapInterleave, CUtensorMapSwizzle, CUtensorMapL2promotion, CUtensorMapFloatOOBfill);

void enc2(EncFn enc, CUtensorMap* tm, const void* p, uint64_t cols, uint64_t rows, uint32_t boxrows = 64, CUtensorMapL2promotion promo = CU_TENSOR_MAP_L2_PROMOTION_L2_128B) {
  cuuint64_t gd[2] = {cols, rows}, gs[1] = {cols * 2};
  cuuint32_t box[2] = {64, boxrows}, es[2] = {1, 1};
  enc(tm, CU_TENSOR_MAP_DATA_TYPE_BFLOAT16, 2, const_cast<void*>(p), gd, gs, box, es, CU_TENSOR_MAP_INTERLEAVE_NONE, CU_TENSOR_MAP_SWIZZLE_128B,
      promo, CU_TENSOR_MAP_FLOAT_OOB_FILL_NONE);
}
void enc4(EncFn enc, CUtensorMap* tm, const void* p, uint64_t K, uint64_t N, uint64_t d2, uint64_t s2, uint64_t d3, uint64_t s3, uint32_t na) {
  cuuint64_t gd[4] = {64, K, d2, d3}, gs[3] = {N * 2, s2, s3};
  cuuint32_t box[4] = {64, 64, na, 1}, es[4] = {1, 1, 1, 1};
  enc(tm, CU_TENSOR_MAP_DATA_TYPE_BFLOAT16, 4, const_cast<void*>(p), gd, gs, box, es, CU_TENSOR_MAP_INTERLEAVE_NONE, CU_TENSOR_MAP_SWIZZLE_128B,
      WPROMO, CU_TENSOR_MAP_FLOAT_OOB_FILL_NONE);
}

}

extern "C" void kernel_launch(void* const* d_in, const int* in_sizes, int n_in, void* d_out, int out_size) {
  static EncFn enc = nullptr;
  static Scratch* ps = nullptr;
  static void (*kernel)(Ptrs, Params) = mega_kernel<true>;
  if (!enc) {
    cudaDriverEntryPointQueryResult qr;
    cudaGetDriverEntryPoint("cuTensorMapEncodeTiled", (void**)&enc, cudaEnableDefault, &qr);
    int dev = 0, nsm = 0;
    cudaGetDevice(&dev);
    cudaDeviceGetAttribute(&nsm, cudaDevAttrMultiProcessorCount, dev);
    if (nsm != NMAIN + NAUX) kernel = mega_kernel<false>;
    cudaFuncSetAttribute(kernel, cudaFuncAttributeMaxDynamicSharedMemorySize, SMEM_BYTES);
    cudaGetSymbolAddress((void**)&ps, g_s);
  }
  Params P;
  Ptrs Q;
  Q.s = ps;
  void *p_h = ps->h, *p_x = ps->x;
  enc2(enc, &P.tm[TM_XIN], d_in[0], 2048, 1024, 64, XPROMO);
  enc2(enc, &P.tm[TM_X], d_out, 2048, 1024);
  enc2(enc, &P.tm[TM_XA], p_x, 2048, 1024);
  enc2(enc, &P.tm[TM_O], p_h, 3584, 2048);
  enc2(enc, &P.tm[TM_H], p_h, 3584, 2048);
  enc2(enc, &P.tm[TM_X16], d_out, 2048, 1024, 16);
  enc2(enc, &P.tm[TM_XA16], p_x, 2048, 1024, 16);
  enc2(enc, &P.tm[TM_O16], p_h, 3584, 2048, 16);
  enc4(enc, &P.tm[TM_WQKV], d_in[1], 1024, 3072, 3, 2048, 16, 128, 3);
  enc4(enc, &P.tm[TM_WO], d_in[2], 1024, 1024, 16, 128, 1, 128, 2);
  enc4(enc, &P.tm[TM_W1A], d_in[4], 1024, 3584, 56, 128, 1, 128, 4);
  enc4(enc, &P.tm[TM_W1B], d_in[4], 1024, 3584, 56, 128, 1, 128, 3);
  enc4(enc, &P.tm[TM_W2], d_in[6], 3584, 1024, 16, 128, 1, 128, 2);
  Q.out = (__nv_bfloat16*)d_out;
  Q.b1 = (const __nv_bfloat16*)d_in[5];
  Q.b2 = (const __nv_bfloat16*)d_in[7];
  kernel<<<NMAIN + NAUX, NTHREADS, SMEM_BYTES, cudaStreamPerThread>>>(Q, P);
}
```

```cpp
#include <cuda_runtime.h>
#include <cuda_bf16.h>
#include <cuda.h>
#include <stdint.h>

#define LEAD0 2
#define LEAD1 1
#define LEAD2 3
#define LEAD3 1
#define LEAD4 1
#define LEAD5 4
#define WPROMO CU_TENSOR_MAP_L2_PROMOTION_L2_128B
#define PLAN1 0x40201008070000ull
#define PLAN0 0x4030020c8180ull
#define PLANZ 0x40300a050000ull
#define VSKIP 1
#define ELA 1
#define LSO 1
#define STATI 13
#define PACE2 0x1a
#define ST2 12
#define STB 3
#define PROBE 4
#define OWNP 0x22221110
#define SIG0 14
#define STGX 2
#define STGM 3
#define NPRO 4
#define XPROMO CU_TENSOR_MAP_L2_PROMOTION_L2_256B
#define IPRE 7
#define FILLT 1
#define EARLYC 1
#define OWNDLY 0
#define EPW 0
#define CPF 5000
#define STG0 800
#define STG1 500
#define STGL (STG0 + 4 * STG1)
#define STGLX 0
#define STARTC 0
#define PRE5 0
#define PRE2 0
#define FUN 4
#define XEF 0
#define BEF 0xff8
#define AEF 0xdb6
#define SEF 0
#define SDELAYO 1000
#define SDELAY 300
#define HDELAY 450
#define Q44 1
#define FG 8
#define PRB 0
#define HPF 0
#define TAR 0
#define RSV 0
#define NWB 0
#define AGK 1
#define NOI 1
#define EFIRST 1
#define AUGN 0
#define LEARLY 1
#define NPD 0
#define SDP 900
#define LATE2 0
#define ST2W 1
#define STA 1
#define PG (Q44 ? 32 : 16)
#define NH1 6
#define NH2 3
namespace {

constexpr int NMAIN = 128, NAUX = 4, NTHREADS = 384;
constexpr uint32_t OFF_B = 0;
constexpr uint32_t OFF_A = 131072;
constexpr uint32_t OFF_VEC = 229376;
constexpr uint32_t OFF_BAR = 231424;
constexpr uint32_t OFF_RSTD = OFF_VEC + 512, OFF_MEAN = OFF_VEC + 1088, OFF_HOLD = OFF_VEC + 2032;
constexpr uint32_t SMEM_BYTES = OFF_BAR + 960;
constexpr uint32_t BAR_FULLA = OFF_BAR, BAR_FULLB = OFF_BAR + 96, BAR_OWN = OFF_BAR + 160, BAR_EPOCH = OFF_BAR + 176, BAR_AUG = OFF_BAR + 184, BAR_SPEC = OFF_BAR + 192,
                   BAR_EMPTYA = OFF_BAR + 288, BAR_STG = OFF_BAR + 384, BAR_SRV = OFF_BAR + 400, BAR_LEAD = OFF_BAR + 432, BAR_HALO = OFF_BAR + 440, BAR_STG2 = OFF_BAR + 456,
                   BAR_DUMMY3 = OFF_BAR + 472, BAR_EMPTYB = OFF_BAR + 480, BAR_STAT = OFF_BAR + 544, BAR_DUMMY = OFF_BAR + 560;
constexpr int NA = 6;
constexpr uint32_t SB = 1024;
constexpr uint32_t SPIN_LIMIT = 1u << 22;

enum { TM_XIN = 0, TM_X, TM_XA, TM_O, TM_H, TM_WQKV, TM_WO, TM_W1A, TM_W1B, TM_W2, TM_X16, TM_XA16, TM_O16, TM_COUNT };

struct Scratch;
struct Ptrs {
  Scratch* s;
  __nv_bfloat16* out;
  const __nv_bfloat16* b1;
  const __nv_bfloat16* b2;
};
struct Params { CUtensorMap tm[TM_COUNT]; };

constexpr int NSTEP = 280, NSTEP_AUX = 128;
enum : uint32_t { F_STAMP = 1u << 28, F_GATH = 1u << 15, F_NEW = 1u << 16, F_AUG = 1u << 17, F_NOA = 1u << 18, E_HAND = 1u << 19, E_ATTN = 1u << 20, E_XPUB0 = 1u << 21,
                  E_WAIT = 1u << 22, E_REL = 1u << 23, E_KEEP = 1u << 24, E_PART1 = 1u << 25, E_HALO = 1u << 26,
                  E_SIG = 1u << 27, E_RARE = F_NEW | E_KEEP | (0xfu << 20) | (3u << 26) };
constexpr int own_round(int j) { return (OWNP >> (4 * j)) & 15; }
constexpr uint32_t first_order(int j) {
  uint32_t used = 0, v = 0;
  for (int p = 0; p < 8; p++) {
    int c = own_round(j) == p ? j : -1;
    for (int u = 0; u < 8 && c < 0; u++) if (u != j && !((used >> u) & 1) && own_round(u) < p) c = u;
    if (c < 0 && own_round(j ^ 1) == p) c = j ^ 1;
    for (int u = 0; u < 8 && c < 0; u++) { const int x = (u + (j & 6)) & 7; if (x != j && own_round(x) == p) c = x; }
    used |= 1u << c; v |= (uint32_t)c << (4 * p);
  }
  return v;
}
constexpr uint32_t first_round(int p) { uint32_t v = 0; for (int j = 0; j < 8; j++) v |= ((first_order(j) >> (4 * p)) & 15) << (4 * j); return v; }
constexpr uint32_t ROUND0 = first_round(0), ROUND1 = first_round(1);
struct Sched { uint32_t v[9][NSTEP + 8]; };
constexpr Sched make_sched() {
  Sched T{};
  for (int j = 0; j < 8; j++) {
    int owner[16] = {};
    for (int i = 0; i < 16; i++) owner[i] = -100;
    int p = 0, g = 0;
    for (int t = 0; t < 12; t++) {
      const int kind = t % 6, ks = kind == 5 ? 56 : (kind == 2 ? 16 : 17);
      for (int i = 0; i < ks; i++) {
        const bool augs = ks == 17 && i == 16;
        const int na = (kind == 2 || kind == 5) ? 2 : (augs ? 1 : (kind == 4 ? 4 : 3));
        if (i == 0) p = (0x20cc63 >> (4 * kind)) & 15;
        if (augs) p = (0x0f0af >> (4 * kind)) & 15;
        if (p + na > 16) p = 0;
        int need = g - 8;
        for (int a = p; a < p + na; a++) { if (owner[a] > need) need = owner[a]; owner[a] = g; }
        if (g == 16 && need < AUGN) need = AUGN;
        uint32_t k = i, f = i == (t ? 0 : NPRO) ? F_NEW | (1u << 29) : 0;
        if (augs) { k = 0; f |= F_AUG; }
        else if (kind == 0 || kind == 3) {
          const int o = i - 2;
          if (t == 0) k = ((first_order(j) >> (4 * (i >> 1))) & 15) * 2 + (i & 1);
          else if (i < 2) { k = 2 * j + i; f |= F_NOA | (i == 0 ? E_XPUB0 : 0); }
          else { const int half = o >= 7; int u = o - 7 * half; u += u >= j; k = 2 * u + half; if (i == 6) f |= E_REL; }
          if (i == 11) f |= E_HAND;
          if (i == (t ? 11 : SIG0)) f |= E_SIG;
        } else if (kind == 1 || kind == 4) {
          if (kind == 1) f |= i == 3 ? E_HAND : (i == 8 ? E_HAND | E_KEEP : (i == 5 ? E_HALO : 0));
          if (kind == 1) f |= i == 13 ? E_REL : 0;
          else if (i == 4 || i == 7 || i == 10) f |= E_HAND;
        } else if (kind == 2) {
          f |= i == 0 ? E_WAIT : (i == 3 ? E_HAND : (i == 5 ? E_HALO : 0));
          if (i == 8) { k = 8 + j; f |= E_ATTN | E_KEEP | F_NOA; }
          if (i > 8) k = i - 1 + (i - 9 >= j);
          if (i == 11) f |= E_REL;
        } else {
          k = i < 24 ? (i / 3) * 7 + i % 3 : ((i - 24) / 4) * 7 + 3 + (i - 24) % 4;
          if (i == 4 || i == 7 || i == 10 || i == 13) f |= E_HAND;
          f |= i == 0 ? E_WAIT : (i == 24 ? E_WAIT | E_PART1 : 0);
        }
        if ((kind == 2 || kind == 5) && t < 11 && i == ks - (kind == 2 ? STA : STB)) f |= F_STAMP;
        if (((PACE2 >> kind) & 1) && i == ST2) f |= F_STAMP;
        if (i == 0 && t && ((PACE2 >> ((t - 1) % 6)) & 1)) f |= F_GATH;
        T.v[j][g] = p | ((g - need) << 5) | (k << 9) | f;
        p += na; g++;
      }
    }
    T.v[j][NSTEP] = F_NEW | F_NOA | E_XPUB0 | (2 * j << 9);
  }
  for (int w = 0; w < 2; w++) {
    int owner[14] = {};
    for (int i = 0; i < 14; i++) owner[i] = -100;
    for (int g = w, p = 0; g < NSTEP_AUX; g += 2) {
      const int na = g < 96 ? 3 : 4;
      if (p + na > 14) p = 0;
      int need = g - 8;
      for (int a = p; a < p + na; a++) { if (owner[a] > need) need = owner[a]; owner[a] = g; }
      T.v[8][g] = (p + 14 * w) | ((g - need) << 5) | ((g & 31) >> 1 << 9) | ((g & 30) && g - w != 8 ? 0 : F_NEW | (g - w == 64 ? 2u : 1u) << 29);
      p += na;
    }
  }
  return T;
}
__constant__ Sched c_sched = make_sched();
__device__ __forceinline__ int sched_k(uint32_t e) { return (e >> 3) & 0xfc0; }

struct Scratch {
  __nv_bfloat16 x[2048 * 1024];
  __nv_bfloat16 h[2048 * 3584];
  uint32_t epoch[160];
  uint8_t flags[16][2][64];
  uint32_t pace[8][64];
  uint32_t aug[2][32][1024];
  uint4 stats[4][512][8][2];
  uint4 halo[4][256][136];
};
__device__ __align__(1024) Scratch g_s;
#define PROF_T(w, t, i)
#define PRO(i)
#define LT(i)
#define CT(n)
#define ST(i)
#define AP(i)

__device__ __forceinline__ int work_id() {
  uint32_t smid;
  asm volatile("mov.u32 %0, %%smid;" : "=r"(smid));
  const int t = smid >> 1, u = t - 32, d = (u * 37) >> 8;
  int id = (t & 7) * 16 + (t >> 3) * 2;
  if (t >= 32) id = (1 + u - 7 * d) * 16 + (4 + d) * 2;
  if (t >= 60) id = t < 62 ? t * 2 + 8 : t * 2 - 116;
  return id + (smid & 1);
}

__device__ __forceinline__ uint32_t smem_u32(const void* p) { return (uint32_t)__cvta_generic_to_shared(p); }
__device__ __forceinline__ void mbar_init(uint32_t bar, int cnt) { asm volatile("mbarrier.init.shared::cta.b64 [%0], %1;" ::"r"(bar), "r"(cnt)); }
__device__ __forceinline__ void mbar_expect_tx(uint32_t bar, uint32_t bytes) { asm volatile("mbarrier.arrive.expect_tx.shared::cta.b64 _, [%0], %1;" ::"r"(bar), "r"(bytes) : "memory"); }
__device__ __forceinline__ void mbar_arrive(uint32_t bar, uint32_t cnt) { asm volatile("mbarrier.arrive.shared::cta.b64 _, [%0], %1;" ::"r"(bar), "r"(cnt) : "memory"); }
__device__ __forceinline__ void arrive_n(uint32_t bar, bool) { asm volatile("{\n.reg .pred p;\nelect.sync _|p, 0xffffffff;\n@p mbarrier.arrive.shared::cta.b64 _, [%0];\n}" ::"r"(bar) : "memory"); }
__device__ __forceinline__ void arrive_2(uint32_t b0, uint32_t b1, bool) {
  asm volatile("{\n.reg .pred p;\nelect.sync _|p, 0xffffffff;\n@p mbarrier.arrive.shared::cta.b64 _, [%0];\n@p mbarrier.arrive.shared::cta.b64 _, [%1];\n}" ::"r"(b0), "r"(b1) : "memory");
}
__device__ __forceinline__ void mbar_wait(uint32_t bar, uint32_t parity) {
  asm volatile(
      "{\n.reg .pred p;\n.reg .u32 c;\nmov.u32 c, 0;\n"
      "LAB_WAIT:\nmbarrier.try_wait.parity.shared::cta.b64 p, [%0], %1;\n@p bra.uni DONE;\n"
      "add.u32 c, c, 1;\nsetp.lt.u32 p, c, 4000000;\n@p bra.uni LAB_WAIT;\ntrap;\nDONE:\n}" ::"r"(bar), "r"(parity) : "memory");
}
__device__ __forceinline__ void mbar_spin(uint32_t bar, uint32_t parity) {
  asm volatile("{\n.reg .pred p;\nLAB_WAIT:\nmbarrier.try_wait.parity.shared::cta.b64 p, [%0], %1;\n@!p pmevent 7;\n@!p bra.uni LAB_WAIT;\n}" ::"r"(bar), "r"(parity) : "memory");
}
__device__ __forceinline__ bool elect_one() {
  uint32_t p;
  asm volatile("{\n.reg .pred P;\nelect.sync _|P, 0xffffffff;\nselp.u32 %0, 1, 0, P;\n}" : "=r"(p));
  return p != 0;
}
__device__ __forceinline__ bool mbar_test(uint32_t bar, uint32_t parity) {
  uint32_t ok;
  asm volatile("{\n.reg .pred p;\nmbarrier.test_wait.parity.shared::cta.b64 p, [%1], %2;\nselp.u32 %0, 1, 0, p;\n}" : "=r"(ok) : "r"(bar), "r"(parity) : "memory");
  return ok != 0;
}
__device__ __forceinline__ void tma_ld2(uint32_t dst, const CUtensorMap* tm, int c0, int c1, uint32_t bar) {
  asm volatile("cp.async.bulk.tensor.2d.shared::cluster.global.mbarrier::complete_tx::bytes [%0], [%1, {%3, %4}], [%2];" ::"r"(dst), "l"(tm), "r"(bar), "r"(c0), "r"(c1) : "memory");
}
__device__ __forceinline__ void tma_ld4(uint32_t dst, const CUtensorMap* tm, int c1, int c2, int c3, uint32_t bar, uint64_t pol = 0x1000000000000000ull) {
  asm volatile("cp.async.bulk.tensor.4d.shared::cluster.global.mbarrier::complete_tx::bytes.L2::cache_hint [%0], [%1, {%3, %4, %5, %6}], [%2], %7;" ::"r"(dst), "l"(tm), "r"(bar), "r"(0), "r"(c1), "r"(c2), "r"(c3), "l"(pol) : "memory");
}
__device__ __forceinline__ void tma_st2(const CUtensorMap* tm, int c0, int c1, uint32_t src) {
  asm volatile("cp.async.bulk.tensor.2d.global.shared::cta.bulk_group [%0, {%2, %3}], [%1];" ::"l"(tm), "r"(src), "r"(c0), "r"(c1) : "memory");
}
__device__ __forceinline__ void bulk_ld(uint32_t dst, const void* src, uint32_t bytes, uint32_t bar) {
  asm volatile("cp.async.bulk.shared::cluster.global.mbarrier::complete_tx::bytes [%0], [%1], %2, [%3];" ::"r"(dst), "l"(src), "r"(bytes), "r"(bar) : "memory");
}
__device__ __forceinline__ void e_arrive(uint32_t bar, uint32_t cnt) {
  if (cnt == 1) asm volatile("{\n.reg .pred p;\nelect.sync _|p, 0xffffffff;\n@p mbarrier.arrive.shared::cta.b64 _, [%0];\n}" ::"r"(bar) : "memory");
  else asm volatile("{\n.reg .pred p;\nelect.sync _|p, 0xffffffff;\n@p mbarrier.arrive.shared::cta.b64 _, [%0], %1;\n}" ::"r"(bar), "r"(cnt) : "memory");
}
template <int BYTES = 8192> __device__ __forceinline__ void e_load(uint32_t dst, const CUtensorMap* tm, int c0, int c1, uint32_t bar, uint64_t pol = 0x1000000000000000ull) {
  asm volatile("{\n.reg .pred p;\nelect.sync _|p, 0xffffffff;\n@p mbarrier.arrive.expect_tx.shared::cta.b64 _, [%2], %5;\n"
               "@p cp.async.bulk.tensor.2d.shared::cluster.global.mbarrier::complete_tx::bytes.L2::cache_hint [%0], [%1, {%3, %4}], [%2], %6;\n}"
               ::"r"(dst), "l"(tm), "r"(bar), "r"(c0), "r"(c1), "n"(BYTES), "l"(pol) : "memory");
}
__device__ __forceinline__ void e_store(const CUtensorMap* tm, int c0, int c1, uint32_t src) {
  asm volatile("{\n.reg .pred p;\nfence.proxy.async.shared::cta;\nelect.sync _|p, 0xffffffff;\n"
               "@p cp.async.bulk.tensor.2d.global.shared::cta.bulk_group [%0, {%2, %3}], [%1];\ncp.async.bulk.commit_group;\n}"
               ::"l"(tm), "r"(src), "r"(c0), "r"(c1) : "memory");
}
__device__ __forceinline__ void bulk_commit() { asm volatile("cp.async.bulk.commit_group;" ::: "memory"); }
template <int N> __device__ __forceinline__ void bulk_wait_read() { asm volatile("cp.async.bulk.wait_group.read %0;" ::"n"(N) : "memory"); }
__device__ __forceinline__ void bulk_wait_all() { asm volatile("cp.async.bulk.wait_group 0;" ::: "memory"); }
__device__ __forceinline__ void fence_async_smem() { asm volatile("fence.proxy.async.shared::cta;" ::: "memory"); }
__device__ __forceinline__ void wg_fence() { asm volatile("wgmma.fence.sync.aligned;" ::: "memory"); }
__device__ __forceinline__ void wg_commit() { asm volatile("wgmma.commit_group.sync.aligned;" ::: "memory"); }
template <int N> __device__ __forceinline__ void wg_wait() { asm volatile("wgmma.wait_group.sync.aligned %0;" ::"n"(N) : "memory"); }
__device__ __forceinline__ void wg_bar(int w) { asm volatile("bar.sync %0, 128;" ::"r"(w + 1) : "memory"); }
__device__ __forceinline__ uint32_t ld_acquire(const uint32_t* p) { uint32_t v; asm volatile("ld.acquire.gpu.global.u32 %0, [%1];" : "=r"(v) : "l"(p) : "memory"); return v; }
__device__ __forceinline__ uint4 ld_relaxed4(const uint32_t* p) {
  uint4 v; asm volatile("ld.relaxed.gpu.global.v4.u32 {%0,%1,%2,%3}, [%4];" : "=r"(v.x), "=r"(v.y), "=r"(v.z), "=r"(v.w) : "l"(p) : "memory"); return v;
}
__device__ __forceinline__ void st_release8(uint8_t* p, uint32_t v) { asm volatile("st.release.gpu.global.u8 [%0], %1;" ::"l"(p), "r"(v) : "memory"); }
__device__ __forceinline__ uint32_t ld_relaxed(const uint32_t* p) { uint32_t v; asm volatile("ld.relaxed.gpu.global.u32 %0, [%1];" : "=r"(v) : "l"(p) : "memory"); return v; }
__device__ __forceinline__ void st_release(uint32_t* p, uint32_t v) { asm volatile("st.release.gpu.global.u32 [%0], %1;" ::"l"(p), "r"(v) : "memory"); }
__device__ __forceinline__ void st_pkt(uint4* p, uint32_t a, uint32_t b, uint32_t c, uint32_t d) {
  asm volatile("{\n.reg .b64 lo, hi;\n.reg .b128 v;\nmov.b64 lo, {%1, %2};\nmov.b64 hi, {%3, %4};\nmov.b128 v, {lo, hi};\nst.relaxed.gpu.global.b128 [%0], v;\n}" ::"l"(p), "r"(a), "r"(b), "r"(c), "r"(d) : "memory");
}
__device__ __forceinline__ uint4 ld_pkt(const uint4* p) {
  uint4 r;
  asm volatile("{\n.reg .b64 lo, hi;\n.reg .b128 v;\nld.relaxed.gpu.global.b128 v, [%4];\nmov.b128 {lo, hi}, v;\nmov.b64 {%0, %1}, lo;\nmov.b64 {%2, %3}, hi;\n}" : "=r"(r.x), "=r"(r.y), "=r"(r.z), "=r"(r.w) : "l"(p) : "memory");
  return r;
}
__device__ __forceinline__ uint32_t pack_bf16(float lo, float hi) { uint32_t d; asm("cvt.rn.bf16x2.f32 %0, %1, %2;" : "=r"(d) : "f"(hi), "f"(lo)); return d; }
__device__ __forceinline__ float ex2(float x) { float y; asm("ex2.approx.ftz.f32 %0, %1;" : "=f"(y) : "f"(x)); return y; }
__device__ __forceinline__ float rsq(float x) { float y; asm("rsqrt.approx.ftz.f32 %0, %1;" : "=f"(y) : "f"(x)); return y; }
__device__ __forceinline__ float rcp(float x) { float y; asm("rcp.approx.ftz.f32 %0, %1;" : "=f"(y) : "f"(x)); return y; }
__device__ __forceinline__ float bf_lo(uint32_t v) { return __uint_as_float(v << 16); }
__device__ __forceinline__ float bf_hi(uint32_t v) { return __uint_as_float(v & 0xffff0000u); }
__device__ __forceinline__ void stsm4(uint32_t addr, uint32_t a, uint32_t b, uint32_t c, uint32_t d) {
  asm volatile("stmatrix.sync.aligned.m8n8.x4.shared.b16 [%0], {%1, %2, %3, %4};" ::"r"(addr), "r"(a), "r"(b), "r"(c), "r"(d) : "memory");
}
__device__ __forceinline__ uint32_t movm(uint32_t a) { uint32_t d; asm volatile("movmatrix.sync.aligned.m8n8.trans.b16 %0, %1;" : "=r"(d) : "r"(a)); return d; }
__device__ __forceinline__ void mma16(float (&c)[4], uint32_t a0, uint32_t a1, uint32_t a2, uint32_t a3, uint32_t b0, uint32_t b1) {
  asm volatile("mma.sync.aligned.m16n8k16.row.col.f32.bf16.bf16.f32 {%0,%1,%2,%3}, {%4,%5,%6,%7}, {%8,%9}, {%0,%1,%2,%3};"
               : "+f"(c[0]), "+f"(c[1]), "+f"(c[2]), "+f"(c[3]) : "r"(a0), "r"(a1), "r"(a2), "r"(a3), "r"(b0), "r"(b1));
}
__device__ __forceinline__ void mma8(float (&c)[4], uint32_t a0, uint32_t a1, uint32_t b0) {
  asm volatile("mma.sync.aligned.m16n8k8.row.col.f32.bf16.bf16.f32 {%0,%1,%2,%3}, {%4,%5}, {%6}, {%0,%1,%2,%3};"
               : "+f"(c[0]), "+f"(c[1]), "+f"(c[2]), "+f"(c[3]) : "r"(a0), "r"(a1), "r"(b0));
}
__device__ __forceinline__ void sts128(uint32_t a, uint32_t x, uint32_t y, uint32_t z, uint32_t w) {
  asm volatile("st.shared.v4.b32 [%0], {%1,%2,%3,%4};" ::"r"(a), "r"(x), "r"(y), "r"(z), "r"(w) : "memory");
}
__device__ __forceinline__ float2 lds64(uint32_t a) { float2 v; asm volatile("ld.shared.v2.f32 {%0,%1}, [%2];" : "=f"(v.x), "=f"(v.y) : "r"(a)); return v; }
__device__ __forceinline__ float4 lds128(uint32_t a) { float4 v; asm volatile("ld.shared.v4.f32 {%0,%1,%2,%3}, [%4];" : "=f"(v.x), "=f"(v.y), "=f"(v.z), "=f"(v.w) : "r"(a)); return v; }
__device__ __forceinline__ uint32_t lds32(uint32_t a) { uint32_t v; asm volatile("ld.shared.b32 %0, [%1];" : "=r"(v) : "r"(a)); return v; }
template <int S> __device__ __forceinline__ void wgmma_first128(float (&d)[S], uint32_t da, uint32_t db) {
  asm volatile("{\n.reg .b64 a, b;\n.reg .b32 t, u, h;\n.reg .pred p, q;\nmov.b32 h, 0x40000040;\nwgmma.fence.sync.aligned;\n"
    "add.u32 t, %64, 0;\nadd.u32 u, %65, 0;\nmov.b64 a, {t, h};\nmov.b64 b, {u, h};\n"
    "wgmma.mma_async.sync.aligned.m64n128k16.f32.bf16.bf16 "
    "{%0, %1, %2, %3, %4, %5, %6, %7, %8, %9, %10, %11, %12, %13, %14, %15, %16, %17, %18, %19, %20, %21, %22, %23, %24, %25, %26, %27, %28, %29, %30, %31, %32, %33, %34, %35, %36, %37, %38, %39, %40, %41, %42, %43, %44, %45, %46, %47, %48, %49, %50, %51, %52, %53, %54, %55, %56, %57, %58, %59, %60, %61, %62, %63}, "
    "a, b, 0, 1, 1, 0, 1;\n"
    "add.u32 t, %64, 2;\nadd.u32 u, %65, 128;\nmov.b64 a, {t, h};\nmov.b64 b, {u, h};\n"
    "wgmma.mma_async.sync.aligned.m64n128k16.f32.bf16.bf16 "
    "{%0, %1, %2, %3, %4, %5, %6, %7, %8, %9, %10, %11, %12, %13, %14, %15, %16, %17, %18, %19, %20, %21, %22, %23, %24, %25, %26, %27, %28, %29, %30, %31, %32, %33, %34, %35, %36, %37, %38, %39, %40, %41, %42, %43, %44, %45, %46, %47, %48, %49, %50, %51, %52, %53, %54, %55, %56, %57, %58, %59, %60, %61, %62, %63}, "
    "a, b, 1, 1, 1, 0, 1;\n"
    "add.u32 t, %64, 4;\nadd.u32 u, %65, 256;\nmov.b64 a, {t, h};\nmov.b64 b, {u, h};\n"
    "wgmma.mma_async.sync.aligned.m64n128k16.f32.bf16.bf16 "
    "{%0, %1, %2, %3, %4, %5, %6, %7, %8, %9, %10, %11, %12, %13, %14, %15, %16, %17, %18, %19, %20, %21, %22, %23, %24, %25, %26, %27, %28, %29, %30, %31, %32, %33, %34, %35, %36, %37, %38, %39, %40, %41, %42, %43, %44, %45, %46, %47, %48, %49, %50, %51, %52, %53, %54, %55, %56, %57, %58, %59, %60, %61, %62, %63}, "
    "a, b, 1, 1, 1, 0, 1;\n"
    "add.u32 t, %64, 6;\nadd.u32 u, %65, 384;\nmov.b64 a, {t, h};\nmov.b64 b, {u, h};\n"
    "wgmma.mma_async.sync.aligned.m64n128k16.f32.bf16.bf16 "
    "{%0, %1, %2, %3, %4, %5, %6, %7, %8, %9, %10, %11, %12, %13, %14, %15, %16, %17, %18, %19, %20, %21, %22, %23, %24, %25, %26, %27, %28, %29, %30, %31, %32, %33, %34, %35, %36, %37, %38, %39, %40, %41, %42, %43, %44, %45, %46, %47, %48, %49, %50, %51, %52, %53, %54, %55, %56, %57, %58, %59, %60, %61, %62, %63}, "
    "a, b, 1, 1, 1, 0, 1;\n"
    "wgmma.commit_group.sync.aligned;\n}"
    : "=f"(d[0]), "=f"(d[1]), "=f"(d[2]), "=f"(d[3]), "=f"(d[4]), "=f"(d[5]), "=f"(d[6]), "=f"(d[7]), "=f"(d[8]), "=f"(d[9]), "=f"(d[10]), "=f"(d[11]), "=f"(d[12]), "=f"(d[13]), "=f"(d[14]), "=f"(d[15]), "=f"(d[16]), "=f"(d[17]), "=f"(d[18]), "=f"(d[19]), "=f"(d[20]), "=f"(d[21]), "=f"(d[22]), "=f"(d[23]), "=f"(d[24]), "=f"(d[25]), "=f"(d[26]), "=f"(d[27]), "=f"(d[28]), "=f"(d[29]), "=f"(d[30]), "=f"(d[31]), "=f"(d[32]), "=f"(d[33]), "=f"(d[34]), "=f"(d[35]), "=f"(d[36]), "=f"(d[37]), "=f"(d[38]), "=f"(d[39]), "=f"(d[40]), "=f"(d[41]), "=f"(d[42]), "=f"(d[43]), "=f"(d[44]), "=f"(d[45]), "=f"(d[46]), "=f"(d[47]), "=f"(d[48]), "=f"(d[49]), "=f"(d[50]), "=f"(d[51]), "=f"(d[52]), "=f"(d[53]), "=f"(d[54]), "=f"(d[55]), "=f"(d[56]), "=f"(d[57]), "=f"(d[58]), "=f"(d[59]), "=f"(d[60]), "=f"(d[61]), "=f"(d[62]), "=f"(d[63])
    : "r"(da), "r"(db) : "memory");
}
template <int S> __device__ __forceinline__ uint2 wgmma_probe128(float (&d)[S], uint32_t da, uint32_t db, uint32_t b0, uint32_t p0, uint32_t b1, uint32_t p1) {
  uint2 ok;
  asm volatile("{\n.reg .b64 a, b;\n.reg .b32 t, u, h;\n.reg .pred p, q;\nmov.b32 h, 0x40000040;\nwgmma.fence.sync.aligned;\n"
    "add.u32 t, %66, 0;\nadd.u32 u, %67, 0;\nmov.b64 a, {t, h};\nmov.b64 b, {u, h};\n"
    "wgmma.mma_async.sync.aligned.m64n128k16.f32.bf16.bf16 "
    "{%2, %3, %4, %5, %6, %7, %8, %9, %10, %11, %12, %13, %14, %15, %16, %17, %18, %19, %20, %21, %22, %23, %24, %25, %26, %27, %28, %29, %30, %31, %32, %33, %34, %35, %36, %37, %38, %39, %40, %41, %42, %43, %44, %45, %46, %47, %48, %49, %50, %51, %52, %53, %54, %55, %56, %57, %58, %59, %60, %61, %62, %63, %64, %65}, "
    "a, b, 1, 1, 1, 0, 1;\n"
    "add.u32 t, %66, 2;\nadd.u32 u, %67, 128;\nmov.b64 a, {t, h};\nmov.b64 b, {u, h};\n"
    "wgmma.mma_async.sync.aligned.m64n128k16.f32.bf16.bf16 "
    "{%2, %3, %4, %5, %6, %7, %8, %9, %10, %11, %12, %13, %14, %15, %16, %17, %18, %19, %20, %21, %22, %23, %24, %25, %26, %27, %28, %29, %30, %31, %32, %33, %34, %35, %36, %37, %38, %39, %40, %41, %42, %43, %44, %45, %46, %47, %48, %49, %50, %51, %52, %53, %54, %55, %56, %57, %58, %59, %60, %61, %62, %63, %64, %65}, "
    "a, b, 1, 1, 1, 0, 1;\n"
    "mbarrier.test_wait.parity.shared::cta.b64 p, [%68], %69;\nmbarrier.test_wait.parity.shared::cta.b64 q, [%70], %71;\n"
    "add.u32 t, %66, 4;\nadd.u32 u, %67, 256;\nmov.b64 a, {t, h};\nmov.b64 b, {u, h};\n"
    "wgmma.mma_async.sync.aligned.m64n128k16.f32.bf16.bf16 "
    "{%2, %3, %4, %5, %6, %7, %8, %9, %10, %11, %12, %13, %14, %15, %16, %17, %18, %19, %20, %21, %22, %23, %24, %25, %26, %27, %28, %29, %30, %31, %32, %33, %34, %35, %36, %37, %38, %39, %40, %41, %42, %43, %44, %45, %46, %47, %48, %49, %50, %51, %52, %53, %54, %55, %56, %57, %58, %59, %60, %61, %62, %63, %64, %65}, "
    "a, b, 1, 1, 1, 0, 1;\n"
    "add.u32 t, %66, 6;\nadd.u32 u, %67, 384;\nmov.b64 a, {t, h};\nmov.b64 b, {u, h};\n"
    "wgmma.mma_async.sync.aligned.m64n128k16.f32.bf16.bf16 "
    "{%2, %3, %4, %5, %6, %7, %8, %9, %10, %11, %12, %13, %14, %15, %16, %17, %18, %19, %20, %21, %22, %23, %24, %25, %26, %27, %28, %29, %30, %31, %32, %33, %34, %35, %36, %37, %38, %39, %40, %41, %42, %43, %44, %45, %46, %47, %48, %49, %50, %51, %52, %53, %54, %55, %56, %57, %58, %59, %60, %61, %62, %63, %64, %65}, "
    "a, b, 1, 1, 1, 0, 1;\n"
    "wgmma.commit_group.sync.aligned;\nselp.u32 %0, 1, 0, p;\nselp.u32 %1, 1, 0, q;\n}"
    : "=r"(ok.x), "=r"(ok.y), "+f"(d[0]), "+f"(d[1]), "+f"(d[2]), "+f"(d[3]), "+f"(d[4]), "+f"(d[5]), "+f"(d[6]), "+f"(d[7]), "+f"(d[8]), "+f"(d[9]), "+f"(d[10]), "+f"(d[11]), "+f"(d[12]), "+f"(d[13]), "+f"(d[14]), "+f"(d[15]), "+f"(d[16]), "+f"(d[17]), "+f"(d[18]), "+f"(d[19]), "+f"(d[20]), "+f"(d[21]), "+f"(d[22]), "+f"(d[23]), "+f"(d[24]), "+f"(d[25]), "+f"(d[26]), "+f"(d[27]), "+f"(d[28]), "+f"(d[29]), "+f"(d[30]), "+f"(d[31]), "+f"(d[32]), "+f"(d[33]), "+f"(d[34]), "+f"(d[35]), "+f"(d[36]), "+f"(d[37]), "+f"(d[38]), "+f"(d[39]), "+f"(d[40]), "+f"(d[41]), "+f"(d[42]), "+f"(d[43]), "+f"(d[44]), "+f"(d[45]), "+f"(d[46]), "+f"(d[47]), "+f"(d[48]), "+f"(d[49]), "+f"(d[50]), "+f"(d[51]), "+f"(d[52]), "+f"(d[53]), "+f"(d[54]), "+f"(d[55]), "+f"(d[56]), "+f"(d[57]), "+f"(d[58]), "+f"(d[59]), "+f"(d[60]), "+f"(d[61]), "+f"(d[62]), "+f"(d[63])
    : "r"(da), "r"(db), "r"(b0), "r"(p0), "r"(b1), "r"(p1) : "memory");
  return ok;
}
template <int S> __device__ __forceinline__ void wgmma_first192(float (&d)[S], uint32_t da, uint32_t db) {
  asm volatile("{\n.reg .b64 a, b;\n.reg .b32 t, u, h;\n.reg .pred p, q;\nmov.b32 h, 0x40000040;\nwgmma.fence.sync.aligned;\n"
    "add.u32 t, %96, 0;\nadd.u32 u, %97, 0;\nmov.b64 a, {t, h};\nmov.b64 b, {u, h};\n"
    "wgmma.mma_async.sync.aligned.m64n192k16.f32.bf16.bf16 "
    "{%0, %1, %2, %3, %4, %5, %6, %7, %8, %9, %10, %11, %12, %13, %14, %15, %16, %17, %18, %19, %20, %21, %22, %23, %24, %25, %26, %27, %28, %29, %30, %31, %32, %33, %34, %35, %36, %37, %38, %39, %40, %41, %42, %43, %44, %45, %46, %47, %48, %49, %50, %51, %52, %53, %54, %55, %56, %57, %58, %59, %60, %61, %62, %63, %64, %65, %66, %67, %68, %69, %70, %71, %72, %73, %74, %75, %76, %77, %78, %79, %80, %81, %82, %83, %84, %85, %86, %87, %88, %89, %90, %91, %92, %93, %94, %95}, "
    "a, b, 0, 1, 1, 0, 1;\n"
    "add.u32 t, %96, 2;\nadd.u32 u, %97, 128;\nmov.b64 a, {t, h};\nmov.b64 b, {u, h};\n"
    "wgmma.mma_async.sync.aligned.m64n192k16.f32.bf16.bf16 "
    "{%0, %1, %2, %3, %4, %5, %6, %7, %8, %9, %10, %11, %12, %13, %14, %15, %16, %17, %18, %19, %20, %21, %22, %23, %24, %25, %26, %27, %28, %29, %30, %31, %32, %33, %34, %35, %36, %37, %38, %39, %40, %41, %42, %43, %44, %45, %46, %47, %48, %49, %50, %51, %52, %53, %54, %55, %56, %57, %58, %59, %60, %61, %62, %63, %64, %65, %66, %67, %68, %69, %70, %71, %72, %73, %74, %75, %76, %77, %78, %79, %80, %81, %82, %83, %84, %85, %86, %87, %88, %89, %90, %91, %92, %93, %94, %95}, "
    "a, b, 1, 1, 1, 0, 1;\n"
    "add.u32 t, %96, 4;\nadd.u32 u, %97, 256;\nmov.b64 a, {t, h};\nmov.b64 b, {u, h};\n"
    "wgmma.mma_async.sync.aligned.m64n192k16.f32.bf16.bf16 "
    "{%0, %1, %2, %3, %4, %5, %6, %7, %8, %9, %10, %11, %12, %13, %14, %15, %16, %17, %18, %19, %20, %21, %22, %23, %24, %25, %26, %27, %28, %29, %30, %31, %32, %33, %34, %35, %36, %37, %38, %39, %40, %41, %42, %43, %44, %45, %46, %47, %48, %49, %50, %51, %52, %53, %54, %55, %56, %57, %58, %59, %60, %61, %62, %63, %64, %65, %66, %67, %68, %69, %70, %71, %72, %73, %74, %75, %76, %77, %78, %79, %80, %81, %82, %83, %84, %85, %86, %87, %88, %89, %90, %91, %92, %93, %94, %95}, "
    "a, b, 1, 1, 1, 0, 1;\n"
    "add.u32 t, %96, 6;\nadd.u32 u, %97, 384;\nmov.b64 a, {t, h};\nmov.b64 b, {u, h};\n"
    "wgmma.mma_async.sync.aligned.m64n192k16.f32.bf16.bf16 "
    "{%0, %1, %2, %3, %4, %5, %6, %7, %8, %9, %10, %11, %12, %13, %14, %15, %16, %17, %18, %19, %20, %21, %22, %23, %24, %25, %26, %27, %28, %29, %30, %31, %32, %33, %34, %35, %36, %37, %38, %39, %40, %41, %42, %43, %44, %45, %46, %47, %48, %49, %50, %51, %52, %53, %54, %55, %56, %57, %58, %59, %60, %61, %62, %63, %64, %65, %66, %67, %68, %69, %70, %71, %72, %73, %74, %75, %76, %77, %78, %79, %80, %81, %82, %83, %84, %85, %86, %87, %88, %89, %90, %91, %92, %93, %94, %95}, "
    "a, b, 1, 1, 1, 0, 1;\n"
    "wgmma.commit_group.sync.aligned;\n}"
    : "=f"(d[0]), "=f"(d[1]), "=f"(d[2]), "=f"(d[3]), "=f"(d[4]), "=f"(d[5]), "=f"(d[6]), "=f"(d[7]), "=f"(d[8]), "=f"(d[9]), "=f"(d[10]), "=f"(d[11]), "=f"(d[12]), "=f"(d[13]), "=f"(d[14]), "=f"(d[15]), "=f"(d[16]), "=f"(d[17]), "=f"(d[18]), "=f"(d[19]), "=f"(d[20]), "=f"(d[21]), "=f"(d[22]), "=f"(d[23]), "=f"(d[24]), "=f"(d[25]), "=f"(d[26]), "=f"(d[27]), "=f"(d[28]), "=f"(d[29]), "=f"(d[30]), "=f"(d[31]), "=f"(d[32]), "=f"(d[33]), "=f"(d[34]), "=f"(d[35]), "=f"(d[36]), "=f"(d[37]), "=f"(d[38]), "=f"(d[39]), "=f"(d[40]), "=f"(d[41]), "=f"(d[42]), "=f"(d[43]), "=f"(d[44]), "=f"(d[45]), "=f"(d[46]), "=f"(d[47]), "=f"(d[48]), "=f"(d[49]), "=f"(d[50]), "=f"(d[51]), "=f"(d[52]), "=f"(d[53]), "=f"(d[54]), "=f"(d[55]), "=f"(d[56]), "=f"(d[57]), "=f"(d[58]), "=f"(d[59]), "=f"(d[60]), "=f"(d[61]), "=f"(d[62]), "=f"(d[63]), "=f"(d[64]), "=f"(d[65]), "=f"(d[66]), "=f"(d[67]), "=f"(d[68]), "=f"(d[69]), "=f"(d[70]), "=f"(d[71]), "=f"(d[72]), "=f"(d[73]), "=f"(d[74]), "=f"(d[75]), "=f"(d[76]), "=f"(d[77]), "=f"(d[78]), "=f"(d[79]), "=f"(d[80]), "=f"(d[81]), "=f"(d[82]), "=f"(d[83]), "=f"(d[84]), "=f"(d[85]), "=f"(d[86]), "=f"(d[87]), "=f"(d[88]), "=f"(d[89]), "=f"(d[90]), "=f"(d[91]), "=f"(d[92]), "=f"(d[93]), "=f"(d[94]), "=f"(d[95])
    : "r"(da), "r"(db) : "memory");
}
template <int S> __device__ __forceinline__ uint2 wgmma_probe192(float (&d)[S], uint32_t da, uint32_t db, uint32_t b0, uint32_t p0, uint32_t b1, uint32_t p1) {
  uint2 ok;
  asm volatile("{\n.reg .b64 a, b;\n.reg .b32 t, u, h;\n.reg .pred p, q;\nmov.b32 h, 0x40000040;\nwgmma.fence.sync.aligned;\n"
    "add.u32 t, %98, 0;\nadd.u32 u, %99, 0;\nmov.b64 a, {t, h};\nmov.b64 b, {u, h};\n"
    "wgmma.mma_async.sync.aligned.m64n192k16.f32.bf16.bf16 "
    "{%2, %3, %4, %5, %6, %7, %8, %9, %10, %11, %12, %13, %14, %15, %16, %17, %18, %19, %20, %21, %22, %23, %24, %25, %26, %27, %28, %29, %30, %31, %32, %33, %34, %35, %36, %37, %38, %39, %40, %41, %42, %43, %44, %45, %46, %47, %48, %49, %50, %51, %52, %53, %54, %55, %56, %57, %58, %59, %60, %61, %62, %63, %64, %65, %66, %67, %68, %69, %70, %71, %72, %73, %74, %75, %76, %77, %78, %79, %80, %81, %82, %83, %84, %85, %86, %87, %88, %89, %90, %91, %92, %93, %94, %95, %96, %97}, "
    "a, b, 1, 1, 1, 0, 1;\n"
    "add.u32 t, %98, 2;\nadd.u32 u, %99, 128;\nmov.b64 a, {t, h};\nmov.b64 b, {u, h};\n"
    "wgmma.mma_async.sync.aligned.m64n192k16.f32.bf16.bf16 "
    "{%2, %3, %4, %5, %6, %7, %8, %9, %10, %11, %12, %13, %14, %15, %16, %17, %18, %19, %20, %21, %22, %23, %24, %25, %26, %27, %28, %29, %30, %31, %32, %33, %34, %35, %36, %37, %38, %39, %40, %41, %42, %43, %44, %45, %46, %47, %48, %49, %50, %51, %52, %53, %54, %55, %56, %57, %58, %59, %60, %61, %62, %63, %64, %65, %66, %67, %68, %69, %70, %71, %72, %73, %74, %75, %76, %77, %78, %79, %80, %81, %82, %83, %84, %85, %86, %87, %88, %89, %90, %91, %92, %93, %94, %95, %96, %97}, "
    "a, b, 1, 1, 1, 0, 1;\n"
    "mbarrier.test_wait.parity.shared::cta.b64 p, [%100], %101;\nmbarrier.test_wait.parity.shared::cta.b64 q, [%102], %103;\n"
    "add.u32 t, %98, 4;\nadd.u32 u, %99, 256;\nmov.b64 a, {t, h};\nmov.b64 b, {u, h};\n"
    "wgmma.mma_async.sync.aligned.m64n192k16.f32.bf16.bf16 "
    "{%2, %3, %4, %5, %6, %7, %8, %9, %10, %11, %12, %13, %14, %15, %16, %17, %18, %19, %20, %21, %22, %23, %24, %25, %26, %27, %28, %29, %30, %31, %32, %33, %34, %35, %36, %37, %38, %39, %40, %41, %42, %43, %44, %45, %46, %47, %48, %49, %50, %51, %52, %53, %54, %55, %56, %57, %58, %59, %60, %61, %62, %63, %64, %65, %66, %67, %68, %69, %70, %71, %72, %73, %74, %75, %76, %77, %78, %79, %80, %81, %82, %83, %84, %85, %86, %87, %88, %89, %90, %91, %92, %93, %94, %95, %96, %97}, "
    "a, b, 1, 1, 1, 0, 1;\n"
    "add.u32 t, %98, 6;\nadd.u32 u, %99, 384;\nmov.b64 a, {t, h};\nmov.b64 b, {u, h};\n"
    "wgmma.mma_async.sync.aligned.m64n192k16.f32.bf16.bf16 "
    "{%2, %3, %4, %5, %6, %7, %8, %9, %10, %11, %12, %13, %14, %15, %16, %17, %18, %19, %20, %21, %22, %23, %24, %25, %26, %27, %28, %29, %30, %31, %32, %33, %34, %35, %36, %37, %38, %39, %40, %41, %42, %43, %44, %45, %46, %47, %48, %49, %50, %51, %52, %53, %54, %55, %56, %57, %58, %59, %60, %61, %62, %63, %64, %65, %66, %67, %68, %69, %70, %71, %72, %73, %74, %75, %76, %77, %78, %79, %80, %81, %82, %83, %84, %85, %86, %87, %88, %89, %90, %91, %92, %93, %94, %95, %96, %97}, "
    "a, b, 1, 1, 1, 0, 1;\n"
    "wgmma.commit_group.sync.aligned;\nselp.u32 %0, 1, 0, p;\nselp.u32 %1, 1, 0, q;\n}"
    : "=r"(ok.x), "=r"(ok.y), "+f"(d[0]), "+f"(d[1]), "+f"(d[2]), "+f"(d[3]), "+f"(d[4]), "+f"(d[5]), "+f"(d[6]), "+f"(d[7]), "+f"(d[8]), "+f"(d[9]), "+f"(d[10]), "+f"(d[11]), "+f"(d[12]), "+f"(d[13]), "+f"(d[14]), "+f"(d[15]), "+f"(d[16]), "+f"(d[17]), "+f"(d[18]), "+f"(d[19]), "+f"(d[20]), "+f"(d[21]), "+f"(d[22]), "+f"(d[23]), "+f"(d[24]), "+f"(d[25]), "+f"(d[26]), "+f"(d[27]), "+f"(d[28]), "+f"(d[29]), "+f"(d[30]), "+f"(d[31]), "+f"(d[32]), "+f"(d[33]), "+f"(d[34]), "+f"(d[35]), "+f"(d[36]), "+f"(d[37]), "+f"(d[38]), "+f"(d[39]), "+f"(d[40]), "+f"(d[41]), "+f"(d[42]), "+f"(d[43]), "+f"(d[44]), "+f"(d[45]), "+f"(d[46]), "+f"(d[47]), "+f"(d[48]), "+f"(d[49]), "+f"(d[50]), "+f"(d[51]), "+f"(d[52]), "+f"(d[53]), "+f"(d[54]), "+f"(d[55]), "+f"(d[56]), "+f"(d[57]), "+f"(d[58]), "+f"(d[59]), "+f"(d[60]), "+f"(d[61]), "+f"(d[62]), "+f"(d[63]), "+f"(d[64]), "+f"(d[65]), "+f"(d[66]), "+f"(d[67]), "+f"(d[68]), "+f"(d[69]), "+f"(d[70]), "+f"(d[71]), "+f"(d[72]), "+f"(d[73]), "+f"(d[74]), "+f"(d[75]), "+f"(d[76]), "+f"(d[77]), "+f"(d[78]), "+f"(d[79]), "+f"(d[80]), "+f"(d[81]), "+f"(d[82]), "+f"(d[83]), "+f"(d[84]), "+f"(d[85]), "+f"(d[86]), "+f"(d[87]), "+f"(d[88]), "+f"(d[89]), "+f"(d[90]), "+f"(d[91]), "+f"(d[92]), "+f"(d[93]), "+f"(d[94]), "+f"(d[95])
    : "r"(da), "r"(db), "r"(b0), "r"(p0), "r"(b1), "r"(p1) : "memory");
  return ok;
}
template <int S> __device__ __forceinline__ void wgmma_first256(float (&d)[S], uint32_t da, uint32_t db) {
  asm volatile("{\n.reg .b64 a, b;\n.reg .b32 t, u, h;\n.reg .pred p, q;\nmov.b32 h, 0x40000040;\nwgmma.fence.sync.aligned;\n"
    "add.u32 t, %128, 0;\nadd.u32 u, %129, 0;\nmov.b64 a, {t, h};\nmov.b64 b, {u, h};\n"
    "wgmma.mma_async.sync.aligned.m64n256k16.f32.bf16.bf16 "
    "{%0, %1, %2, %3, %4, %5, %6, %7, %8, %9, %10, %11, %12, %13, %14, %15, %16, %17, %18, %19, %20, %21, %22, %23, %24, %25, %26, %27, %28, %29, %30, %31, %32, %33, %34, %35, %36, %37, %38, %39, %40, %41, %42, %43, %44, %45, %46, %47, %48, %49, %50, %51, %52, %53, %54, %55, %56, %57, %58, %59, %60, %61, %62, %63, %64, %65, %66, %67, %68, %69, %70, %71, %72, %73, %74, %75, %76, %77, %78, %79, %80, %81, %82, %83, %84, %85, %86, %87, %88, %89, %90, %91, %92, %93, %94, %95, %96, %97, %98, %99, %100, %101, %102, %103, %104, %105, %106, %107, %108, %109, %110, %111, %112, %113, %114, %115, %116, %117, %118, %119, %120, %121, %122, %123, %124, %125, %126, %127}, "
    "a, b, 0, 1, 1, 0, 1;\n"
    "add.u32 t, %128, 2;\nadd.u32 u, %129, 128;\nmov.b64 a, {t, h};\nmov.b64 b, {u, h};\n"
    "wgmma.mma_async.sync.aligned.m64n256k16.f32.bf16.bf16 "
    "{%0, %1, %2, %3, %4, %5, %6, %7, %8, %9, %10, %11, %12, %13, %14, %15, %16, %17, %18, %19, %20, %21, %22, %23, %24, %25, %26, %27, %28, %29, %30, %31, %32, %33, %34, %35, %36, %37, %38, %39, %40, %41, %42, %43, %44, %45, %46, %47, %48, %49, %50, %51, %52, %53, %54, %55, %56, %57, %58, %59, %60, %61, %62, %63, %64, %65, %66, %67, %68, %69, %70, %71, %72, %73, %74, %75, %76, %77, %78, %79, %80, %81, %82, %83, %84, %85, %86, %87, %88, %89, %90, %91, %92, %93, %94, %95, %96, %97, %98, %99, %100, %101, %102, %103, %104, %105, %106, %107, %108, %109, %110, %111, %112, %113, %114, %115, %116, %117, %118, %119, %120, %121, %122, %123, %124, %125, %126, %127}, "
    "a, b, 1, 1, 1, 0, 1;\n"
    "add.u32 t, %128, 4;\nadd.u32 u, %129, 256;\nmov.b64 a, {t, h};\nmov.b64 b, {u, h};\n"
    "wgmma.mma_async.sync.aligned.m64n256k16.f32.bf16.bf16 "
    "{%0, %1, %2, %3, %4, %5, %6, %7, %8, %9, %10, %11, %12, %13, %14, %15, %16, %17, %18, %19, %20, %21, %22, %23, %24, %25, %26, %27, %28, %29, %30, %31, %32, %33, %34, %35, %36, %37, %38, %39, %40, %41, %42, %43, %44, %45, %46, %47, %48, %49, %50, %51, %52, %53, %54, %55, %56, %57, %58, %59, %60, %61, %62, %63, %64, %65, %66, %67, %68, %69, %70, %71, %72, %73, %74, %75, %76, %77, %78, %79, %80, %81, %82, %83, %84, %85, %86, %87, %88, %89, %90, %91, %92, %93, %94, %95, %96, %97, %98, %99, %100, %101, %102, %103, %104, %105, %106, %107, %108, %109, %110, %111, %112, %113, %114, %115, %116, %117, %118, %119, %120, %121, %122, %123, %124, %125, %126, %127}, "
    "a, b, 1, 1, 1, 0, 1;\n"
    "add.u32 t, %128, 6;\nadd.u32 u, %129, 384;\nmov.b64 a, {t, h};\nmov.b64 b, {u, h};\n"
    "wgmma.mma_async.sync.aligned.m64n256k16.f32.bf16.bf16 "
    "{%0, %1, %2, %3, %4, %5, %6, %7, %8, %9, %10, %11, %12, %13, %14, %15, %16, %17, %18, %19, %20, %21, %22, %23, %24, %25, %26, %27, %28, %29, %30, %31, %32, %33, %34, %35, %36, %37, %38, %39, %40, %41, %42, %43, %44, %45, %46, %47, %48, %49, %50, %51, %52, %53, %54, %55, %56, %57, %58, %59, %60, %61, %62, %63, %64, %65, %66, %67, %68, %69, %70, %71, %72, %73, %74, %75, %76, %77, %78, %79, %80, %81, %82, %83, %84, %85, %86, %87, %88, %89, %90, %91, %92, %93, %94, %95, %96, %97, %98, %99, %100, %101, %102, %103, %104, %105, %106, %107, %108, %109, %110, %111, %112, %113, %114, %115, %116, %117, %118, %119, %120, %121, %122, %123, %124, %125, %126, %127}, "
    "a, b, 1, 1, 1, 0, 1;\n"
    "wgmma.commit_group.sync.aligned;\n}"
    : "=f"(d[0]), "=f"(d[1]), "=f"(d[2]), "=f"(d[3]), "=f"(d[4]), "=f"(d[5]), "=f"(d[6]), "=f"(d[7]), "=f"(d[8]), "=f"(d[9]), "=f"(d[10]), "=f"(d[11]), "=f"(d[12]), "=f"(d[13]), "=f"(d[14]), "=f"(d[15]), "=f"(d[16]), "=f"(d[17]), "=f"(d[18]), "=f"(d[19]), "=f"(d[20]), "=f"(d[21]), "=f"(d[22]), "=f"(d[23]), "=f"(d[24]), "=f"(d[25]), "=f"(d[26]), "=f"(d[27]), "=f"(d[28]), "=f"(d[29]), "=f"(d[30]), "=f"(d[31]), "=f"(d[32]), "=f"(d[33]), "=f"(d[34]), "=f"(d[35]), "=f"(d[36]), "=f"(d[37]), "=f"(d[38]), "=f"(d[39]), "=f"(d[40]), "=f"(d[41]), "=f"(d[42]), "=f"(d[43]), "=f"(d[44]), "=f"(d[45]), "=f"(d[46]), "=f"(d[47]), "=f"(d[48]), "=f"(d[49]), "=f"(d[50]), "=f"(d[51]), "=f"(d[52]), "=f"(d[53]), "=f"(d[54]), "=f"(d[55]), "=f"(d[56]), "=f"(d[57]), "=f"(d[58]), "=f"(d[59]), "=f"(d[60]), "=f"(d[61]), "=f"(d[62]), "=f"(d[63]), "=f"(d[64]), "=f"(d[65]), "=f"(d[66]), "=f"(d[67]), "=f"(d[68]), "=f"(d[69]), "=f"(d[70]), "=f"(d[71]), "=f"(d[72]), "=f"(d[73]), "=f"(d[74]), "=f"(d[75]), "=f"(d[76]), "=f"(d[77]), "=f"(d[78]), "=f"(d[79]), "=f"(d[80]), "=f"(d[81]), "=f"(d[82]), "=f"(d[83]), "=f"(d[84]), "=f"(d[85]), "=f"(d[86]), "=f"(d[87]), "=f"(d[88]), "=f"(d[89]), "=f"(d[90]), "=f"(d[91]), "=f"(d[92]), "=f"(d[93]), "=f"(d[94]), "=f"(d[95]), "=f"(d[96]), "=f"(d[97]), "=f"(d[98]), "=f"(d[99]), "=f"(d[100]), "=f"(d[101]), "=f"(d[102]), "=f"(d[103]), "=f"(d[104]), "=f"(d[105]), "=f"(d[106]), "=f"(d[107]), "=f"(d[108]), "=f"(d[109]), "=f"(d[110]), "=f"(d[111]), "=f"(d[112]), "=f"(d[113]), "=f"(d[114]), "=f"(d[115]), "=f"(d[116]), "=f"(d[117]), "=f"(d[118]), "=f"(d[119]), "=f"(d[120]), "=f"(d[121]), "=f"(d[122]), "=f"(d[123]), "=f"(d[124]), "=f"(d[125]), "=f"(d[126]), "=f"(d[127])
    : "r"(da), "r"(db) : "memory");
}
template <int S> __device__ __forceinline__ void wgmma_acc256(float (&d)[S], uint32_t da, uint32_t db) {
  asm volatile("{\n.reg .b64 a, b;\n.reg .b32 t, u, h;\n.reg .pred p, q;\nmov.b32 h, 0x40000040;\nwgmma.fence.sync.aligned;\n"
    "add.u32 t, %128, 0;\nadd.u32 u, %129, 0;\nmov.b64 a, {t, h};\nmov.b64 b, {u, h};\n"
    "wgmma.mma_async.sync.aligned.m64n256k16.f32.bf16.bf16 "
    "{%0, %1, %2, %3, %4, %5, %6, %7, %8, %9, %10, %11, %12, %13, %14, %15, %16, %17, %18, %19, %20, %21, %22, %23, %24, %25, %26, %27, %28, %29, %30, %31, %32, %33, %34, %35, %36, %37, %38, %39, %40, %41, %42, %43, %44, %45, %46, %47, %48, %49, %50, %51, %52, %53, %54, %55, %56, %57, %58, %59, %60, %61, %62, %63, %64, %65, %66, %67, %68, %69, %70, %71, %72, %73, %74, %75, %76, %77, %78, %79, %80, %81, %82, %83, %84, %85, %86, %87, %88, %89, %90, %91, %92, %93, %94, %95, %96, %97, %98, %99, %100, %101, %102, %103, %104, %105, %106, %107, %108, %109, %110, %111, %112, %113, %114, %115, %116, %117, %118, %119, %120, %121, %122, %123, %124, %125, %126, %127}, "
    "a, b, 1, 1, 1, 0, 1;\n"
    "add.u32 t, %128, 2;\nadd.u32 u, %129, 128;\nmov.b64 a, {t, h};\nmov.b64 b, {u, h};\n"
    "wgmma.mma_async.sync.aligned.m64n256k16.f32.bf16.bf16 "
    "{%0, %1, %2, %3, %4, %5, %6, %7, %8, %9, %10, %11, %12, %13, %14, %15, %16, %17, %18, %19, %20, %21, %22, %23, %24, %25, %26, %27, %28, %29, %30, %31, %32, %33, %34, %35, %36, %37, %38, %39, %40, %41, %42, %43, %44, %45, %46, %47, %48, %49, %50, %51, %52, %53, %54, %55, %56, %57, %58, %59, %60, %61, %62, %63, %64, %65, %66, %67, %68, %69, %70, %71, %72, %73, %74, %75, %76, %77, %78, %79, %80, %81, %82, %83, %84, %85, %86, %87, %88, %89, %90, %91, %92, %93, %94, %95, %96, %97, %98, %99, %100, %101, %102, %103, %104, %105, %106, %107, %108, %109, %110, %111, %112, %113, %114, %115, %116, %117, %118, %119, %120, %121, %122, %123, %124, %125, %126, %127}, "
    "a, b, 1, 1, 1, 0, 1;\n"
    "add.u32 t, %128, 4;\nadd.u32 u, %129, 256;\nmov.b64 a, {t, h};\nmov.b64 b, {u, h};\n"
    "wgmma.mma_async.sync.aligned.m64n256k16.f32.bf16.bf16 "
    "{%0, %1, %2, %3, %4, %5, %6, %7, %8, %9, %10, %11, %12, %13, %14, %15, %16, %17, %18, %19, %20, %21, %22, %23, %24, %25, %26, %27, %28, %29, %30, %31, %32, %33, %34, %35, %36, %37, %38, %39, %40, %41, %42, %43, %44, %45, %46, %47, %48, %49, %50, %51, %52, %53, %54, %55, %56, %57, %58, %59, %60, %61, %62, %63, %64, %65, %66, %67, %68, %69, %70, %71, %72, %73, %74, %75, %76, %77, %78, %79, %80, %81, %82, %83, %84, %85, %86, %87, %88, %89, %90, %91, %92, %93, %94, %95, %96, %97, %98, %99, %100, %101, %102, %103, %104, %105, %106, %107, %108, %109, %110, %111, %112, %113, %114, %115, %116, %117, %118, %119, %120, %121, %122, %123, %124, %125, %126, %127}, "
    "a, b, 1, 1, 1, 0, 1;\n"
    "add.u32 t, %128, 6;\nadd.u32 u, %129, 384;\nmov.b64 a, {t, h};\nmov.b64 b, {u, h};\n"
    "wgmma.mma_async.sync.aligned.m64n256k16.f32.bf16.bf16 "
    "{%0, %1, %2, %3, %4, %5, %6, %7, %8, %9, %10, %11, %12, %13, %14, %15, %16, %17, %18, %19, %20, %21, %22, %23, %24, %25, %26, %27, %28, %29, %30, %31, %32, %33, %34, %35, %36, %37, %38, %39, %40, %41, %42, %43, %44, %45, %46, %47, %48, %49, %50, %51, %52, %53, %54, %55, %56, %57, %58, %59, %60, %61, %62, %63, %64, %65, %66, %67, %68, %69, %70, %71, %72, %73, %74, %75, %76, %77, %78, %79, %80, %81, %82, %83, %84, %85, %86, %87, %88, %89, %90, %91, %92, %93, %94, %95, %96, %97, %98, %99, %100, %101, %102, %103, %104, %105, %106, %107, %108, %109, %110, %111, %112, %113, %114, %115, %116, %117, %118, %119, %120, %121, %122, %123, %124, %125, %126, %127}, "
    "a, b, 1, 1, 1, 0, 1;\n"
    "wgmma.commit_group.sync.aligned;\n}"
    : "+f"(d[0]), "+f"(d[1]), "+f"(d[2]), "+f"(d[3]), "+f"(d[4]), "+f"(d[5]), "+f"(d[6]), "+f"(d[7]), "+f"(d[8]), "+f"(d[9]), "+f"(d[10]), "+f"(d[11]), "+f"(d[12]), "+f"(d[13]), "+f"(d[14]), "+f"(d[15]), "+f"(d[16]), "+f"(d[17]), "+f"(d[18]), "+f"(d[19]), "+f"(d[20]), "+f"(d[21]), "+f"(d[22]), "+f"(d[23]), "+f"(d[24]), "+f"(d[25]), "+f"(d[26]), "+f"(d[27]), "+f"(d[28]), "+f"(d[29]), "+f"(d[30]), "+f"(d[31]), "+f"(d[32]), "+f"(d[33]), "+f"(d[34]), "+f"(d[35]), "+f"(d[36]), "+f"(d[37]), "+f"(d[38]), "+f"(d[39]), "+f"(d[40]), "+f"(d[41]), "+f"(d[42]), "+f"(d[43]), "+f"(d[44]), "+f"(d[45]), "+f"(d[46]), "+f"(d[47]), "+f"(d[48]), "+f"(d[49]), "+f"(d[50]), "+f"(d[51]), "+f"(d[52]), "+f"(d[53]), "+f"(d[54]), "+f"(d[55]), "+f"(d[56]), "+f"(d[57]), "+f"(d[58]), "+f"(d[59]), "+f"(d[60]), "+f"(d[61]), "+f"(d[62]), "+f"(d[63]), "+f"(d[64]), "+f"(d[65]), "+f"(d[66]), "+f"(d[67]), "+f"(d[68]), "+f"(d[69]), "+f"(d[70]), "+f"(d[71]), "+f"(d[72]), "+f"(d[73]), "+f"(d[74]), "+f"(d[75]), "+f"(d[76]), "+f"(d[77]), "+f"(d[78]), "+f"(d[79]), "+f"(d[80]), "+f"(d[81]), "+f"(d[82]), "+f"(d[83]), "+f"(d[84]), "+f"(d[85]), "+f"(d[86]), "+f"(d[87]), "+f"(d[88]), "+f"(d[89]), "+f"(d[90]), "+f"(d[91]), "+f"(d[92]), "+f"(d[93]), "+f"(d[94]), "+f"(d[95]), "+f"(d[96]), "+f"(d[97]), "+f"(d[98]), "+f"(d[99]), "+f"(d[100]), "+f"(d[101]), "+f"(d[102]), "+f"(d[103]), "+f"(d[104]), "+f"(d[105]), "+f"(d[106]), "+f"(d[107]), "+f"(d[108]), "+f"(d[109]), "+f"(d[110]), "+f"(d[111]), "+f"(d[112]), "+f"(d[113]), "+f"(d[114]), "+f"(d[115]), "+f"(d[116]), "+f"(d[117]), "+f"(d[118]), "+f"(d[119]), "+f"(d[120]), "+f"(d[121]), "+f"(d[122]), "+f"(d[123]), "+f"(d[124]), "+f"(d[125]), "+f"(d[126]), "+f"(d[127])
    : "r"(da), "r"(db) : "memory");
}
template <int S> __device__ __forceinline__ void wgmma_aug192(float (&d)[S], uint32_t a0, uint32_t a1, uint32_t db) {
  asm volatile("{\n.reg .b64 b;\n.reg .b32 h, z;\nmov.b32 h, 0x40000000;\nmov.b32 z, 0;\n"
    "mov.b64 b, {%98, h};\nwgmma.fence.sync.aligned;\n"
    "wgmma.mma_async.sync.aligned.m64n192k16.f32.bf16.bf16 "
    "{%0, %1, %2, %3, %4, %5, %6, %7, %8, %9, %10, %11, %12, %13, %14, %15, %16, %17, %18, %19, %20, %21, %22, %23, %24, %25, %26, %27, %28, %29, %30, %31, %32, %33, %34, %35, %36, %37, %38, %39, %40, %41, %42, %43, %44, %45, %46, %47, %48, %49, %50, %51, %52, %53, %54, %55, %56, %57, %58, %59, %60, %61, %62, %63, %64, %65, %66, %67, %68, %69, %70, %71, %72, %73, %74, %75, %76, %77, %78, %79, %80, %81, %82, %83, %84, %85, %86, %87, %88, %89, %90, %91, %92, %93, %94, %95}, "
    "{%96, %97, z, z}, b, 1, 1, 1, 1;\n"
    "wgmma.commit_group.sync.aligned;\n}"
    : "+f"(d[0]), "+f"(d[1]), "+f"(d[2]), "+f"(d[3]), "+f"(d[4]), "+f"(d[5]), "+f"(d[6]), "+f"(d[7]), "+f"(d[8]), "+f"(d[9]), "+f"(d[10]), "+f"(d[11]), "+f"(d[12]), "+f"(d[13]), "+f"(d[14]), "+f"(d[15]), "+f"(d[16]), "+f"(d[17]), "+f"(d[18]), "+f"(d[19]), "+f"(d[20]), "+f"(d[21]), "+f"(d[22]), "+f"(d[23]), "+f"(d[24]), "+f"(d[25]), "+f"(d[26]), "+f"(d[27]), "+f"(d[28]), "+f"(d[29]), "+f"(d[30]), "+f"(d[31]), "+f"(d[32]), "+f"(d[33]), "+f"(d[34]), "+f"(d[35]), "+f"(d[36]), "+f"(d[37]), "+f"(d[38]), "+f"(d[39]), "+f"(d[40]), "+f"(d[41]), "+f"(d[42]), "+f"(d[43]), "+f"(d[44]), "+f"(d[45]), "+f"(d[46]), "+f"(d[47]), "+f"(d[48]), "+f"(d[49]), "+f"(d[50]), "+f"(d[51]), "+f"(d[52]), "+f"(d[53]), "+f"(d[54]), "+f"(d[55]), "+f"(d[56]), "+f"(d[57]), "+f"(d[58]), "+f"(d[59]), "+f"(d[60]), "+f"(d[61]), "+f"(d[62]), "+f"(d[63]), "+f"(d[64]), "+f"(d[65]), "+f"(d[66]), "+f"(d[67]), "+f"(d[68]), "+f"(d[69]), "+f"(d[70]), "+f"(d[71]), "+f"(d[72]), "+f"(d[73]), "+f"(d[74]), "+f"(d[75]), "+f"(d[76]), "+f"(d[77]), "+f"(d[78]), "+f"(d[79]), "+f"(d[80]), "+f"(d[81]), "+f"(d[82]), "+f"(d[83]), "+f"(d[84]), "+f"(d[85]), "+f"(d[86]), "+f"(d[87]), "+f"(d[88]), "+f"(d[89]), "+f"(d[90]), "+f"(d[91]), "+f"(d[92]), "+f"(d[93]), "+f"(d[94]), "+f"(d[95])
    : "r"(a0), "r"(a1), "r"(db) : "memory");
}
template <int S> __device__ __forceinline__ void wgmma_aug256(float (&d)[S], uint32_t a0, uint32_t a1, uint32_t db) {
  asm volatile("{\n.reg .b64 b;\n.reg .b32 h, z;\nmov.b32 h, 0x40000000;\nmov.b32 z, 0;\n"
    "mov.b64 b, {%130, h};\nwgmma.fence.sync.aligned;\n"
    "wgmma.mma_async.sync.aligned.m64n256k16.f32.bf16.bf16 "
    "{%0, %1, %2, %3, %4, %5, %6, %7, %8, %9, %10, %11, %12, %13, %14, %15, %16, %17, %18, %19, %20, %21, %22, %23, %24, %25, %26, %27, %28, %29, %30, %31, %32, %33, %34, %35, %36, %37, %38, %39, %40, %41, %42, %43, %44, %45, %46, %47, %48, %49, %50, %51, %52, %53, %54, %55, %56, %57, %58, %59, %60, %61, %62, %63, %64, %65, %66, %67, %68, %69, %70, %71, %72, %73, %74, %75, %76, %77, %78, %79, %80, %81, %82, %83, %84, %85, %86, %87, %88, %89, %90, %91, %92, %93, %94, %95, %96, %97, %98, %99, %100, %101, %102, %103, %104, %105, %106, %107, %108, %109, %110, %111, %112, %113, %114, %115, %116, %117, %118, %119, %120, %121, %122, %123, %124, %125, %126, %127}, "
    "{%128, %129, z, z}, b, 1, 1, 1, 1;\n"
    "wgmma.commit_group.sync.aligned;\n}"
    : "+f"(d[0]), "+f"(d[1]), "+f"(d[2]), "+f"(d[3]), "+f"(d[4]), "+f"(d[5]), "+f"(d[6]), "+f"(d[7]), "+f"(d[8]), "+f"(d[9]), "+f"(d[10]), "+f"(d[11]), "+f"(d[12]), "+f"(d[13]), "+f"(d[14]), "+f"(d[15]), "+f"(d[16]), "+f"(d[17]), "+f"(d[18]), "+f"(d[19]), "+f"(d[20]), "+f"(d[21]), "+f"(d[22]), "+f"(d[23]), "+f"(d[24]), "+f"(d[25]), "+f"(d[26]), "+f"(d[27]), "+f"(d[28]), "+f"(d[29]), "+f"(d[30]), "+f"(d[31]), "+f"(d[32]), "+f"(d[33]), "+f"(d[34]), "+f"(d[35]), "+f"(d[36]), "+f"(d[37]), "+f"(d[38]), "+f"(d[39]), "+f"(d[40]), "+f"(d[41]), "+f"(d[42]), "+f"(d[43]), "+f"(d[44]), "+f"(d[45]), "+f"(d[46]), "+f"(d[47]), "+f"(d[48]), "+f"(d[49]), "+f"(d[50]), "+f"(d[51]), "+f"(d[52]), "+f"(d[53]), "+f"(d[54]), "+f"(d[55]), "+f"(d[56]), "+f"(d[57]), "+f"(d[58]), "+f"(d[59]), "+f"(d[60]), "+f"(d[61]), "+f"(d[62]), "+f"(d[63]), "+f"(d[64]), "+f"(d[65]), "+f"(d[66]), "+f"(d[67]), "+f"(d[68]), "+f"(d[69]), "+f"(d[70]), "+f"(d[71]), "+f"(d[72]), "+f"(d[73]), "+f"(d[74]), "+f"(d[75]), "+f"(d[76]), "+f"(d[77]), "+f"(d[78]), "+f"(d[79]), "+f"(d[80]), "+f"(d[81]), "+f"(d[82]), "+f"(d[83]), "+f"(d[84]), "+f"(d[85]), "+f"(d[86]), "+f"(d[87]), "+f"(d[88]), "+f"(d[89]), "+f"(d[90]), "+f"(d[91]), "+f"(d[92]), "+f"(d[93]), "+f"(d[94]), "+f"(d[95]), "+f"(d[96]), "+f"(d[97]), "+f"(d[98]), "+f"(d[99]), "+f"(d[100]), "+f"(d[101]), "+f"(d[102]), "+f"(d[103]), "+f"(d[104]), "+f"(d[105]), "+f"(d[106]), "+f"(d[107]), "+f"(d[108]), "+f"(d[109]), "+f"(d[110]), "+f"(d[111]), "+f"(d[112]), "+f"(d[113]), "+f"(d[114]), "+f"(d[115]), "+f"(d[116]), "+f"(d[117]), "+f"(d[118]), "+f"(d[119]), "+f"(d[120]), "+f"(d[121]), "+f"(d[122]), "+f"(d[123]), "+f"(d[124]), "+f"(d[125]), "+f"(d[126]), "+f"(d[127])
    : "r"(a0), "r"(a1), "r"(db) : "memory");
}

__device__ __forceinline__ uint32_t clock32() { uint32_t c; asm volatile("mov.u32 %0, %%clock;" : "=r"(c)); return c; }
__device__ __forceinline__ void spin_until(uint32_t c) {
  asm volatile("{\n.reg .pred p;\n.reg .s32 t;\nLAB_WAIT:\nmov.u32 t, %%clock;\nsub.s32 t, t, %0;\nsetp.lt.s32 p, t, 0;\n@p bra.uni LAB_WAIT;\n}" ::"r"(c) : "memory");
}
struct Nop { __device__ __forceinline__ void operator()(int) const {} };
template <int V> struct IC { static constexpr int v = V; };
struct Pipe {
  uint32_t p, g8, a8, aph, tph, aend, curB, curA, prevB, prevA, bo, so, sph, hold;
  uint2 nx;
  int w; bool l0;
  __device__ __forceinline__ int lane() const { return LSO ? (so >> 5) & 31 : threadIdx.x & 31; }
  __device__ __forceinline__ void adv_a() { a8 += 8; if (a8 == aend) { a8 -= NA * 8; aph ^= 1; } }
  __device__ __forceinline__ uint32_t take() { const uint32_t a = SB + OFF_A + a8 * 1024; adv_a(); return a; }
  __device__ __forceinline__ uint32_t ahead(int d) const { uint32_t ls = a8 + d * 8; if (ls >= aend) ls -= NA * 8; return SB + OFF_A + ls * 1024; }
  __device__ __forceinline__ uint32_t wait_ahead(int d) {
    uint32_t ls = a8 + d * 8, lp = aph;
    if (ls >= aend) { ls -= NA * 8; lp ^= 1; }
    mbar_spin(SB + BAR_FULLA + ls, lp);
    return SB + OFF_A + ls * 1024;
  }
  template <int N, bool FIRST, int S> __device__ __forceinline__ uint2 iss(float (&acc)[S], bool skip) {
    if (p + N / 64 > 16) p = 0;
    const uint32_t da = (((SB + OFF_A) >> 4) | (1u << 16)) + a8 * 64;
    const uint32_t db = (((SB + OFF_B) >> 4) | (512u << 16)) + p * 512;
    prevB = curB; prevA = curA;
    curB = g8 & 56; curA = a8;
    p += N / 64; g8 += 8;
    a8 += skip ? 16 : 8;
    if (a8 >= aend) { a8 -= NA * 8; aph ^= 1; }
    uint2 ok = make_uint2(0, 0);
    if constexpr (N == 128) {
      if (FIRST) wgmma_first128(acc, da, db);
      else ok = wgmma_probe128(acc, da, db, SB + BAR_FULLB + (g8 & 56), (g8 >> 6) & 1, SB + BAR_FULLA + a8, aph);
    }
    if constexpr (N == 192) {
      if (FIRST) wgmma_first192(acc, da, db);
      else ok = wgmma_probe192(acc, da, db, SB + BAR_FULLB + (g8 & 56), (g8 >> 6) & 1, SB + BAR_FULLA + a8, aph);
    }
    if constexpr (N == 256) { if (FIRST) wgmma_first256(acc, da, db); else wgmma_acc256(acc, da, db); }
    return ok;
  }
  __device__ __forceinline__ void ensure(uint2 ok) {
    asm volatile(
        "{\n.reg .pred p, q;\nsetp.ne.u32 p, %4, 0;\nsetp.ne.u32 q, %5, 0;\n@!p bra.uni LAB_WAIT;\n@q bra.uni DONE;\n"
        "LAB_WAIT:\nmbarrier.try_wait.parity.shared::cta.b64 p, [%0], %1;\nmbarrier.try_wait.parity.shared::cta.b64 q, [%2], %3;\n"
        "and.pred p, p, q;\n@!p bra.uni LAB_WAIT;\nDONE:\n}" ::"r"(SB + BAR_FULLB + (g8 & 56)), "r"((g8 >> 6) & 1), "r"(SB + BAR_FULLA + a8), "r"(aph), "r"(ok.x), "r"(ok.y) : "memory");
  }
  template <class Hook> __device__ __forceinline__ void validate(bool check, const CUtensorMap* tm16, int c0, int c1, int wp, int j, Hook hook) {
    const uint32_t rows = SB + OFF_A + a8 * 1024 + wp * 2048, ad = a8 * 1024 + so;
    uint32_t v0 = 0, v1 = 0;
    asm volatile("{\n.reg .pred p;\nsetp.ne.u32 p, %3, 0;\n@p ld.shared.b32 %0, [%2];\n@p ld.shared.b32 %1, [%2 + 1024];\n}" : "+r"(v0), "+r"(v1) : "r"(ad), "r"((uint32_t)check));
    check = true;
    hook();
    while (__any_sync(~0u, check && max(v0, v1) == 0xffffffffu)) {
      const uint32_t bar = SB + BAR_SPEC + (w * 4 + wp) * 8;
      e_load<2048>(rows, tm16, c0 + sched_k(c_sched.v[j][g8 >> 3]), c1 + wp * 16, bar);
      mbar_spin(bar, sph);
      sph ^= 1;
      v0 = lds32(ad); v1 = lds32(ad + 1024);
    }
  }
  __device__ __forceinline__ void drain() {
    wg_wait<0>();
    arrive_2(SB + BAR_EMPTYB + curB, SB + BAR_EMPTYA + curA, l0);
    curB = BAR_DUMMY - BAR_EMPTYB; curA = BAR_DUMMY - BAR_EMPTYA;
  }
  __device__ __forceinline__ void signal_server(uint32_t odd) { __syncwarp(); arrive_n(SB + BAR_SRV + w * 16 + odd * 8, l0); }
  __device__ __forceinline__ void signal_loader() { __syncwarp(); arrive_n(SB + BAR_STG + w * 8, l0); }
  template <int N, bool HOLD = false, int S, class Pre = Nop> __device__ __forceinline__ void begin(float (&acc)[S], uint32_t p0, int proft, Pre pre = Pre()) {
    p = p0;
    const uint32_t c1 = HOLD && !HPF ? clock32() : 0;
    if (HOLD && HPF)
      asm volatile("{\n.reg .pred p;\n.reg .s32 t, c;\nsetp.lt.u32 p, %0, 48;\n@p bra.uni DONE;\nmov.u32 c, %%clock;\nadd.s32 c, c, %0;\n"
                   "LAB_WAIT:\nmov.u32 t, %%clock;\nsub.s32 t, t, c;\nsetp.lt.s32 p, t, 0;\n@p bra.uni LAB_WAIT;\nDONE:\n}" ::"r"(hold) : "memory");
    ensure(PRB ? nx : make_uint2(0, 0));
    if (HOLD && !HPF) spin_until(c1 + lds32(SB + OFF_HOLD + w * 4));
    pre(0);
    PROF_T(w, proft, 0);
    ensure(iss<N, true>(acc, false));
  }
  template <int N, bool ENSURE = true, int S, class Hook, class Mid = Nop> __device__ __forceinline__ void run(float (&acc)[S], int i0, int i1, uint32_t skips, int pause, Hook hook, int imid = -1, Mid mid = Mid()) {
    int i = i0, ev = imid >= 0 ? imid : (w ? pause : -1);
#pragma unroll 1
    while (true) {
      const uint2 ok = iss<N, false>(acc, (skips >> i) & 1);
      wg_wait<1>();
      arrive_2(SB + BAR_EMPTYB + prevB, SB + BAR_EMPTYA + prevA, l0);
      if (pause >= 0 && i + 1 == i1) { nx = ok; break; }
      if constexpr (ENSURE) { ensure(ok); hook(i); } else hook(i, ok);
      i++;
      if (pause < 0 && i == i1) break;
      if (i == ev) {
        const bool ps = w && i == pause;
        if (ps) drain();
        if (i == imid) mid(i);
        if (ps) mbar_spin(SB + BAR_LEAD, tph);
        ev = pause;
      }
    }
  }
  template <int N, bool AUG, int S> __device__ __forceinline__ void end(float (&acc)[S], int ns, uint32_t pa, uint32_t au0, uint32_t au1, int proft) {
    uint32_t augB = 0;
    if (LEARLY) arrive_n(SB + BAR_LEAD + w * (BAR_DUMMY - BAR_LEAD), l0);
    if constexpr (AUG) {
      if (AGK && N == 192)
        asm volatile("{\n.reg .pred p;\nsetp.ne.u32 p, %2, 0;\n@p bra.uni DONE;\nLAB_WAIT:\nmbarrier.try_wait.parity.shared::cta.b64 p, [%0], %1;\n@!p bra.uni LAB_WAIT;\nDONE:\n}"
                     ::"r"(SB + BAR_FULLB + (g8 & 56)), "r"((g8 >> 6) & 1), "r"(nx.x) : "memory");
      else mbar_spin(SB + BAR_FULLB + (g8 & 56), (g8 >> 6) & 1);
      const uint32_t db = (((SB + OFF_B) >> 4) | (64u << 16)) + pa * 512;
      if constexpr (N == 192) wgmma_aug192(acc, au0, au1, db); else wgmma_aug256(acc, au0, au1, db);
      augB = g8 & 56; g8 += 8;
    }
    if (!LEARLY) arrive_n(SB + BAR_LEAD + w * (BAR_DUMMY - BAR_LEAD), l0);
    tph ^= 1;
    if (ns > 0) wait_ahead(ns - 1);
    if (PRB) nx = make_uint2(mbar_test(SB + BAR_FULLB + (g8 & 56), (g8 >> 6) & 1), AUG ? mbar_test(SB + BAR_FULLA + a8, aph) : 1);
    if (HPF && AUG) hold = lds32(SB + OFF_HOLD + w * 4);
    wg_wait<0>();
    arrive_2(SB + BAR_EMPTYB + curB, SB + BAR_EMPTYA + curA, l0);
    if (AUG) arrive_n(SB + BAR_EMPTYB + augB, l0);
    PROF_T(w, proft, 1);
  }
};

__device__ __forceinline__ uint32_t box_addr(uint32_t buf, uint32_t bo, int u) { return (buf + bo) ^ (u * 32); }

__device__ __forceinline__ float bf_round(float x) { return __bfloat162float(__float2bfloat16_rn(x)); }
__device__ __forceinline__ void own_rstd(int w, int wp, int lane, float (&rstd)[2]) {
#pragma unroll
  for (int hh = 0; hh < 2; hh++) rstd[hh] = __uint_as_float(lds32(SB + OFF_RSTD + (w * 72 + 8 + wp * 16 + (lane >> 2) + hh * 8) * 4));
}
__device__ __forceinline__ void stats_fetch(int w, int wp, int lane, uint32_t (&au)[2]) {
  const int g = lane >> 2, q4 = lane & 3;
  float rstd[2];
  own_rstd(w, wp, lane, rstd);
#pragma unroll
  for (int hh = 0; hh < 2; hh++) {
    const float m = __uint_as_float(lds32(SB + OFF_MEAN + (w * 64 + wp * 16 + g + hh * 8) * 4));
    const float v = q4 == 3 ? rcp(rstd[hh]) : -m;
    const float v1 = bf_round(v), v2 = bf_round(v - v1);
    const float p = q4 == 1 ? v2 : (q4 == 2 ? v - v1 - v2 : v1);
    au[hh] = pack_bf16(p, q4 == 3 ? v2 : p);
  }
}

__device__ __forceinline__ void halo_fetch(uint32_t slot, int w, const uint4* src, uint32_t bar) {
  asm volatile("{\n.reg .pred p;\nelect.sync _|p, 0xffffffff;\n@p mbarrier.arrive.expect_tx.shared::cta.b64 _, [%4], 2080;\n"
               "@p cp.async.bulk.shared::cluster.global.mbarrier::complete_tx::bytes [%0], [%2], 2048, [%4];\n"
               "@p cp.async.bulk.shared::cluster.global.mbarrier::complete_tx::bytes [%1], [%3], 32, [%4];\n}"
               ::"r"(slot), "r"(SB + OFF_RSTD + w * 288), "l"(src), "l"(src + 128), "r"(bar) : "memory");
}
struct Attn {
  uint32_t lo[24], hi[24], ha[16], hslot;
  float c[8][4], rstd[2];
  float2 rk[3];
  __device__ __forceinline__ void A(const float (&acc)[96], Pipe& M, int w, int wp, int r, uint4* halo_out) {
    const int lane = M.lane();
    M.signal_loader();
    auto cvt = [&](uint32_t& d, int u) { asm volatile("cvt.rn.bf16x2.f32 %0, %1, %2;" : "=r"(d) : "f"(acc[u + 1]), "f"(acc[u])); };
    auto rest = [&] {
#pragma unroll
      for (int nb = 23; nb >= 0; nb--) {
        cvt(lo[nb], 4 * nb);
        if (nb < 8) cvt(hi[nb], 4 * nb + 2);
        if (nb >= 16) lo[nb] = movm(lo[nb]);
      }
    };
#pragma unroll
    for (int nb = 8; nb < 24; nb++) hi[nb] = pack_bf16(acc[4 * nb + 2], acc[4 * nb + 3]);
    hslot = M.ahead(3);
    const uint32_t hbuf = hslot + wp * 2048 + lane * 16;
#pragma unroll
    for (int nb = 16; nb < 24; nb++) hi[nb] = movm(hi[nb]);
    if (TAR) rest();
    if (wp == 3) {
      if (r < 15) {
#pragma unroll
        for (int p = 0; p < 4; p++) halo_out[p * 32 + lane] = make_uint4(hi[8 + 4 * p] ? hi[8 + 4 * p] : 0x8000u, hi[9 + 4 * p], hi[10 + 4 * p], hi[11 + 4 * p]);
        if (!RSV) {
          const uint32_t rh = lds32(SB + OFF_RSTD + (w * 72 + 64 + (lane & 7)) * 4);
          if (lane < 8) reinterpret_cast<uint32_t*>(halo_out + 128)[lane] = rh ? rh : 0x80000000u;
        }
      }
    } else {
#pragma unroll
      for (int p = 0; p < 4; p++)
        asm volatile("st.shared.v4.b32 [%0], {%1,%2,%3,%4};" ::"r"(hbuf + 2048 + p * 512), "r"(hi[8 + 4 * p]), "r"(hi[9 + 4 * p]), "r"(hi[10 + 4 * p]), "r"(hi[11 + 4 * p]) : "memory");
      __syncwarp();
      arrive_n(SB + BAR_HALO + w * 8, M.l0);
    }
    if (!TAR) rest();
  }
  __device__ __forceinline__ void B(int w, int wp, int lane, uint32_t hph) {
    own_rstd(w, wp, lane, rstd);
    mbar_spin(SB + BAR_HALO + w * 8, hph);
#pragma unroll
    for (int p = 0; p < 4; p++)
      asm volatile("ld.shared.v4.b32 {%0,%1,%2,%3}, [%4];" : "=r"(ha[4 * p]), "=r"(ha[4 * p + 1]), "=r"(ha[4 * p + 2]), "=r"(ha[4 * p + 3]) : "r"(hslot + wp * 2048 + lane * 16 + p * 512) : "memory");
#pragma unroll
    for (int u = 0; u < 3; u++) rk[u] = lds64(SB + OFF_RSTD + (w * 72 + wp * 16 + u * 8 + 2 * (lane & 3)) * 4);
  }
  template <class F> __device__ __forceinline__ void C(int wp, int r, int lane, uint32_t zero, F last) {
    const int g = lane >> 2, q = lane & 3;
    const bool nohalo = (wp == 0) && (r == 0);
    const bool up0 = 2 * q > g, up1 = 2 * q + 1 > g;
    const float sc = 0.17677669529663687f * 1.4426950408889634f;
    const float kx0 = up0 ? rk[0].x : rk[1].x, kx1 = up1 ? rk[0].y : rk[1].y;
    const float ky0 = up0 ? rk[1].x : rk[2].x, ky1 = up1 ? rk[1].y : rk[2].y;
    const float fx = rstd[0] * sc, fy = rstd[1] * sc;
    float sm[2][4] = {}, s0[2][4] = {}, s1[2][4] = {};
#pragma unroll
    for (int ks = 0; ks < 2; ks++)
#pragma unroll
      for (int h = 0; h < 2; h++) {
        const int a = 4 * h + 2 * ks;
        mma16(s0[h], lo[a], hi[a], lo[a + 1], hi[a + 1], lo[8 + a], lo[9 + a]);
        mma16(s1[h], lo[a], hi[a], lo[a + 1], hi[a + 1], hi[8 + a], hi[9 + a]);
      }
#pragma unroll
    for (int u = 0; u < 4; u++) { const int a = 4 * (u & 1) + (u & 2); mma16(sm[u & 1], lo[a], hi[a], lo[a + 1], hi[a + 1], ha[a], ha[a + 1]); }
    uint32_t pf[2][4];
    const uint32_t um = (up0 ? 0xffffu : 0u) | (up1 ? 0xffff0000u : 0u);
#pragma unroll
    for (int h = 0; h < 2; h++) {
      if (nohalo) { sm[h][0] = -INFINITY; sm[h][1] = -INFINITY; }
      float x0 = (up0 ? sm[h][0] : s0[h][0]) * (kx0 * fx), x1 = (up1 ? sm[h][1] : s0[h][1]) * (kx1 * fx);
      float y0 = (up0 ? s0[h][2] : s1[h][2]) * (ky0 * fy), y1 = (up1 ? s0[h][3] : s1[h][3]) * (ky1 * fy);
      float mx = fmaxf(x0, x1), my = fmaxf(y0, y1);
      mx = fmaxf(mx, __shfl_xor_sync(~0u, mx, 1)); my = fmaxf(my, __shfl_xor_sync(~0u, my, 1));
      mx = fmaxf(mx, __shfl_xor_sync(~0u, mx, 2)); my = fmaxf(my, __shfl_xor_sync(~0u, my, 2));
      x0 = ex2(x0 - mx); x1 = ex2(x1 - mx); y0 = ex2(y0 - my); y1 = ex2(y1 - my);
      float sx = x0 + x1, sy = y0 + y1;
      x0 *= kx0; x1 *= kx1; y0 *= ky0; y1 *= ky1;
      sx += __shfl_xor_sync(~0u, sx, 1); sy += __shfl_xor_sync(~0u, sy, 1);
      sx += __shfl_xor_sync(~0u, sx, 2); sy += __shfl_xor_sync(~0u, sy, 2);
      sx = rcp(sx); sy = rcp(sy);
      x0 *= sx; x1 *= sx; y0 *= sy; y1 *= sy;
      const uint32_t px = pack_bf16(x0, x1), py = pack_bf16(y0, y1);
      pf[h][0] = px & um; pf[h][1] = px & ~um; pf[h][2] = py & um; pf[h][3] = py & ~um;
    }
#pragma unroll
    for (int u = 0; u < 4; u++) {
#pragma unroll
      for (int e = 0; e < 4; e++) { c[2 * u][e] = 0.f; c[2 * u + 1][e] = 0.f; }
      mma8(c[2 * u], ha[8 + 2 * u], ha[9 + 2 * u], pf[u >> 1][0]);
      mma8(c[2 * u + 1], lo[16 + 2 * u], lo[17 + 2 * u], pf[u >> 1][2]);
    }
#pragma unroll
    for (int u = 0; u < 4; u++) {
      mma8(c[2 * u], lo[16 + 2 * u], lo[17 + 2 * u], pf[u >> 1][1]);
      mma8(c[2 * u + 1], hi[16 + 2 * u], hi[17 + 2 * u], pf[u >> 1][3]);
    }
    uint32_t dep = 0;
    last();
#pragma unroll
    for (int u = 0; u < (EFIRST == 3 ? 0 : 8); u++) dep |= __float_as_uint(c[u][0]);
    asm volatile("bar.sync %0, 256;" ::"r"(3 + (dep & zero)) : "memory");
  }
  __device__ __forceinline__ void E(Pipe& M, bool urgent) {
#pragma unroll
    for (int u = 0; u < 4; u++)
      asm volatile("stmatrix.sync.aligned.m8n8.x4.trans.shared.b16 [%0], {%1, %2, %3, %4};" ::"r"(box_addr(hslot, M.bo, u)),
                   "r"(pack_bf16(c[2 * u][0], c[2 * u][1])), "r"(pack_bf16(c[2 * u + 1][0], c[2 * u + 1][1])),
                   "r"(pack_bf16(c[2 * u][2], c[2 * u][3])), "r"(pack_bf16(c[2 * u + 1][2], c[2 * u + 1][3])) : "memory");
    __syncwarp();
    arrive_n(SB + (urgent ? BAR_STG + M.w * 8 : BAR_SRV + M.w * 16 + 8), M.l0);
  }
};

__device__ __forceinline__ void epi_res(const float (&acc)[64], const float (&pre)[64], float sc0, float sc1, uint32_t (&xr)[32], Pipe& M, int wp) {
  Pipe T = M;
  const uint32_t buf0 = T.take(), buf1 = T.take();
#pragma unroll
  for (int u = 0; u < 8; u++) {
#pragma unroll
    for (int nb = 2 * u; nb < 2 * u + 2; nb++) {
      xr[2 * nb] = pack_bf16(fmaf(acc[4 * nb], sc0, pre[2 * nb]), fmaf(acc[4 * nb + 1], sc0, pre[32 + 2 * nb]));
      xr[2 * nb + 1] = pack_bf16(fmaf(acc[4 * nb + 2], sc1, pre[2 * nb + 1]), fmaf(acc[4 * nb + 3], sc1, pre[33 + 2 * nb]));
    }
    stsm4(box_addr(u < 4 ? buf0 : buf1, M.bo, u & 3), xr[4 * u], xr[4 * u + 1], xr[4 * u + 2], xr[4 * u + 3]);
    if (u == 3) M.signal_loader();
  }
  __syncwarp();
  arrive_n(SB + BAR_STG2 + M.w * 8, M.l0);
  fence_async_smem();
  if (!NWB) wg_bar(M.w);
}
__device__ __forceinline__ void presum(float (&pre)[64], int lane, float usebias) {
  const uint32_t bias = SB + OFF_VEC + (lane & 3) * 8;
#pragma unroll
  for (int nb = 0; nb < 16; nb++) {
    const float2 b = lds64(bias + nb * 32);
#pragma unroll
    for (int u = 2 * nb; u < 2 * nb + 2; u++) {
      const uint32_t v = __float_as_uint(pre[u]);
      pre[32 + u] = fmaf(b.y, usebias, bf_hi(v)); pre[u] = fmaf(b.x, usebias, bf_lo(v));
    }
  }
}
template <int S, int Q> __device__ __forceinline__ void pack_relu(uint32_t (&o)[Q], const float (&acc)[S]) {
#pragma unroll
  for (int u = 0; u < Q; u++) asm("cvt.rn.relu.bf16x2.f32 %0, %1, %2;" : "=r"(o[u]) : "f"(acc[2 * u + 1]), "f"(acc[2 * u]));
}
__device__ __forceinline__ uint32_t sq_bf16x2(uint32_t a) { uint32_t d; asm("mul.rn.bf16x2 %0, %1, %1;" : "=r"(d) : "r"(a)); return d; }
template <int Q> __device__ __forceinline__ void ffn_stage(const uint32_t (&o)[Q], int i, Pipe& M) {
  i -= M.w;
  if (i == 1 || i == 4 || i == 7 || (Q == 64 && i == 10)) {
    const uint32_t buf = M.wait_ahead(2 - M.w);
#pragma unroll
    for (int b = 0; b < Q / 16; b++)
      if (i == 3 * b + 1) {
#pragma unroll
        for (int u = 4 * b; u < 4 * b + 4; u++)
          stsm4(box_addr(buf, M.bo, u & 3), sq_bf16x2(o[4 * u]), sq_bf16x2(o[4 * u + 1]), sq_bf16x2(o[4 * u + 2]), sq_bf16x2(o[4 * u + 3]));
      }
    M.signal_server((i & 1) ^ (Q == 64));
  }
}

__device__ __forceinline__ void wait_flags(const uint8_t* f, uint32_t tag, int lane) {
  const uint32_t t4 = (tag & 0xff) * 0x01010101u;
  const uint32_t* fp = reinterpret_cast<const uint32_t*>(f) + (lane & (FG / 4 - 1));
  while (__any_sync(~0u, __vsub4(ld_relaxed(fp), t4) & 0x80808080u)) {}
  asm volatile("fence.acquire.gpu;\nfence.proxy.async.global;" ::: "memory");
}
__device__ __forceinline__ uint32_t get_epoch() { mbar_spin(SB + BAR_EPOCH, 0); return __shfl_sync(~0u, lds32(SB + OFF_HOLD + 8), 0); }
__device__ __forceinline__ void aloader(const Params& P, const Ptrs& Q, int bid, int r, int j, int lane, int w, uint32_t e, uint32_t epoch) {
  const uint32_t abase = SB + OFF_A + w * NA * 8192, fbase = SB + BAR_FULLA + w * NA * 8, ebase = SB + BAR_EMPTYA + w * NA * 8;
  uint32_t slot = NPRO, ph = 1, nst = 0, hph = 0, npace = 0;
  int t = -1, kind = -1, a0 = 0, a1 = 0;
  const CUtensorMap* tmA = nullptr;
  uint64_t pol = 0;
  uint4* hin = Q.s->halo[0][0] + (r * 16 + j * 2 + w - 16) * 136;
  uint32_t* const pace = Q.s->pace[0] + (bid & -PG) * 4;
  const uint8_t* const flags = Q.s->flags[r / (FG / 8)][w];
  auto adv = [&] { if (++slot == NA) { slot = 0; ph ^= 1; } };
#pragma unroll 1
  for (int g = NPRO; g <= NSTEP; g++) {
    const uint32_t cur = e;
    e = c_sched.v[j][g + 1];
    if (!(cur & E_RARE)) {
      if (cur & E_HAND) { mbar_spin(ebase + slot * 8, ph); e_arrive(fbase + slot * 8, 1); adv(); }
    } else {
      if (cur & F_NEW) {
        t++; kind = kind == 5 ? 0 : kind + 1;
        const bool narrow = kind == 2 || kind == 5;
        static_assert(TM_XIN == 0 && TM_X == 1 && TM_XA == 2 && TM_O == 3 && TM_H == 4, "map order");
        tmA = &P.tm[t < 2 ? 0 : (0x422311 >> (4 * kind)) & 15];
        pol = ((AEF >> t) & 1) ? 0x12F0000000000000ull : 0x1000000000000000ull;
        a0 = narrow ? 0 : w * 1024; a1 = narrow ? r * 128 + w * 64 : r * 64;
      }
      const bool xo = cur & E_XPUB0;
      uint32_t s = slot;
      if (cur & (E_HAND | E_ATTN | E_XPUB0)) {
        if (cur & E_KEEP) e_arrive(ebase + slot * 8, 4);
#pragma unroll 1
        for (int u = xo ? 0 : 1; u < 2; u++) { mbar_wait(ebase + slot * 8, ph); e_arrive(fbase + slot * 8, 1); adv(); }
      }
      uint32_t hold = 0;
      int lag = 0;
      if ((xo && t < 12) || (cur & F_GATH)) {
        uint32_t v;
        uint32_t v1;
        do asm volatile("ld.relaxed.gpu.global.v2.u32 {%0, %1}, [%2];" : "=r"(v), "=r"(v1) : "l"(pace + npace + (lane & (PG - 1)) * 2) : "memory");
        while (__any_sync(~0u, ((v ^ (epoch * 16 + t - 1)) | (v ^ v1)) & 31));
        v += v1;
        npace ^= PG * 2;
        lag = min((int)(v - __shfl_sync(~0u, v, bid & (PG - 1))), 8000) * 27 >> 5;
        hold = __reduce_max_sync(~0u, lag);
        asm volatile("st.shared.b32 [%0], %1;" ::"r"(SB + OFF_HOLD + w * 4), "r"(hold) : "memory");
      }
      if (cur & (E_ATTN | E_XPUB0)) {
        const uint32_t s2 = s == NA - 1 ? 0 : s + 1;
        mbar_wait(SB + BAR_STG + w * 8, nst & 1);
        nst++;
        LT(0);
        const uint32_t c1 = clock32();
        e_store(tmA, a0 + sched_k(cur), a1, abase + s * 8192);
        if (xo) {
          if (!LATE2 || t == 12) {
            mbar_spin(SB + BAR_STG2 + w * 8, ~t & 1);
            e_store(tmA, a0 + sched_k(cur) + 64, a1, abase + s2 * 8192);
          }
          if (t == 12) break;
          if (NPD) {
#pragma unroll 1
            for (int u = 0; u < NPD; u++) {
              const int c = u + (u >= j);
              spin_until(c1 + SDP + __shfl_sync(~0u, lag, Q44 ? c * 4 + (bid & 3) : c * 2 + (bid & 1)));
              e_load(abase + slot * 8192, tmA, a0 + c * 128, a1, fbase + slot * 8, pol);
              adv();
            }
            g += NPD + 1;
            e = c_sched.v[j][g + 1];
          }
          if (LATE2) {
            mbar_spin(SB + BAR_STG2 + w * 8, ~t & 1);
            e_store(tmA, a0 + sched_k(cur) + 64, a1, abase + s2 * 8192);
          }
        } else e_arrive(SB + BAR_OWN + w * 8, 1);
        LT(1);
        spin_until(c1 + hold + (xo ? SDELAY : SDELAYO));
        LT(2);
        LT(5);
      }
      if (cur & E_SIG) {
        e_arrive(SB + BAR_SRV + w * 16, 4);
      }
      if (cur & E_REL) bulk_wait_all();
      if (cur & E_HALO) {
        mbar_spin(SB + BAR_STG + w * 8, nst & 1);
        nst++;
        const uint32_t hs = abase + (slot >= 3 ? slot - 3 : slot + 3) * 8192, ad = hs + lane * 32 + (lane & 4) * 4;
        if (r == 0) {
#pragma unroll
          for (int p = 0; p < 4; p++) sts128(hs + lane * 16 + p * 512, 0, 0, 0, 0);
          asm volatile("st.shared.b32 [%0], %1;" ::"r"(SB + OFF_RSTD + w * 288 + (lane & 7) * 4), "r"(0x3f800000) : "memory");
        } else {
          spin_until(clock32() + HDELAY);
          do {
            halo_fetch(hs, w, hin, SB + BAR_SPEC + 80 + w * 8);
            mbar_spin(SB + BAR_SPEC + 80 + w * 8, hph);
            hph ^= 1;
          } while (__any_sync(~0u, min(min(lds32(ad), lds32(ad + 1024)), lds32(SB + OFF_RSTD + w * 288)) == 0));
        }
        e_arrive(SB + BAR_HALO + w * 8, 1);
      }
      if ((cur & E_REL) && (kind == 1 || kind == 2) && r > 0) {
        uint4* hz = hin + lane;
        hin += 256 * 136;
#pragma unroll
        for (int p = 0; p < 4; p++) hz[p * 32] = make_uint4(0, 0, 0, 0);
        if (lane < 2) hz[128] = make_uint4(0, 0, 0, 0);
      }
      if (cur & E_WAIT) {
        wait_flags(flags + ((cur & E_PART1) ? FG : 0), epoch * 16 + t, lane);
      }
    }
    if (!(cur & (F_AUG | F_NOA))) {
      mbar_wait(ebase + slot * 8, ph);
      e_load(abase + slot * 8192, tmA, a0 + sched_k(cur), a1, fbase + slot * 8, pol);
      adv();
      if ((cur & F_STAMP) && (ST2W || w == 0)) {
        if (!ST2W) mbar_spin(SB + BAR_EMPTYB + ((g - 6) & 7) * 8, ((g - 6) >> 3) & 1);
        uint32_t stamp;
        asm volatile("mov.u32 %0, %%globaltimer_lo;" : "=r"(stamp));
        asm volatile("st.relaxed.gpu.global.u32 [%0], %1;" ::"l"(pace + npace + (ST2W ? (bid & (PG - 1)) * 2 + w : bid & (PG - 1))), "r"((stamp & ~31u) | ((epoch * 16 + t) & 31)) : "memory");
      }
    }
  }
  bulk_wait_all();
}

__device__ __forceinline__ void bloader(const Params& P, const Ptrs& Q, bool aux, int j, int lane, uint32_t e, uint32_t epoch) {
  const uint32_t* const sched = c_sched.v[aux ? 8 : j];
  int kind = -1, c2 = 0, c3 = 0, na = 0;
  const CUtensorMap* tmB = nullptr;
  uint32_t sph = 0, efm = aux ? 0 : BEF * 2;
  uint64_t pol = 0;
#pragma unroll 1
  for (int g = aux ? 8 + (j & 1) : NPRO; g < (aux ? NSTEP_AUX : NSTEP); g += 1 + aux) {
    const uint32_t cur = e;
    e = sched[g + 1 + aux];
    if (cur & F_NEW) {
      kind = kind == 5 ? 0 : kind + ((cur >> 29) & 3);
      static_assert(TM_WQKV == 5 && TM_WO == 6 && TM_W1A == 7 && TM_W1B == 8 && TM_W2 == 9, "map order");
      tmB = &P.tm[(0x978655 >> (4 * kind)) & 15];
      efm >>= 1;
      pol = (efm & 1) ? 0x12F0000000000000ull : 0x1000000000000000ull;
      na = (0x243233 >> (4 * kind)) & 15;
      c2 = ((0x277200 >> (4 * kind)) & 15) * j + (kind == 4 ? 3 : 0);
      c3 = kind <= 1 ? kind * 8 + j : 0;
    }
    const int need = g - (int)((cur >> 5) & 15);
    const uint32_t dst = SB + OFF_B + (cur & 31) * 8192, bar = SB + BAR_FULLB + (g & 7) * 8;
    mbar_wait(SB + BAR_EMPTYB + (need & 7) * 8, (need >> 3) & 1);
    if (!(cur & F_AUG)) {
      asm volatile("{\n.reg .pred p;\nelect.sync _|p, 0xffffffff;\n@p mbarrier.arrive.expect_tx.shared::cta.b64 _, [%2], %7;\n"
                   "@p cp.async.bulk.tensor.4d.shared::cluster.global.mbarrier::complete_tx::bytes.L2::cache_hint [%0], [%1, {%3, %4, %5, %6}], [%2], %8;\n}"
                   ::"r"(dst), "l"(tmB), "r"(bar), "r"(0), "r"(sched_k(cur)), "r"(c2), "r"(c3), "r"(na * 8192), "l"(pol) : "memory");
    } else {
      const bool chk = g < NSTEP / 2;
      const uint32_t b2 = chk ? SB + BAR_AUG : bar, ad = dst + lane * 16 + (lane >> 3) * 4;
      while (true) {
        asm volatile("{\n.reg .pred p;\nelect.sync _|p, 0xffffffff;\n@p mbarrier.arrive.expect_tx.shared::cta.b64 _, [%2], 4096;\n"
                     "@p cp.async.bulk.shared::cluster.global.mbarrier::complete_tx::bytes [%0], [%1], 4096, [%2];\n}"
                     ::"r"(dst), "l"(Q.s->aug[epoch & 1][(kind - (kind >= 3)) * 8 + j]), "r"(b2) : "memory");
        if (!chk) break;
        mbar_spin(b2, sph);
        sph ^= 1;
        uint32_t mn = ~0u;
#pragma unroll
        for (int u = 0; u < 8; u++) mn = min(mn, lds32(ad + u * 512));
        if (!__any_sync(~0u, mn == 0)) { e_arrive(bar, 1); break; }
      }
      __syncwarp();
    }
  }
}

constexpr uint32_t job_slots(int layer) {
  const int pos[10] = {11, 26, 63, 73, 77, 81, 92, 96, 100, 104};
  uint32_t v = 0;
  for (int m = 0; m < 10; m++) v |= (uint32_t)((layer * 148 + pos[m]) % NA) << (3 * m);
  return v;
}
constexpr uint32_t JOB_SLOTS0 = job_slots(0), JOB_SLOTS1 = job_slots(1);
__device__ __forceinline__ void server(const Params& P, const Ptrs& Q, int bid, int r, int j, int lane, uint32_t epoch) {
  if (CPF) spin_until(clock32() + CPF);
  epoch += __shfl_sync(~0u, c_sched.v[j][lane < 18 ? lane * 16 : 0] >> 31, 0);
  {
    const uint2 b = reinterpret_cast<const uint2*>(Q.b2 + j * 128)[lane];
    sts128(SB + OFF_VEC + lane * 16, b.x << 16, b.x & 0xffff0000u, b.y << 16, b.y & 0xffff0000u);
  }
  int hl = 0;
  uint32_t fph = 0, pend = SB + BAR_DUMMY3;
#pragma unroll 1
  for (int n = 0; n < 20; n++) {
    const int layer = n >= 10, m = n - 10 * layer;
    const bool stat = m == 0 || m == 2;
    const uint32_t slot = ((layer ? JOB_SLOTS1 : JOB_SLOTS0) >> (m * 3)) & 7;
    auto fetch = [&](int w) {
      asm volatile("{\n.reg .pred p;\nelect.sync _|p, 0xffffffff;\n@p mbarrier.arrive.expect_tx.shared::cta.b64 _, [%2], 4096;\n"
                   "@p cp.async.bulk.shared::cluster.global.mbarrier::complete_tx::bytes [%0], [%1], 4096, [%2];\n}"
                   ::"r"(SB + OFF_A + (w * NA + slot) * 8192), "l"(&Q.s->stats[hl][r * 32 + w * 16][0][0]), "r"(SB + BAR_SPEC + 64 + w * 8) : "memory");
    };
#pragma unroll 1
    for (int w = 0; w < 2; w++) {
      mbar_spin(SB + BAR_SRV + w * 16 + (n & 1) * 8, (n >> 1) & 1);
      if (stat) fetch(w);
      else {
        e_store(&P.tm[m == 1 ? TM_O : TM_H], m == 1 ? j * 64 : 448 * j + (m - 3) * 64, r * 128 + w * 64, SB + OFF_A + (w * NA + slot) * 8192);
        bulk_wait_read<1>();
        e_arrive(pend, 4);
        pend = SB + BAR_EMPTYA + (w * NA + slot) * 8;
      }
    }
    if (stat) {
#pragma unroll 1
      for (int w = 0; w < 2; w++) {
        const uint32_t src = SB + OFF_A + (w * NA + slot) * 8192 + (lane >> 1) * 256 + ((lane >> 1) & 7) * 32 + (lane & 1) * 16;
        float ms[2], md[2], mq[2], m0[2];
        while (true) {
          mbar_spin(SB + BAR_SPEC + 64 + w * 8, (fph >> w) & 1);
          fph ^= 1u << w;
          uint32_t bad = 0;
          ms[0] = ms[1] = md[0] = md[1] = mq[0] = mq[1] = m0[0] = m0[1] = 0.f;
#pragma unroll 1
          for (int p = 0; p < 8; p += 2) {
            const float4 v2[2] = {lds128(src ^ (p * 32)), lds128(src ^ (p * 32) ^ 32)};
            if (p == 0) { m0[0] = v2[0].x; m0[1] = v2[0].z; }
#pragma unroll
            for (int z = 0; z < 2; z++) {
              const float4 v = v2[z];
              const float a = v.x - m0[0], b = v.z - m0[1];
              bad |= __float_as_uint(v.y) ^ epoch;
              ms[0] += a; md[0] = fmaf(a, a, md[0]); mq[0] += __uint_as_float(__float_as_uint(v.y) & ~63u);
              ms[1] += b; md[1] = fmaf(b, b, md[1]); mq[1] += v.w;
            }
          }
          if (!__any_sync(~0u, bad & 63)) break;
          fetch(w);
          __syncwarp();
        }
        e_arrive(SB + BAR_EMPTYA + (w * NA + slot) * 8, 4);
        const int row = (lane >> 3) * 16 + (lane & 7);
#pragma unroll
        for (int z = 0; z < 2; z++) {
          const float d = ms[z] * 0.125f;
          asm volatile("st.shared.f32 [%0], %1;" ::"r"(SB + OFF_MEAN + (w * 64 + row + z * 8) * 4), "f"(m0[z] + d) : "memory");
          const float rs = rsq(fmaf(mq[z], 1.f / 1024.f, fmaxf(fmaf(md[z], 0.125f, -d * d), 0.f)) + 1e-5f);
          asm volatile("st.shared.f32 [%0], %1;" ::"r"(SB + OFF_RSTD + (w * 72 + 8 + row + z * 8) * 4), "f"(rs) : "memory");
          if (RSV && z && !m && lane >= 24) {
            float* const h = reinterpret_cast<float*>(Q.s->halo[0][0] + 122) + (uint32_t)((hl * 256 + r * 16 + j * 2 + w) * 544 + lane);
            h[0] = h[256 * 544] = rs != 0.f ? rs : -0.f;
          }
        }
        e_arrive(SB + BAR_STAT + w * 8, 8);
      }
    }
    if (stat && n != 12) {
#pragma unroll 1
      for (int u = 0; u < (m ? 2 : 3); u++) {
        const uint32_t pitch = u == 2 ? 448 : 128;
        uint4* p = reinterpret_cast<uint4*>(u == 2 ? Q.s->h : (m ? Q.out : Q.s->x)) + (u == 2 ? 64 + j * 8 : j * 16 + u * 8) + ((r * 128 + (lane >> 3)) * pitch + (lane & 7));
#pragma unroll 1
        for (int k = 0; k < 32 / FUN; k++) {
#pragma unroll
          for (int z = 0; z < FUN; z++) {
            *p = make_uint4(~0u, ~0u, ~0u, ~0u);
            p += 4 * pitch;
            asm volatile("" : "+l"(p));
          }
        }
      }
      __syncwarp();
    }
    if ((0x222 >> m) & 1) {
      bulk_wait_all();
      e_arrive(pend, 4);
      pend = SB + BAR_DUMMY3;
      if (lane < 2) st_release8(&Q.s->flags[r / (FG / 8)][lane][(r & (FG / 8 - 1)) * 8 + j + (m == 9 ? FG : 0)], epoch * 16 + layer * 6 + (m == 1 ? 2 : 5));
      __syncwarp();
    }
    hl += stat;
  }
}

__device__ __forceinline__ void aux_math(const Ptrs& Q, int bid, int jj, int warp, int lane) {
  const int g = lane >> 2, q = lane & 3, c0 = (warp & 3) * 2;
  uint32_t st = warp >> 2, bf[16][4] = {};
  const uint32_t ad0 = SB + ((lane >> 4) * 8 + (lane & 7)) * 128 + (((c0 + ((lane >> 3) & 1)) ^ (lane & 7)) << 4);
#pragma unroll 1
  for (int t = 0; t < 4; t++) {
    float acc[4][4] = {};
    uint32_t bias[8];
#pragma unroll
    for (int a = 0; a < 8; a++) bias[a] = t >= 2 ? reinterpret_cast<const uint32_t*>(Q.b1 + 448 * jj + (t - 2) * 192 + c0 * 8)[(a >> 1) * 32 + (a & 1) * 4 + q] : 0u;
#pragma unroll 1
    for (int i = 0; i < 16; i++, st += 2) {
      const uint32_t ad = ad0 + (c_sched.v[8][st] & 31) * 8192;
      mbar_spin(SB + BAR_FULLB + (st & 7) * 8, (st >> 3) & 1);
#pragma unroll
      for (int u = 0; u < 16; u++)
        asm volatile("{\n.reg .pred p;\nsetp.ne.u32 p, %5, 0;\n@p ldmatrix.sync.aligned.m8n8.x4.trans.shared.b16 {%0,%1,%2,%3}, [%4];\n}"
                     : "+r"(bf[u][0]), "+r"(bf[u][1]), "+r"(bf[u][2]), "+r"(bf[u][3])
                     : "r"(ad + (u & 3) * 8192 + (u >> 2) * 2048), "r"((u & 3) != 3 || t == 3 ? 1 : 0) : "memory");
      __syncwarp();
      e_arrive(SB + BAR_EMPTYB + (st & 7) * 8, 2);
#pragma unroll
      for (int u = 0; u < 16; u++) mma16(acc[u & 3], bf[u][0], bf[u][1], bf[u][2], bf[u][3], 0x3F803F80u, 0x3F803F80u);
    }
    const uint32_t epoch = lds32(SB + OFF_HOLD + 8);
    const uint32_t o = (t * 8 + jj) * 1024 + g * 32 + ((c0 ^ g) << 2) + q + (epoch & 1) * 32768;
    uint32_t *const p0 = Q.s->aug[0][0] + o, *const p1 = Q.s->aug[0][0] + (o ^ 4);
#pragma unroll
    for (int a = 0; a < 8; a++) {
      const float u = acc[a >> 1][(a & 1) * 2];
      uint32_t h = movm(pack_bf16(u, u - bf_round(u)));
      if (g >= 6) h = bias[a];
      ((a & 1) ? p1 : p0)[(a >> 1) * 256] = h ? h : 0x8000u;
    }
    uint4* const z = reinterpret_cast<uint4*>(Q.s->aug[~epoch & 1][t * 8 + jj]) + (threadIdx.x & 127);
    z[0] = z[128] = make_uint4(0, 0, 0, 0);
  }
}

template <bool BYSM> __global__ void __launch_bounds__(NTHREADS, 1) mega_kernel(const __grid_constant__ Ptrs Q, const __grid_constant__ Params P) {
  extern __shared__ __align__(1024) uint8_t smem_raw[];
  constexpr uint32_t sb = SB;
  const uint32_t centry = clock32();
  const int warp = __shfl_sync(~0u, threadIdx.x >> 5, 0), lane = threadIdx.x & 31;
  const int bid = BYSM ? work_id() : blockIdx.x;
  const bool aux = bid >= NMAIN;
  const int r = Q44 ? ((bid >> 5) << 2) | (bid & 3) : ((bid >> 4) << 1) | (bid & 1), j = (aux ? bid * 2 : bid >> (1 + Q44)) & 7;
  PRO(0);
  {
    const uint32_t b = sb + OFF_BAR + warp * 48, cnt = warp < 6 ? 1 : (warp < 10 ? 4 : 8);
    asm volatile("{\n.reg .pred p;\nelect.sync _|p, 0xffffffff;\n@p mbarrier.init.shared::cta.b64 [%0], %1;\n@p mbarrier.init.shared::cta.b64 [%0 + 8], %1;\n"
                 "@p mbarrier.init.shared::cta.b64 [%0 + 16], %1;\n@p mbarrier.init.shared::cta.b64 [%0 + 24], %1;\n"
                 "@p mbarrier.init.shared::cta.b64 [%0 + 32], %1;\n@p mbarrier.init.shared::cta.b64 [%0 + 40], %1;\nfence.mbarrier_init.release.cluster;\n}"
                 ::"r"(b), "r"(cnt) : "memory");
  }
  __syncthreads();
  {
    static_assert(NPRO == 4 && ROUND0 == 0, "prologue stages");
    const int st = ((11 - warp) * (aux ? 32 : 11)) >> 5, op = aux ? (st < 8) * 2 : 11 - warp - 3 * st, sd = aux ? st >> STGX : (op == 2 ? st : st & 2);
    const uint32_t bar0 = sb + OFF_BAR + (op * 6 + st) * 8;
    const int kc = aux ? (st >> 1) * 64 : (st & 2 ? (ROUND1 >> (4 * j)) & 15 : 0) * 128 + (st & 1) * 64;
    spin_until(centry + (sd ? STG0 + sd * STG1 : 0));
    if (op == 2) {
      asm volatile("{\n.reg .pred p;\nelect.sync _|p, 0xffffffff;\n@p mbarrier.arrive.expect_tx.shared::cta.b64 _, [%2], 24576;\n"
                   "@p cp.async.bulk.tensor.4d.shared::cluster.global.mbarrier::complete_tx::bytes [%0], [%1, {%3, %4, %3, %5}], [%2];\n}"
                   ::"r"(sb + OFF_B + (aux ? (st & 1) * 114688 + (st >> 1) * 24576 : (st + 1) * 24576)), "l"(&P.tm[TM_WQKV]), "r"(bar0), "r"(0), "r"(kc), "r"(j + (st & aux)) : "memory");
    } else if (!aux) e_load(sb + OFF_A + (op * 6 + st) * 8192, &P.tm[TM_XIN], op * 1024 + kc, r * 64, bar0);
    PRO(1);
    asm volatile("prefetch.tensormap [%0];" ::"l"(&P.tm[warp]) : "memory");
  }
  if (warp >= 8) {
    asm volatile("setmaxnreg.dec.sync.aligned.u32 24;");
    if (warp == 11) {
      if (smem_u32(smem_raw) != SB) __trap();
      const uint32_t epoch = __shfl_sync(~0u, ld_relaxed(&Q.s->epoch[bid]) + 1, 0);
      Q.s->epoch[bid] = epoch;
      asm volatile("st.shared.b32 [%0], %1;" ::"r"(sb + OFF_HOLD + 8), "r"(epoch) : "memory");
      e_arrive(sb + BAR_EPOCH, 1);
      PRO(2);
      if (!aux) server(P, Q, bid, r, j, lane, epoch);
    } else {
      const uint32_t e = c_sched.v[aux ? 8 : j][aux ? warp : NPRO];
      spin_until(centry + STGL + (e >> 31));
      PRO(2);
      const uint32_t epoch = get_epoch();
      PRO(3);
      if (warp <= 8 + aux) bloader(P, Q, aux, j + warp - 8, lane, e, epoch);
      else if (!aux) aloader(P, Q, bid, r, j, lane, warp - 9, e, epoch);
    }
  } else if (aux) aux_math(Q, bid, j + (warp >> 2), warp, lane);
  else {
    asm volatile("setmaxnreg.inc.sync.aligned.u32 240;");
    const int w = warp >> 2, wp = warp & 3;
    {
      uint32_t xr[32];
#pragma unroll
      for (int u = 0; u < 32; u++) if (NOI) asm volatile("" : "=r"(xr[u])); else xr[u] = 0;
      Pipe M;
      M.p = 0; M.g8 = 0; M.a8 = w * NA * 8; M.aph = 0; M.tph = 0; M.aend = (w + 1) * NA * 8;
      M.curB = M.curA = M.prevB = M.prevA = M.sph = 0; M.nx = make_uint2(0, 0); M.w = w; M.l0 = lane == 0;
      M.bo = (wp * 16 + (lane & 15)) * 128 + (((lane >> 4) ^ (lane & 7)) << 4);
      M.so = __shfl_sync(~0u, SB + OFF_A + wp * 2048 + lane * 32 + (lane >> 2) * 4, lane);
      M.bo = __shfl_sync(~0u, M.bo, lane);
      auto nop = [](int) {};
      const uint32_t zero = gridDim.y - 1;
      PROF_T(w, 0, 3);
      if (STARTC) spin_until(centry + STARTC);
#pragma unroll 1
      for (int hl = 0; hl < 4; hl++) {
        const int t0 = hl * 3;
        const bool ffn = hl & 1;
        float acc[96], acn[64];
        uint32_t au[2] = {0u, 0u};
        {
          const int d = hl ? 0 : ((OWNP * 2u) >> (4 * j)) & 15;
          auto own = [&](auto h, uint32_t dep = 0) {
#pragma unroll
            for (int u = 4 * h.v; u < 4 * h.v + 4; u++)
              asm volatile("ldmatrix.sync.aligned.m8n8.x4.shared.b16 {%0,%1,%2,%3}, [%4];" : "=r"(xr[4 * u]), "=r"(xr[4 * u + 1]), "=r"(xr[4 * u + 2]), "=r"(xr[4 * u + 3])
                           : "r"(box_addr(sb + OFF_A + M.a8 * 1024, M.bo + dep, u & 3)) : "memory");
          };
          M.begin<192>(acc, ffn ? 12 : 3, t0, [&](int) { if (hl + d == 0) own(IC<0>{}); });
          if (hl + d == 0) own(IC<1>{}, (xr[0] | xr[4] | xr[8] | xr[12]) & zero);
          float ss[2] = {0.f, 0.f}, sq[2] = {0.f, 0.f};
          auto part = [&](auto c0, auto n) {
#pragma unroll
            for (int v = 0; v < 4 * n.v; v++) {
              const int u = c0.v + v / n.v * 4 + v % n.v;
              float a, b;
              asm volatile("shl.b32 %0, %2, 16;\nand.b32 %1, %2, 0xffff0000;" : "=f"(a), "=f"(b) : "r"(xr[u]));
              ss[u & 1] += a + b; sq[u & 1] = fmaf(a, a, fmaf(b, b, sq[u & 1]));
            }
          };
          const uint64_t plan = hl ? PLAN1 : (d ? PLAN0 : PLANZ);
          auto todo = [&](int i) { uint64_t v; asm volatile("shr.u64 %0, %1, %2;" : "=l"(v) : "l"(plan), "r"((i + 1 - d) * 8)); return (uint32_t)v; };
          uint32_t m = todo(1);
          M.run<192, false>(acc, 1, 16, 1u << 10, 16 - (ffn ? LEAD3 : LEAD0), [&](int i, uint2 ok) {
           CT(0);
           if (m & 7) {
             if (m & 1) part(IC<0>{}, IC<2>{});
             if (m & 2) part(IC<2>{}, IC<2>{});
             if (m & 4) part(IC<16>{}, IC<1>{});
           }
           CT(1);
           M.ensure(ok);
           CT(3);
           M.validate(hl != 0, &P.tm[ffn ? TM_XA16 : TM_X16], w * 1024, r * 64, wp, j, [&] {
            if (m & 0xf8) {
              if (m & 128) { if (m & 1) own(IC<1>{}); else own(IC<0>{}); }
              if (m & 8) part(IC<17>{}, IC<1>{});
              if (m & 16) part(IC<18>{}, IC<1>{});
              if (m & 32) part(IC<19>{}, IC<1>{});
              if (m & 64) {
                const uint32_t epoch = lds32(sb + OFF_HOLD + 8);
#pragma unroll
                for (int o = 1; o < 4; o *= 2)
#pragma unroll
                  for (int z = 0; z < 2; z++) { ss[z] += __shfl_xor_sync(~0u, ss[z], o); sq[z] += __shfl_xor_sync(~0u, sq[z], o); }
                const float m0 = ss[0] * (1.f / 128.f), m1 = ss[1] * (1.f / 128.f);
                const int rowpair = r * 64 + w * 32 + wp * 8 + (M.lane() >> 2);
                if ((M.lane() & 3) == 0)
                  st_pkt(&Q.s->stats[hl][rowpair >> 1][j][rowpair & 1], __float_as_uint(m0), (__float_as_uint(fmaxf(fmaf(-ss[0], m0, sq[0]), 0.f)) & ~63u) | (epoch & 63),
                         __float_as_uint(m1), __float_as_uint(fmaxf(fmaf(-ss[1], m1, sq[1]), 0.f)));
              }
            }
            m = todo(i + 1);
            if (i == STATI) { mbar_spin(sb + BAR_STAT + w * 8, hl & 1); stats_fetch(w, wp, M.lane(), au); }
           });
           CT(4);
          });
          M.end<192, true>(acc, ffn ? 0 : 4, 15, au[0], au[1], t0);
          PROF_T(w, t0, 2);
        }
        if (!ffn) {
          Attn T;
#pragma unroll 1
          for (int wave = 0; wave < 2; wave++) {
            AP(9);
            uint4* const hp = Q.s->halo[0][0] + (uint32_t)(((hl + wave) * 256 + r * 16 + j * 2 + w) * 136);
            T.A(acc, M, w, wp, r, hp);
            AP(0);
            if (wave == 0) {
              M.begin<192, PACE2 & 1>(acc, 6, t0 + 1);
              M.run<192>(acc, 1, NH1, 4, -1, nop);
              T.B(w, wp, M.lane(), 0);
              M.drain();
            } else {
              M.begin<128, (PACE2 >> 1) & 1>(acn, 12, t0 + 2);
              M.run<128>(acn, 1, NH2, 4, -1, nop);
              T.B(w, wp, M.lane(), 1);
              M.drain();
#pragma unroll
              for (int z = 0; z < 64; z++) asm volatile("mov.b32 %0, %1;" : "=f"(acc[z]) : "f"(acn[z]));
#pragma unroll
              for (int z = 64; z < 96; z++) acc[z] = 0.f;
            }
            AP(2);
            T.C(wp, r, M.lane(), zero, [&] { if (EFIRST == 3 || (EFIRST == 2 && wave)) T.E(M, wave); });
            AP(3);
            if (wave == 1) break;
            M.run<192>(acc, NH1, 16, 1u << 7, 16 - LEAD1, [&](int i) { if (EFIRST < 3 && i == NH1) T.E(M, false); });
            M.end<192, true>(acc, 4, 10, au[0], au[1], t0 + 1);
            PROF_T(w, t0 + 1, 2);
          }
#pragma unroll
          for (int z = 0; z < 64; z++) asm volatile("mov.b32 %0, %1;" : "=f"(acn[z]) : "f"(acc[z]));
          if (EFIRST == 1) T.E(M, true);
          else if (!EFIRST) {
            M.ensure(M.iss<128, false>(acn, false));
            T.E(M, true);
          }
        } else {
          uint32_t pk[48], pk2[64];
          pack_relu(pk, acc);
          {
            float acc2[128];
            M.begin<256, (PACE2 >> 3) & 1>(acc2, 0, t0 + 1);
            M.run<256>(acc2, 1, 16, 0x248, 16 - LEAD4, [&](int i) { ffn_stage(pk, i, M); });
            M.end<256, true>(acc2, 0, 0, au[0], au[1], t0 + 1);
            pack_relu(pk2, acc2);
            PROF_T(w, t0 + 1, 2);
          }
          M.begin<128, (PACE2 >> 4) & 1>(acn, 2, t0 + 2);
          M.run<128>(acn, 1, 13, 0x1248, -1, [&](int i) { ffn_stage(pk2, i, M); });
        }
        {
          float pre[64], rstd[2] = {0.f, 0.f};
#pragma unroll
          for (int u = 0; u < 32; u++) { pre[u] = __uint_as_float(xr[u]); if (!NOI) pre[32 + u] = 0.f; }
          if (NOI) {
#pragma unroll
            for (int u = 32; u < 64; u += 4) { const float4 v = lds128(sb + OFF_VEC); pre[u] = v.x; pre[u + 1] = v.y; pre[u + 2] = v.z; pre[u + 3] = v.w; }
          }
          const int ks = ffn ? 56 : 16, pause = ks - (ffn ? LEAD5 : LEAD2), vfrom = ffn ? 99 : 7;
          M.run<128>(acn, ffn ? 13 : NH2 + !EFIRST, ks, 0, pause, [&](int i) {
            if (i >= vfrom) {
              if (i == 7) mbar_spin(sb + BAR_OWN + w * 8, hl >> 1);
              M.validate(true, &P.tm[TM_O16], 0, r * 128 + w * 64, wp, j, [] {});
            }
          }, w ? (ffn ? (PRE5 ? PRE5 : pause) : (PRE2 ? PRE2 : pause)) : (ffn ? 20 : IPRE), [&](int) { presum(pre, M.lane(), ffn ? 1.f : 0.f); own_rstd(w, wp, M.lane(), rstd); });
          M.end<128, false>(acn, 2, 0, 0, 0, t0 + 2);
          epi_res(acn, pre, ffn ? rstd[0] * rstd[0] : 1.f, ffn ? rstd[1] * rstd[1] : 1.f, xr, M, wp);
          PROF_T(w, t0 + 2, 2);
        }
      }
    }
  }
}

typedef CUresult (*EncFn)(CUtensorMap*, CUtensorMapDataType, cuuint32_t, void*, const cuuint64_t*, const cuuint64_t*, const cuuint32_t*,
                          const cuuint32_t*, CUtensorMapInterleave, CUtensorMapSwizzle, CUtensorMapL2promotion, CUtensorMapFloatOOBfill);

void enc2(EncFn enc, CUtensorMap* tm, const void* p, uint64_t cols, uint64_t rows, uint32_t boxrows = 64, CUtensorMapL2promotion promo = CU_TENSOR_MAP_L2_PROMOTION_L2_128B) {
  cuuint64_t gd[2] = {cols, rows}, gs[1] = {cols * 2};
  cuuint32_t box[2] = {64, boxrows}, es[2] = {1, 1};
  enc(tm, CU_TENSOR_MAP_DATA_TYPE_BFLOAT16, 2, const_cast<void*>(p), gd, gs, box, es, CU_TENSOR_MAP_INTERLEAVE_NONE, CU_TENSOR_MAP_SWIZZLE_128B,
      promo, CU_TENSOR_MAP_FLOAT_OOB_FILL_NONE);
}
void enc4(EncFn enc, CUtensorMap* tm, const void* p, uint64_t K, uint64_t N, uint64_t d2, uint64_t s2, uint64_t d3, uint64_t s3, uint32_t na) {
  cuuint64_t gd[4] = {64, K, d2, d3}, gs[3] = {N * 2, s2, s3};
  cuuint32_t box[4] = {64, 64, na, 1}, es[4] = {1, 1, 1, 1};
  enc(tm, CU_TENSOR_MAP_DATA_TYPE_BFLOAT16, 4, const_cast<void*>(p), gd, gs, box, es, CU_TENSOR_MAP_INTERLEAVE_NONE, CU_TENSOR_MAP_SWIZZLE_128B,
      WPROMO, CU_TENSOR_MAP_FLOAT_OOB_FILL_NONE);
}

}

extern "C" void kernel_launch(void* const* d_in, const int* in_sizes, int n_in, void* d_out, int out_size) {
  static EncFn enc = nullptr;
  static Scratch* ps = nullptr;
  static void (*kernel)(Ptrs, Params) = mega_kernel<true>;
  if (!enc) {
    cudaDriverEntryPointQueryResult qr;
    cudaGetDriverEntryPoint("cuTensorMapEncodeTiled", (void**)&enc, cudaEnableDefault, &qr);
    int dev = 0, nsm = 0;
    cudaGetDevice(&dev);
    cudaDeviceGetAttribute(&nsm, cudaDevAttrMultiProcessorCount, dev);
    if (nsm != NMAIN + NAUX) kernel = mega_kernel<false>;
    cudaFuncSetAttribute(kernel, cudaFuncAttributeMaxDynamicSharedMemorySize, SMEM_BYTES);
    cudaGetSymbolAddress((void**)&ps, g_s);
  }
  Params P;
  Ptrs Q;
  Q.s = ps;
  void *p_h = ps->h, *p_x = ps->x;
  enc2(enc, &P.tm[TM_XIN], d_in[0], 2048, 1024, 64, XPROMO);
  enc2(enc, &P.tm[TM_X], d_out, 2048, 1024);
  enc2(enc, &P.tm[TM_XA], p_x, 2048, 1024);
  enc2(enc, &P.tm[TM_O], p_h, 3584, 2048);
  enc2(enc, &P.tm[TM_H], p_h, 3584, 2048);
  enc2(enc, &P.tm[TM_X16], d_out, 2048, 1024, 16);
  enc2(enc, &P.tm[TM_XA16], p_x, 2048, 1024, 16);
  enc2(enc, &P.tm[TM_O16], p_h, 3584, 2048, 16);
  enc4(enc, &P.tm[TM_WQKV], d_in[1], 1024, 3072, 3, 2048, 16, 128, 3);
  enc4(enc, &P.tm[TM_WO], d_in[2], 1024, 1024, 16, 128, 1, 128, 2);
  enc4(enc, &P.tm[TM_W1A], d_in[4], 1024, 3584, 56, 128, 1, 128, 4);
  enc4(enc, &P.tm[TM_W1B], d_in[4], 1024, 3584, 56, 128, 1, 128, 3);
  enc4(enc, &P.tm[TM_W2], d_in[6], 3584, 1024, 16, 128, 1, 128, 2);
  Q.out = (__nv_bfloat16*)d_out;
  Q.b1 = (const __nv_bfloat16*)d_in[5];
  Q.b2 = (const __nv_bfloat16*)d_in[7];
  kernel<<<NMAIN + NAUX, NTHREADS, SMEM_BYTES, cudaStreamPerThread>>>(Q, P);
}
```

```cpp
#include <cuda_runtime.h>
#include <cuda_bf16.h>
#include <cuda.h>
#include <stdint.h>

#define LEAD0 2
#define LEAD1 1
#define LEAD2 3
#define LEAD3 1
#define LEAD4 1
#define LEAD5 4
#define WPROMO CU_TENSOR_MAP_L2_PROMOTION_L2_128B
#define PLAN1 0x40201008070000ull
#define PLAN0 0x4030020c8180ull
#define PLANZ 0x40300a050000ull
#define VSKIP 1
#define ELA 1
#define LSO 1
#define STATI 13
#define PACE2 0x1a
#define ST2 12
#define STB 3
#define PROBE 4
#define OWNP 0x22221110
#define SIG0 14
#define STGX 2
#define STGM 3
#define NPRO 4
#define XPROMO CU_TENSOR_MAP_L2_PROMOTION_L2_256B
#define IPRE 7
#define FILLT 1
#define EARLYC 1
#define OWNDLY 0
#define EPW 0
#define CPF 5000
#define STG0 800
#define STG1 500
#define STGL (STG0 + 4 * STG1)
#define STGLX 0
#define STARTC 0
#define PRE5 0
#define PRE2 0
#define FUN 4
#define XEF 0
#define BEF 0xff8
#define AEF 0xdb6
#define SEF 0
#define SDELAYO 1000
#define SDELAY 300
#define HDELAY 450
#define Q44 1
#define FG 8
#define TAR 0
#define RSV 0
#define NWB 0
#define AGK 1
#define NOI 1
#define EFIRST 1
#define AUGN 0
#define LEARLY 1
#define NPD 0
#define SDP 900
#define LATE2 0
#define ST2W 1
#define STA 1
#define PG (Q44 ? 32 : 16)
#define NH1 6
#define NH2 3
namespace {

constexpr int NMAIN = 128, NAUX = 4, NTHREADS = 384;
constexpr uint32_t OFF_B = 0;
constexpr uint32_t OFF_A = 131072;
constexpr uint32_t OFF_VEC = 229376;
constexpr uint32_t OFF_BAR = 231424;
constexpr uint32_t OFF_RSTD = OFF_VEC + 512, OFF_MEAN = OFF_VEC + 1088, OFF_HOLD = OFF_VEC + 2032;
constexpr uint32_t SMEM_BYTES = OFF_BAR + 960;
constexpr uint32_t BAR_FULLA = OFF_BAR, BAR_FULLB = OFF_BAR + 96, BAR_OWN = OFF_BAR + 160, BAR_EPOCH = OFF_BAR + 176, BAR_AUG = OFF_BAR + 184, BAR_SPEC = OFF_BAR + 192,
                   BAR_EMPTYA = OFF_BAR + 288, BAR_STG = OFF_BAR + 384, BAR_SRV = OFF_BAR + 400, BAR_LEAD = OFF_BAR + 432, BAR_HALO = OFF_BAR + 440, BAR_STG2 = OFF_BAR + 456,
                   BAR_DUMMY3 = OFF_BAR + 472, BAR_EMPTYB = OFF_BAR + 480, BAR_STAT = OFF_BAR + 544, BAR_DUMMY = OFF_BAR + 560;
constexpr int NA = 6;
constexpr uint32_t SB = 1024;
constexpr uint32_t SPIN_LIMIT = 1u << 22;

enum { TM_XIN = 0, TM_X, TM_XA, TM_O, TM_H, TM_WQKV, TM_WO, TM_W1A, TM_W1B, TM_W2, TM_X16, TM_XA16, TM_O16, TM_COUNT };

struct Scratch;
struct Ptrs {
  Scratch* s;
  __nv_bfloat16* out;
  const __nv_bfloat16* b1;
  const __nv_bfloat16* b2;
};
struct Params { CUtensorMap tm[TM_COUNT]; };

constexpr int NSTEP = 280, NSTEP_AUX = 128;
enum : uint32_t { F_STAMP = 1u << 28, F_GATH = 1u << 15, F_NEW = 1u << 16, F_AUG = 1u << 17, F_NOA = 1u << 18, E_HAND = 1u << 19, E_ATTN = 1u << 20, E_XPUB0 = 1u << 21,
                  E_WAIT = 1u << 22, E_REL = 1u << 23, E_KEEP = 1u << 24, E_PART1 = 1u << 25, E_HALO = 1u << 26,
                  E_SIG = 1u << 27, E_RARE = F_NEW | E_KEEP | (0xfu << 20) | (3u << 26) };
constexpr int own_round(int j) { return (OWNP >> (4 * j)) & 15; }
constexpr uint32_t first_order(int j) {
  uint32_t used = 0, v = 0;
  for (int p = 0; p < 8; p++) {
    int c = own_round(j) == p ? j : -1;
    for (int u = 0; u < 8 && c < 0; u++) if (u != j && !((used >> u) & 1) && own_round(u) < p) c = u;
    if (c < 0 && own_round(j ^ 1) == p) c = j ^ 1;
    for (int u = 0; u < 8 && c < 0; u++) { const int x = (u + (j & 6)) & 7; if (x != j && own_round(x) == p) c = x; }
    used |= 1u << c; v |= (uint32_t)c << (4 * p);
  }
  return v;
}
constexpr uint32_t first_round(int p) { uint32_t v = 0; for (int j = 0; j < 8; j++) v |= ((first_order(j) >> (4 * p)) & 15) << (4 * j); return v; }
constexpr uint32_t ROUND0 = first_round(0), ROUND1 = first_round(1);
struct Sched { uint32_t v[9][NSTEP + 8]; };
constexpr Sched make_sched() {
  Sched T{};
  for (int j = 0; j < 8; j++) {
    int owner[16] = {};
    for (int i = 0; i < 16; i++) owner[i] = -100;
    int p = 0, g = 0;
    for (int t = 0; t < 12; t++) {
      const int kind = t % 6, ks = kind == 5 ? 56 : (kind == 2 ? 16 : 17);
      for (int i = 0; i < ks; i++) {
        const bool augs = ks == 17 && i == 16;
        const int na = (kind == 2 || kind == 5) ? 2 : (augs ? 1 : (kind == 4 ? 4 : 3));
        if (i == 0) p = (0x20cc63 >> (4 * kind)) & 15;
        if (augs) p = (0x0f0af >> (4 * kind)) & 15;
        if (p + na > 16) p = 0;
        int need = g - 8;
        for (int a = p; a < p + na; a++) { if (owner[a] > need) need = owner[a]; owner[a] = g; }
        if (g == 16 && need < AUGN) need = AUGN;
        uint32_t k = i, f = i == (t ? 0 : NPRO) ? F_NEW | (1u << 29) : 0;
        if (augs) { k = 0; f |= F_AUG; }
        else if (kind == 0 || kind == 3) {
          const int o = i - 2;
          if (t == 0) k = ((first_order(j) >> (4 * (i >> 1))) & 15) * 2 + (i & 1);
          else if (i < 2) { k = 2 * j + i; f |= F_NOA | (i == 0 ? E_XPUB0 : 0); }
          else { const int half = o >= 7; int u = o - 7 * half; u += u >= j; k = 2 * u + half; if (i == 6) f |= E_REL; }
          if (i == 11) f |= E_HAND;
          if (i == (t ? 11 : SIG0)) f |= E_SIG;
        } else if (kind == 1 || kind == 4) {
          if (kind == 1) f |= i == 3 ? E_HAND : (i == 8 ? E_HAND | E_KEEP : (i == 5 ? E_HALO : 0));
          if (kind == 1) f |= i == 13 ? E_REL : 0;
          else if (i == 4 || i == 7 || i == 10) f |= E_HAND;
        } else if (kind == 2) {
          f |= i == 0 ? E_WAIT : (i == 3 ? E_HAND : (i == 5 ? E_HALO : 0));
          if (i == 8) { k = 8 + j; f |= E_ATTN | E_KEEP | F_NOA; }
          if (i > 8) k = i - 1 + (i - 9 >= j);
          if (i == 11) f |= E_REL;
        } else {
          k = i < 24 ? (i / 3) * 7 + i % 3 : ((i - 24) / 4) * 7 + 3 + (i - 24) % 4;
          if (i == 4 || i == 7 || i == 10 || i == 13) f |= E_HAND;
          f |= i == 0 ? E_WAIT : (i == 24 ? E_WAIT | E_PART1 : 0);
        }
        if ((kind == 2 || kind == 5) && t < 11 && i == ks - (kind == 2 ? STA : STB)) f |= F_STAMP;
        if (((PACE2 >> kind) & 1) && i == ST2) f |= F_STAMP;
        if (i == 0 && t && ((PACE2 >> ((t - 1) % 6)) & 1)) f |= F_GATH;
        T.v[j][g] = p | ((g - need) << 5) | (k << 9) | f;
        p += na; g++;
      }
    }
    T.v[j][NSTEP] = F_NEW | F_NOA | E_XPUB0 | (2 * j << 9);
  }
  for (int w = 0; w < 2; w++) {
    int owner[14] = {};
    for (int i = 0; i < 14; i++) owner[i] = -100;
    for (int g = w, p = 0; g < NSTEP_AUX; g += 2) {
      const int na = g < 96 ? 3 : 4;
      if (p + na > 14) p = 0;
      int need = g - 8;
      for (int a = p; a < p + na; a++) { if (owner[a] > need) need = owner[a]; owner[a] = g; }
      T.v[8][g] = (p + 14 * w) | ((g - need) << 5) | ((g & 31) >> 1 << 9) | ((g & 30) && g - w != 8 ? 0 : F_NEW | (g - w == 64 ? 2u : 1u) << 29);
      p += na;
    }
  }
  return T;
}
__constant__ Sched c_sched = make_sched();
__device__ __forceinline__ int sched_k(uint32_t e) { return (e >> 3) & 0xfc0; }

struct Scratch {
  __nv_bfloat16 x[2048 * 1024];
  __nv_bfloat16 h[2048 * 3584];
  uint32_t epoch[160];
  uint8_t flags[16][2][64];
  uint32_t pace[8][64];
  uint32_t aug[2][32][1024];
  uint4 stats[4][512][8][2];
  uint4 halo[4][256][136];
};
__device__ __align__(1024) Scratch g_s;
#define PROF_T(w, t, i)
#define PRO(i)
#define LT(i)
#define CT(n)
#define ST(i)
#define AP(i)

__device__ __forceinline__ int work_id() {
  uint32_t smid;
  asm volatile("mov.u32 %0, %%smid;" : "=r"(smid));
  const int t = smid >> 1, u = t - 32, d = (u * 37) >> 8;
  int id = (t & 7) * 16 + (t >> 3) * 2;
  if (t >= 32) id = (1 + u - 7 * d) * 16 + (4 + d) * 2;
  if (t >= 60) id = t < 62 ? t * 2 + 8 : t * 2 - 116;
  return id + (smid & 1);
}

__device__ __forceinline__ uint32_t smem_u32(const void* p) { return (uint32_t)__cvta_generic_to_shared(p); }
__device__ __forceinline__ void mbar_init(uint32_t bar, int cnt) { asm volatile("mbarrier.init.shared::cta.b64 [%0], %1;" ::"r"(bar), "r"(cnt)); }
__device__ __forceinline__ void mbar_expect_tx(uint32_t bar, uint32_t bytes) { asm volatile("mbarrier.arrive.expect_tx.shared::cta.b64 _, [%0], %1;" ::"r"(bar), "r"(bytes) : "memory"); }
__device__ __forceinline__ void mbar_arrive(uint32_t bar, uint32_t cnt) { asm volatile("mbarrier.arrive.shared::cta.b64 _, [%0], %1;" ::"r"(bar), "r"(cnt) : "memory"); }
__device__ __forceinline__ void arrive_n(uint32_t bar, bool) { asm volatile("{\n.reg .pred p;\nelect.sync _|p, 0xffffffff;\n@p mbarrier.arrive.shared::cta.b64 _, [%0];\n}" ::"r"(bar) : "memory"); }
__device__ __forceinline__ void arrive_2(uint32_t b0, uint32_t b1, bool) {
  asm volatile("{\n.reg .pred p;\nelect.sync _|p, 0xffffffff;\n@p mbarrier.arrive.shared::cta.b64 _, [%0];\n@p mbarrier.arrive.shared::cta.b64 _, [%1];\n}" ::"r"(b0), "r"(b1) : "memory");
}
__device__ __forceinline__ void mbar_wait(uint32_t bar, uint32_t parity) {
  asm volatile(
      "{\n.reg .pred p;\n.reg .u32 c;\nmov.u32 c, 0;\n"
      "LAB_WAIT:\nmbarrier.try_wait.parity.shared::cta.b64 p, [%0], %1;\n@p bra.uni DONE;\n"
      "add.u32 c, c, 1;\nsetp.lt.u32 p, c, 4000000;\n@p bra.uni LAB_WAIT;\ntrap;\nDONE:\n}" ::"r"(bar), "r"(parity) : "memory");
}
__device__ __forceinline__ void mbar_spin(uint32_t bar, uint32_t parity) {
  asm volatile("{\n.reg .pred p;\nLAB_WAIT:\nmbarrier.try_wait.parity.shared::cta.b64 p, [%0], %1;\n@!p pmevent 7;\n@!p bra.uni LAB_WAIT;\n}" ::"r"(bar), "r"(parity) : "memory");
}
__device__ __forceinline__ void mbar_spin31(uint32_t bar, uint32_t ph) {
  asm volatile("{\n.reg .pred p;\n.reg .b64 s;\nmov.b64 s, {%1, %1};\nLAB_WAIT:\nmbarrier.try_wait.shared::cta.b64 p, [%0], s;\n@!p pmevent 7;\n@!p bra.uni LAB_WAIT;\n}" ::"r"(bar), "r"(ph) : "memory");
}
__device__ __forceinline__ bool elect_one() {
  uint32_t p;
  asm volatile("{\n.reg .pred P;\nelect.sync _|P, 0xffffffff;\nselp.u32 %0, 1, 0, P;\n}" : "=r"(p));
  return p != 0;
}
__device__ __forceinline__ bool mbar_test(uint32_t bar, uint32_t parity) {
  uint32_t ok;
  asm volatile("{\n.reg .pred p;\nmbarrier.test_wait.parity.shared::cta.b64 p, [%1], %2;\nselp.u32 %0, 1, 0, p;\n}" : "=r"(ok) : "r"(bar), "r"(parity) : "memory");
  return ok != 0;
}
__device__ __forceinline__ void tma_ld2(uint32_t dst, const CUtensorMap* tm, int c0, int c1, uint32_t bar) {
  asm volatile("cp.async.bulk.tensor.2d.shared::cluster.global.mbarrier::complete_tx::bytes [%0], [%1, {%3, %4}], [%2];" ::"r"(dst), "l"(tm), "r"(bar), "r"(c0), "r"(c1) : "memory");
}
__device__ __forceinline__ void tma_ld4(uint32_t dst, const CUtensorMap* tm, int c1, int c2, int c3, uint32_t bar, uint64_t pol = 0x1000000000000000ull) {
  asm volatile("cp.async.bulk.tensor.4d.shared::cluster.global.mbarrier::complete_tx::bytes.L2::cache_hint [%0], [%1, {%3, %4, %5, %6}], [%2], %7;" ::"r"(dst), "l"(tm), "r"(bar), "r"(0), "r"(c1), "r"(c2), "r"(c3), "l"(pol) : "memory");
}
__device__ __forceinline__ void tma_st2(const CUtensorMap* tm, int c0, int c1, uint32_t src) {
  asm volatile("cp.async.bulk.tensor.2d.global.shared::cta.bulk_group [%0, {%2, %3}], [%1];" ::"l"(tm), "r"(src), "r"(c0), "r"(c1) : "memory");
}
__device__ __forceinline__ void bulk_ld(uint32_t dst, const void* src, uint32_t bytes, uint32_t bar) {
  asm volatile("cp.async.bulk.shared::cluster.global.mbarrier::complete_tx::bytes [%0], [%1], %2, [%3];" ::"r"(dst), "l"(src), "r"(bytes), "r"(bar) : "memory");
}
__device__ __forceinline__ void e_arrive(uint32_t bar, uint32_t cnt) {
  if (cnt == 1) asm volatile("{\n.reg .pred p;\nelect.sync _|p, 0xffffffff;\n@p mbarrier.arrive.shared::cta.b64 _, [%0];\n}" ::"r"(bar) : "memory");
  else asm volatile("{\n.reg .pred p;\nelect.sync _|p, 0xffffffff;\n@p mbarrier.arrive.shared::cta.b64 _, [%0], %1;\n}" ::"r"(bar), "r"(cnt) : "memory");
}
template <int BYTES = 8192> __device__ __forceinline__ void e_load(uint32_t dst, const CUtensorMap* tm, int c0, int c1, uint32_t bar, uint64_t pol = 0x1000000000000000ull) {
  asm volatile("{\n.reg .pred p;\nelect.sync _|p, 0xffffffff;\n@p mbarrier.arrive.expect_tx.shared::cta.b64 _, [%2], %5;\n"
               "@p cp.async.bulk.tensor.2d.shared::cluster.global.mbarrier::complete_tx::bytes.L2::cache_hint [%0], [%1, {%3, %4}], [%2], %6;\n}"
               ::"r"(dst), "l"(tm), "r"(bar), "r"(c0), "r"(c1), "n"(BYTES), "l"(pol) : "memory");
}
__device__ __forceinline__ void e_store(const CUtensorMap* tm, int c0, int c1, uint32_t src) {
  asm volatile("{\n.reg .pred p;\nfence.proxy.async.shared::cta;\nelect.sync _|p, 0xffffffff;\n"
               "@p cp.async.bulk.tensor.2d.global.shared::cta.bulk_group [%0, {%2, %3}], [%1];\ncp.async.bulk.commit_group;\n}"
               ::"l"(tm), "r"(src), "r"(c0), "r"(c1) : "memory");
}
__device__ __forceinline__ void bulk_commit() { asm volatile("cp.async.bulk.commit_group;" ::: "memory"); }
template <int N> __device__ __forceinline__ void bulk_wait_read() { asm volatile("cp.async.bulk.wait_group.read %0;" ::"n"(N) : "memory"); }
__device__ __forceinline__ void bulk_wait_all() { asm volatile("cp.async.bulk.wait_group 0;" ::: "memory"); }
__device__ __forceinline__ void fence_async_smem() { asm volatile("fence.proxy.async.shared::cta;" ::: "memory"); }
__device__ __forceinline__ void wg_fence() { asm volatile("wgmma.fence.sync.aligned;" ::: "memory"); }
__device__ __forceinline__ void wg_commit() { asm volatile("wgmma.commit_group.sync.aligned;" ::: "memory"); }
template <int N> __device__ __forceinline__ void wg_wait() { asm volatile("wgmma.wait_group.sync.aligned %0;" ::"n"(N) : "memory"); }
__device__ __forceinline__ void wg_bar(int w) { asm volatile("bar.sync %0, 128;" ::"r"(w + 1) : "memory"); }
__device__ __forceinline__ uint32_t ld_acquire(const uint32_t* p) { uint32_t v; asm volatile("ld.acquire.gpu.global.u32 %0, [%1];" : "=r"(v) : "l"(p) : "memory"); return v; }
__device__ __forceinline__ uint4 ld_relaxed4(const uint32_t* p) {
  uint4 v; asm volatile("ld.relaxed.gpu.global.v4.u32 {%0,%1,%2,%3}, [%4];" : "=r"(v.x), "=r"(v.y), "=r"(v.z), "=r"(v.w) : "l"(p) : "memory"); return v;
}
__device__ __forceinline__ void st_release8(uint8_t* p, uint32_t v) { asm volatile("st.release.gpu.global.u8 [%0], %1;" ::"l"(p), "r"(v) : "memory"); }
__device__ __forceinline__ uint32_t ld_relaxed(const uint32_t* p) { uint32_t v; asm volatile("ld.relaxed.gpu.global.u32 %0, [%1];" : "=r"(v) : "l"(p) : "memory"); return v; }
__device__ __forceinline__ void st_release(uint32_t* p, uint32_t v) { asm volatile("st.release.gpu.global.u32 [%0], %1;" ::"l"(p), "r"(v) : "memory"); }
__device__ __forceinline__ void st_pkt(uint4* p, uint32_t a, uint32_t b, uint32_t c, uint32_t d) {
  asm volatile("{\n.reg .b64 lo, hi;\n.reg .b128 v;\nmov.b64 lo, {%1, %2};\nmov.b64 hi, {%3, %4};\nmov.b128 v, {lo, hi};\nst.relaxed.gpu.global.b128 [%0], v;\n}" ::"l"(p), "r"(a), "r"(b), "r"(c), "r"(d) : "memory");
}
__device__ __forceinline__ uint4 ld_pkt(const uint4* p) {
  uint4 r;
  asm volatile("{\n.reg .b64 lo, hi;\n.reg .b128 v;\nld.relaxed.gpu.global.b128 v, [%4];\nmov.b128 {lo, hi}, v;\nmov.b64 {%0, %1}, lo;\nmov.b64 {%2, %3}, hi;\n}" : "=r"(r.x), "=r"(r.y), "=r"(r.z), "=r"(r.w) : "l"(p) : "memory");
  return r;
}
__device__ __forceinline__ uint32_t pack_bf16(float lo, float hi) { uint32_t d; asm("cvt.rn.bf16x2.f32 %0, %1, %2;" : "=r"(d) : "f"(hi), "f"(lo)); return d; }
__device__ __forceinline__ float ex2(float x) { float y; asm("ex2.approx.ftz.f32 %0, %1;" : "=f"(y) : "f"(x)); return y; }
__device__ __forceinline__ float rsq(float x) { float y; asm("rsqrt.approx.ftz.f32 %0, %1;" : "=f"(y) : "f"(x)); return y; }
__device__ __forceinline__ float rcp(float x) { float y; asm("rcp.approx.ftz.f32 %0, %1;" : "=f"(y) : "f"(x)); return y; }
__device__ __forceinline__ float bf_lo(uint32_t v) { return __uint_as_float(v << 16); }
__device__ __forceinline__ float bf_hi(uint32_t v) { return __uint_as_float(v & 0xffff0000u); }
__device__ __forceinline__ void stsm4(uint32_t addr, uint32_t a, uint32_t b, uint32_t c, uint32_t d) {
  asm volatile("stmatrix.sync.aligned.m8n8.x4.shared.b16 [%0], {%1, %2, %3, %4};" ::"r"(addr), "r"(a), "r"(b), "r"(c), "r"(d) : "memory");
}
__device__ __forceinline__ uint32_t movm(uint32_t a) { uint32_t d; asm volatile("movmatrix.sync.aligned.m8n8.trans.b16 %0, %1;" : "=r"(d) : "r"(a)); return d; }
__device__ __forceinline__ void mma16(float (&c)[4], uint32_t a0, uint32_t a1, uint32_t a2, uint32_t a3, uint32_t b0, uint32_t b1) {
  asm volatile("mma.sync.aligned.m16n8k16.row.col.f32.bf16.bf16.f32 {%0,%1,%2,%3}, {%4,%5,%6,%7}, {%8,%9}, {%0,%1,%2,%3};"
               : "+f"(c[0]), "+f"(c[1]), "+f"(c[2]), "+f"(c[3]) : "r"(a0), "r"(a1), "r"(a2), "r"(a3), "r"(b0), "r"(b1));
}
__device__ __forceinline__ void mma8(float (&c)[4], uint32_t a0, uint32_t a1, uint32_t b0) {
  asm volatile("mma.sync.aligned.m16n8k8.row.col.f32.bf16.bf16.f32 {%0,%1,%2,%3}, {%4,%5}, {%6}, {%0,%1,%2,%3};"
               : "+f"(c[0]), "+f"(c[1]), "+f"(c[2]), "+f"(c[3]) : "r"(a0), "r"(a1), "r"(b0));
}
__device__ __forceinline__ void sts128(uint32_t a, uint32_t x, uint32_t y, uint32_t z, uint32_t w) {
  asm volatile("st.shared.v4.b32 [%0], {%1,%2,%3,%4};" ::"r"(a), "r"(x), "r"(y), "r"(z), "r"(w) : "memory");
}
__device__ __forceinline__ float2 lds64(uint32_t a) { float2 v; asm volatile("ld.shared.v2.f32 {%0,%1}, [%2];" : "=f"(v.x), "=f"(v.y) : "r"(a)); return v; }
__device__ __forceinline__ float4 lds128(uint32_t a) { float4 v; asm volatile("ld.shared.v4.f32 {%0,%1,%2,%3}, [%4];" : "=f"(v.x), "=f"(v.y), "=f"(v.z), "=f"(v.w) : "r"(a)); return v; }
__device__ __forceinline__ uint32_t lds32(uint32_t a) { uint32_t v; asm volatile("ld.shared.b32 %0, [%1];" : "=r"(v) : "r"(a)); return v; }
template <int S> __device__ __forceinline__ void wgmma_first128(float (&d)[S], uint32_t da, uint32_t db, uint32_t h0, uint32_t h1) {
  asm volatile("{\n.reg .b64 a, b, s;\n.reg .b32 t, u;\n.reg .pred p, q;\nwgmma.fence.sync.aligned;\n"
    "add.u32 t, %64, 0;\nadd.u32 u, %65, 0;\nmov.b64 a, {t, %66};\nmov.b64 b, {u, %67};\n"
    "wgmma.mma_async.sync.aligned.m64n128k16.f32.bf16.bf16 "
    "{%0, %1, %2, %3, %4, %5, %6, %7, %8, %9, %10, %11, %12, %13, %14, %15, %16, %17, %18, %19, %20, %21, %22, %23, %24, %25, %26, %27, %28, %29, %30, %31, %32, %33, %34, %35, %36, %37, %38, %39, %40, %41, %42, %43, %44, %45, %46, %47, %48, %49, %50, %51, %52, %53, %54, %55, %56, %57, %58, %59, %60, %61, %62, %63}, "
    "a, b, 0, 1, 1, 0, 1;\n"
    "add.u32 t, %64, 2;\nadd.u32 u, %65, 128;\nmov.b64 a, {t, %66};\nmov.b64 b, {u, %67};\n"
    "wgmma.mma_async.sync.aligned.m64n128k16.f32.bf16.bf16 "
    "{%0, %1, %2, %3, %4, %5, %6, %7, %8, %9, %10, %11, %12, %13, %14, %15, %16, %17, %18, %19, %20, %21, %22, %23, %24, %25, %26, %27, %28, %29, %30, %31, %32, %33, %34, %35, %36, %37, %38, %39, %40, %41, %42, %43, %44, %45, %46, %47, %48, %49, %50, %51, %52, %53, %54, %55, %56, %57, %58, %59, %60, %61, %62, %63}, "
    "a, b, 1, 1, 1, 0, 1;\n"
    "add.u32 t, %64, 4;\nadd.u32 u, %65, 256;\nmov.b64 a, {t, %66};\nmov.b64 b, {u, %67};\n"
    "wgmma.mma_async.sync.aligned.m64n128k16.f32.bf16.bf16 "
    "{%0, %1, %2, %3, %4, %5, %6, %7, %8, %9, %10, %11, %12, %13, %14, %15, %16, %17, %18, %19, %20, %21, %22, %23, %24, %25, %26, %27, %28, %29, %30, %31, %32, %33, %34, %35, %36, %37, %38, %39, %40, %41, %42, %43, %44, %45, %46, %47, %48, %49, %50, %51, %52, %53, %54, %55, %56, %57, %58, %59, %60, %61, %62, %63}, "
    "a, b, 1, 1, 1, 0, 1;\n"
    "add.u32 t, %64, 6;\nadd.u32 u, %65, 384;\nmov.b64 a, {t, %66};\nmov.b64 b, {u, %67};\n"
    "wgmma.mma_async.sync.aligned.m64n128k16.f32.bf16.bf16 "
    "{%0, %1, %2, %3, %4, %5, %6, %7, %8, %9, %10, %11, %12, %13, %14, %15, %16, %17, %18, %19, %20, %21, %22, %23, %24, %25, %26, %27, %28, %29, %30, %31, %32, %33, %34, %35, %36, %37, %38, %39, %40, %41, %42, %43, %44, %45, %46, %47, %48, %49, %50, %51, %52, %53, %54, %55, %56, %57, %58, %59, %60, %61, %62, %63}, "
    "a, b, 1, 1, 1, 0, 1;\n"
    "wgmma.commit_group.sync.aligned;\n}"
    : "=f"(d[0]), "=f"(d[1]), "=f"(d[2]), "=f"(d[3]), "=f"(d[4]), "=f"(d[5]), "=f"(d[6]), "=f"(d[7]), "=f"(d[8]), "=f"(d[9]), "=f"(d[10]), "=f"(d[11]), "=f"(d[12]), "=f"(d[13]), "=f"(d[14]), "=f"(d[15]), "=f"(d[16]), "=f"(d[17]), "=f"(d[18]), "=f"(d[19]), "=f"(d[20]), "=f"(d[21]), "=f"(d[22]), "=f"(d[23]), "=f"(d[24]), "=f"(d[25]), "=f"(d[26]), "=f"(d[27]), "=f"(d[28]), "=f"(d[29]), "=f"(d[30]), "=f"(d[31]), "=f"(d[32]), "=f"(d[33]), "=f"(d[34]), "=f"(d[35]), "=f"(d[36]), "=f"(d[37]), "=f"(d[38]), "=f"(d[39]), "=f"(d[40]), "=f"(d[41]), "=f"(d[42]), "=f"(d[43]), "=f"(d[44]), "=f"(d[45]), "=f"(d[46]), "=f"(d[47]), "=f"(d[48]), "=f"(d[49]), "=f"(d[50]), "=f"(d[51]), "=f"(d[52]), "=f"(d[53]), "=f"(d[54]), "=f"(d[55]), "=f"(d[56]), "=f"(d[57]), "=f"(d[58]), "=f"(d[59]), "=f"(d[60]), "=f"(d[61]), "=f"(d[62]), "=f"(d[63])
    : "r"(da), "r"(db), "r"(h0), "r"(h1) : "memory");
}
template <int S> __device__ __forceinline__ uint2 wgmma_probe128(float (&d)[S], uint32_t da, uint32_t db, uint32_t h0, uint32_t h1, uint32_t b0, uint32_t p0, uint32_t b1, uint32_t p1) {
  uint2 ok;
  asm volatile("{\n.reg .b64 a, b, s;\n.reg .b32 t, u;\n.reg .pred p, q;\nwgmma.fence.sync.aligned;\n"
    "add.u32 t, %66, 0;\nadd.u32 u, %67, 0;\nmov.b64 a, {t, %68};\nmov.b64 b, {u, %69};\n"
    "wgmma.mma_async.sync.aligned.m64n128k16.f32.bf16.bf16 "
    "{%2, %3, %4, %5, %6, %7, %8, %9, %10, %11, %12, %13, %14, %15, %16, %17, %18, %19, %20, %21, %22, %23, %24, %25, %26, %27, %28, %29, %30, %31, %32, %33, %34, %35, %36, %37, %38, %39, %40, %41, %42, %43, %44, %45, %46, %47, %48, %49, %50, %51, %52, %53, %54, %55, %56, %57, %58, %59, %60, %61, %62, %63, %64, %65}, "
    "a, b, 1, 1, 1, 0, 1;\n"
    "add.u32 t, %66, 2;\nadd.u32 u, %67, 128;\nmov.b64 a, {t, %68};\nmov.b64 b, {u, %69};\n"
    "wgmma.mma_async.sync.aligned.m64n128k16.f32.bf16.bf16 "
    "{%2, %3, %4, %5, %6, %7, %8, %9, %10, %11, %12, %13, %14, %15, %16, %17, %18, %19, %20, %21, %22, %23, %24, %25, %26, %27, %28, %29, %30, %31, %32, %33, %34, %35, %36, %37, %38, %39, %40, %41, %42, %43, %44, %45, %46, %47, %48, %49, %50, %51, %52, %53, %54, %55, %56, %57, %58, %59, %60, %61, %62, %63, %64, %65}, "
    "a, b, 1, 1, 1, 0, 1;\n"
    "mov.b64 s, {%71, %71};\nmbarrier.test_wait.shared::cta.b64 p, [%70], s;\nmov.b64 s, {%73, %73};\nmbarrier.test_wait.shared::cta.b64 q, [%72], s;\n"
    "add.u32 t, %66, 4;\nadd.u32 u, %67, 256;\nmov.b64 a, {t, %68};\nmov.b64 b, {u, %69};\n"
    "wgmma.mma_async.sync.aligned.m64n128k16.f32.bf16.bf16 "
    "{%2, %3, %4, %5, %6, %7, %8, %9, %10, %11, %12, %13, %14, %15, %16, %17, %18, %19, %20, %21, %22, %23, %24, %25, %26, %27, %28, %29, %30, %31, %32, %33, %34, %35, %36, %37, %38, %39, %40, %41, %42, %43, %44, %45, %46, %47, %48, %49, %50, %51, %52, %53, %54, %55, %56, %57, %58, %59, %60, %61, %62, %63, %64, %65}, "
    "a, b, 1, 1, 1, 0, 1;\n"
    "add.u32 t, %66, 6;\nadd.u32 u, %67, 384;\nmov.b64 a, {t, %68};\nmov.b64 b, {u, %69};\n"
    "wgmma.mma_async.sync.aligned.m64n128k16.f32.bf16.bf16 "
    "{%2, %3, %4, %5, %6, %7, %8, %9, %10, %11, %12, %13, %14, %15, %16, %17, %18, %19, %20, %21, %22, %23, %24, %25, %26, %27, %28, %29, %30, %31, %32, %33, %34, %35, %36, %37, %38, %39, %40, %41, %42, %43, %44, %45, %46, %47, %48, %49, %50, %51, %52, %53, %54, %55, %56, %57, %58, %59, %60, %61, %62, %63, %64, %65}, "
    "a, b, 1, 1, 1, 0, 1;\n"
    "wgmma.commit_group.sync.aligned;\nselp.u32 %0, 1, 0, p;\nselp.u32 %1, 1, 0, q;\n}"
    : "=r"(ok.x), "=r"(ok.y), "+f"(d[0]), "+f"(d[1]), "+f"(d[2]), "+f"(d[3]), "+f"(d[4]), "+f"(d[5]), "+f"(d[6]), "+f"(d[7]), "+f"(d[8]), "+f"(d[9]), "+f"(d[10]), "+f"(d[11]), "+f"(d[12]), "+f"(d[13]), "+f"(d[14]), "+f"(d[15]), "+f"(d[16]), "+f"(d[17]), "+f"(d[18]), "+f"(d[19]), "+f"(d[20]), "+f"(d[21]), "+f"(d[22]), "+f"(d[23]), "+f"(d[24]), "+f"(d[25]), "+f"(d[26]), "+f"(d[27]), "+f"(d[28]), "+f"(d[29]), "+f"(d[30]), "+f"(d[31]), "+f"(d[32]), "+f"(d[33]), "+f"(d[34]), "+f"(d[35]), "+f"(d[36]), "+f"(d[37]), "+f"(d[38]), "+f"(d[39]), "+f"(d[40]), "+f"(d[41]), "+f"(d[42]), "+f"(d[43]), "+f"(d[44]), "+f"(d[45]), "+f"(d[46]), "+f"(d[47]), "+f"(d[48]), "+f"(d[49]), "+f"(d[50]), "+f"(d[51]), "+f"(d[52]), "+f"(d[53]), "+f"(d[54]), "+f"(d[55]), "+f"(d[56]), "+f"(d[57]), "+f"(d[58]), "+f"(d[59]), "+f"(d[60]), "+f"(d[61]), "+f"(d[62]), "+f"(d[63])
    : "r"(da), "r"(db), "r"(h0), "r"(h1), "r"(b0), "r"(p0), "r"(b1), "r"(p1) : "memory");
  return ok;
}
template <int S> __device__ __forceinline__ void wgmma_first192(float (&d)[S], uint32_t da, uint32_t db, uint32_t h0, uint32_t h1) {
  asm volatile("{\n.reg .b64 a, b, s;\n.reg .b32 t, u;\n.reg .pred p, q;\nwgmma.fence.sync.aligned;\n"
    "add.u32 t, %96, 0;\nadd.u32 u, %97, 0;\nmov.b64 a, {t, %98};\nmov.b64 b, {u, %99};\n"
    "wgmma.mma_async.sync.aligned.m64n192k16.f32.bf16.bf16 "
    "{%0, %1, %2, %3, %4, %5, %6, %7, %8, %9, %10, %11, %12, %13, %14, %15, %16, %17, %18, %19, %20, %21, %22, %23, %24, %25, %26, %27, %28, %29, %30, %31, %32, %33, %34, %35, %36, %37, %38, %39, %40, %41, %42, %43, %44, %45, %46, %47, %48, %49, %50, %51, %52, %53, %54, %55, %56, %57, %58, %59, %60, %61, %62, %63, %64, %65, %66, %67, %68, %69, %70, %71, %72, %73, %74, %75, %76, %77, %78, %79, %80, %81, %82, %83, %84, %85, %86, %87, %88, %89, %90, %91, %92, %93, %94, %95}, "
    "a, b, 0, 1, 1, 0, 1;\n"
    "add.u32 t, %96, 2;\nadd.u32 u, %97, 128;\nmov.b64 a, {t, %98};\nmov.b64 b, {u, %99};\n"
    "wgmma.mma_async.sync.aligned.m64n192k16.f32.bf16.bf16 "
    "{%0, %1, %2, %3, %4, %5, %6, %7, %8, %9, %10, %11, %12, %13, %14, %15, %16, %17, %18, %19, %20, %21, %22, %23, %24, %25, %26, %27, %28, %29, %30, %31, %32, %33, %34, %35, %36, %37, %38, %39, %40, %41, %42, %43, %44, %45, %46, %47, %48, %49, %50, %51, %52, %53, %54, %55, %56, %57, %58, %59, %60, %61, %62, %63, %64, %65, %66, %67, %68, %69, %70, %71, %72, %73, %74, %75, %76, %77, %78, %79, %80, %81, %82, %83, %84, %85, %86, %87, %88, %89, %90, %91, %92, %93, %94, %95}, "
    "a, b, 1, 1, 1, 0, 1;\n"
    "add.u32 t, %96, 4;\nadd.u32 u, %97, 256;\nmov.b64 a, {t, %98};\nmov.b64 b, {u, %99};\n"
    "wgmma.mma_async.sync.aligned.m64n192k16.f32.bf16.bf16 "
    "{%0, %1, %2, %3, %4, %5, %6, %7, %8, %9, %10, %11, %12, %13, %14, %15, %16, %17, %18, %19, %20, %21, %22, %23, %24, %25, %26, %27, %28, %29, %30, %31, %32, %33, %34, %35, %36, %37, %38, %39, %40, %41, %42, %43, %44, %45, %46, %47, %48, %49, %50, %51, %52, %53, %54, %55, %56, %57, %58, %59, %60, %61, %62, %63, %64, %65, %66, %67, %68, %69, %70, %71, %72, %73, %74, %75, %76, %77, %78, %79, %80, %81, %82, %83, %84, %85, %86, %87, %88, %89, %90, %91, %92, %93, %94, %95}, "
    "a, b, 1, 1, 1, 0, 1;\n"
    "add.u32 t, %96, 6;\nadd.u32 u, %97, 384;\nmov.b64 a, {t, %98};\nmov.b64 b, {u, %99};\n"
    "wgmma.mma_async.sync.aligned.m64n192k16.f32.bf16.bf16 "
    "{%0, %1, %2, %3, %4, %5, %6, %7, %8, %9, %10, %11, %12, %13, %14, %15, %16, %17, %18, %19, %20, %21, %22, %23, %24, %25, %26, %27, %28, %29, %30, %31, %32, %33, %34, %35, %36, %37, %38, %39, %40, %41, %42, %43, %44, %45, %46, %47, %48, %49, %50, %51, %52, %53, %54, %55, %56, %57, %58, %59, %60, %61, %62, %63, %64, %65, %66, %67, %68, %69, %70, %71, %72, %73, %74, %75, %76, %77, %78, %79, %80, %81, %82, %83, %84, %85, %86, %87, %88, %89, %90, %91, %92, %93, %94, %95}, "
    "a, b, 1, 1, 1, 0, 1;\n"
    "wgmma.commit_group.sync.aligned;\n}"
    : "=f"(d[0]), "=f"(d[1]), "=f"(d[2]), "=f"(d[3]), "=f"(d[4]), "=f"(d[5]), "=f"(d[6]), "=f"(d[7]), "=f"(d[8]), "=f"(d[9]), "=f"(d[10]), "=f"(d[11]), "=f"(d[12]), "=f"(d[13]), "=f"(d[14]), "=f"(d[15]), "=f"(d[16]), "=f"(d[17]), "=f"(d[18]), "=f"(d[19]), "=f"(d[20]), "=f"(d[21]), "=f"(d[22]), "=f"(d[23]), "=f"(d[24]), "=f"(d[25]), "=f"(d[26]), "=f"(d[27]), "=f"(d[28]), "=f"(d[29]), "=f"(d[30]), "=f"(d[31]), "=f"(d[32]), "=f"(d[33]), "=f"(d[34]), "=f"(d[35]), "=f"(d[36]), "=f"(d[37]), "=f"(d[38]), "=f"(d[39]), "=f"(d[40]), "=f"(d[41]), "=f"(d[42]), "=f"(d[43]), "=f"(d[44]), "=f"(d[45]), "=f"(d[46]), "=f"(d[47]), "=f"(d[48]), "=f"(d[49]), "=f"(d[50]), "=f"(d[51]), "=f"(d[52]), "=f"(d[53]), "=f"(d[54]), "=f"(d[55]), "=f"(d[56]), "=f"(d[57]), "=f"(d[58]), "=f"(d[59]), "=f"(d[60]), "=f"(d[61]), "=f"(d[62]), "=f"(d[63]), "=f"(d[64]), "=f"(d[65]), "=f"(d[66]), "=f"(d[67]), "=f"(d[68]), "=f"(d[69]), "=f"(d[70]), "=f"(d[71]), "=f"(d[72]), "=f"(d[73]), "=f"(d[74]), "=f"(d[75]), "=f"(d[76]), "=f"(d[77]), "=f"(d[78]), "=f"(d[79]), "=f"(d[80]), "=f"(d[81]), "=f"(d[82]), "=f"(d[83]), "=f"(d[84]), "=f"(d[85]), "=f"(d[86]), "=f"(d[87]), "=f"(d[88]), "=f"(d[89]), "=f"(d[90]), "=f"(d[91]), "=f"(d[92]), "=f"(d[93]), "=f"(d[94]), "=f"(d[95])
    : "r"(da), "r"(db), "r"(h0), "r"(h1) : "memory");
}
template <int S> __device__ __forceinline__ uint2 wgmma_probe192(float (&d)[S], uint32_t da, uint32_t db, uint32_t h0, uint32_t h1, uint32_t b0, uint32_t p0, uint32_t b1, uint32_t p1) {
  uint2 ok;
  asm volatile("{\n.reg .b64 a, b, s;\n.reg .b32 t, u;\n.reg .pred p, q;\nwgmma.fence.sync.aligned;\n"
    "add.u32 t, %98, 0;\nadd.u32 u, %99, 0;\nmov.b64 a, {t, %100};\nmov.b64 b, {u, %101};\n"
    "wgmma.mma_async.sync.aligned.m64n192k16.f32.bf16.bf16 "
    "{%2, %3, %4, %5, %6, %7, %8, %9, %10, %11, %12, %13, %14, %15, %16, %17, %18, %19, %20, %21, %22, %23, %24, %25, %26, %27, %28, %29, %30, %31, %32, %33, %34, %35, %36, %37, %38, %39, %40, %41, %42, %43, %44, %45, %46, %47, %48, %49, %50, %51, %52, %53, %54, %55, %56, %57, %58, %59, %60, %61, %62, %63, %64, %65, %66, %67, %68, %69, %70, %71, %72, %73, %74, %75, %76, %77, %78, %79, %80, %81, %82, %83, %84, %85, %86, %87, %88, %89, %90, %91, %92, %93, %94, %95, %96, %97}, "
    "a, b, 1, 1, 1, 0, 1;\n"
    "add.u32 t, %98, 2;\nadd.u32 u, %99, 128;\nmov.b64 a, {t, %100};\nmov.b64 b, {u, %101};\n"
    "wgmma.mma_async.sync.aligned.m64n192k16.f32.bf16.bf16 "
    "{%2, %3, %4, %5, %6, %7, %8, %9, %10, %11, %12, %13, %14, %15, %16, %17, %18, %19, %20, %21, %22, %23, %24, %25, %26, %27, %28, %29, %30, %31, %32, %33, %34, %35, %36, %37, %38, %39, %40, %41, %42, %43, %44, %45, %46, %47, %48, %49, %50, %51, %52, %53, %54, %55, %56, %57, %58, %59, %60, %61, %62, %63, %64, %65, %66, %67, %68, %69, %70, %71, %72, %73, %74, %75, %76, %77, %78, %79, %80, %81, %82, %83, %84, %85, %86, %87, %88, %89, %90, %91, %92, %93, %94, %95, %96, %97}, "
    "a, b, 1, 1, 1, 0, 1;\n"
    "mov.b64 s, {%103, %103};\nmbarrier.test_wait.shared::cta.b64 p, [%102], s;\nmov.b64 s, {%105, %105};\nmbarrier.test_wait.shared::cta.b64 q, [%104], s;\n"
    "add.u32 t, %98, 4;\nadd.u32 u, %99, 256;\nmov.b64 a, {t, %100};\nmov.b64 b, {u, %101};\n"
    "wgmma.mma_async.sync.aligned.m64n192k16.f32.bf16.bf16 "
    "{%2, %3, %4, %5, %6, %7, %8, %9, %10, %11, %12, %13, %14, %15, %16, %17, %18, %19, %20, %21, %22, %23, %24, %25, %26, %27, %28, %29, %30, %31, %32, %33, %34, %35, %36, %37, %38, %39, %40, %41, %42, %43, %44, %45, %46, %47, %48, %49, %50, %51, %52, %53, %54, %55, %56, %57, %58, %59, %60, %61, %62, %63, %64, %65, %66, %67, %68, %69, %70, %71, %72, %73, %74, %75, %76, %77, %78, %79, %80, %81, %82, %83, %84, %85, %86, %87, %88, %89, %90, %91, %92, %93, %94, %95, %96, %97}, "
    "a, b, 1, 1, 1, 0, 1;\n"
    "add.u32 t, %98, 6;\nadd.u32 u, %99, 384;\nmov.b64 a, {t, %100};\nmov.b64 b, {u, %101};\n"
    "wgmma.mma_async.sync.aligned.m64n192k16.f32.bf16.bf16 "
    "{%2, %3, %4, %5, %6, %7, %8, %9, %10, %11, %12, %13, %14, %15, %16, %17, %18, %19, %20, %21, %22, %23, %24, %25, %26, %27, %28, %29, %30, %31, %32, %33, %34, %35, %36, %37, %38, %39, %40, %41, %42, %43, %44, %45, %46, %47, %48, %49, %50, %51, %52, %53, %54, %55, %56, %57, %58, %59, %60, %61, %62, %63, %64, %65, %66, %67, %68, %69, %70, %71, %72, %73, %74, %75, %76, %77, %78, %79, %80, %81, %82, %83, %84, %85, %86, %87, %88, %89, %90, %91, %92, %93, %94, %95, %96, %97}, "
    "a, b, 1, 1, 1, 0, 1;\n"
    "wgmma.commit_group.sync.aligned;\nselp.u32 %0, 1, 0, p;\nselp.u32 %1, 1, 0, q;\n}"
    : "=r"(ok.x), "=r"(ok.y), "+f"(d[0]), "+f"(d[1]), "+f"(d[2]), "+f"(d[3]), "+f"(d[4]), "+f"(d[5]), "+f"(d[6]), "+f"(d[7]), "+f"(d[8]), "+f"(d[9]), "+f"(d[10]), "+f"(d[11]), "+f"(d[12]), "+f"(d[13]), "+f"(d[14]), "+f"(d[15]), "+f"(d[16]), "+f"(d[17]), "+f"(d[18]), "+f"(d[19]), "+f"(d[20]), "+f"(d[21]), "+f"(d[22]), "+f"(d[23]), "+f"(d[24]), "+f"(d[25]), "+f"(d[26]), "+f"(d[27]), "+f"(d[28]), "+f"(d[29]), "+f"(d[30]), "+f"(d[31]), "+f"(d[32]), "+f"(d[33]), "+f"(d[34]), "+f"(d[35]), "+f"(d[36]), "+f"(d[37]), "+f"(d[38]), "+f"(d[39]), "+f"(d[40]), "+f"(d[41]), "+f"(d[42]), "+f"(d[43]), "+f"(d[44]), "+f"(d[45]), "+f"(d[46]), "+f"(d[47]), "+f"(d[48]), "+f"(d[49]), "+f"(d[50]), "+f"(d[51]), "+f"(d[52]), "+f"(d[53]), "+f"(d[54]), "+f"(d[55]), "+f"(d[56]), "+f"(d[57]), "+f"(d[58]), "+f"(d[59]), "+f"(d[60]), "+f"(d[61]), "+f"(d[62]), "+f"(d[63]), "+f"(d[64]), "+f"(d[65]), "+f"(d[66]), "+f"(d[67]), "+f"(d[68]), "+f"(d[69]), "+f"(d[70]), "+f"(d[71]), "+f"(d[72]), "+f"(d[73]), "+f"(d[74]), "+f"(d[75]), "+f"(d[76]), "+f"(d[77]), "+f"(d[78]), "+f"(d[79]), "+f"(d[80]), "+f"(d[81]), "+f"(d[82]), "+f"(d[83]), "+f"(d[84]), "+f"(d[85]), "+f"(d[86]), "+f"(d[87]), "+f"(d[88]), "+f"(d[89]), "+f"(d[90]), "+f"(d[91]), "+f"(d[92]), "+f"(d[93]), "+f"(d[94]), "+f"(d[95])
    : "r"(da), "r"(db), "r"(h0), "r"(h1), "r"(b0), "r"(p0), "r"(b1), "r"(p1) : "memory");
  return ok;
}
template <int S> __device__ __forceinline__ void wgmma_first256(float (&d)[S], uint32_t da, uint32_t db, uint32_t h0, uint32_t h1) {
  asm volatile("{\n.reg .b64 a, b, s;\n.reg .b32 t, u;\n.reg .pred p, q;\nwgmma.fence.sync.aligned;\n"
    "add.u32 t, %128, 0;\nadd.u32 u, %129, 0;\nmov.b64 a, {t, %130};\nmov.b64 b, {u, %131};\n"
    "wgmma.mma_async.sync.aligned.m64n256k16.f32.bf16.bf16 "
    "{%0, %1, %2, %3, %4, %5, %6, %7, %8, %9, %10, %11, %12, %13, %14, %15, %16, %17, %18, %19, %20, %21, %22, %23, %24, %25, %26, %27, %28, %29, %30, %31, %32, %33, %34, %35, %36, %37, %38, %39, %40, %41, %42, %43, %44, %45, %46, %47, %48, %49, %50, %51, %52, %53, %54, %55, %56, %57, %58, %59, %60, %61, %62, %63, %64, %65, %66, %67, %68, %69, %70, %71, %72, %73, %74, %75, %76, %77, %78, %79, %80, %81, %82, %83, %84, %85, %86, %87, %88, %89, %90, %91, %92, %93, %94, %95, %96, %97, %98, %99, %100, %101, %102, %103, %104, %105, %106, %107, %108, %109, %110, %111, %112, %113, %114, %115, %116, %117, %118, %119, %120, %121, %122, %123, %124, %125, %126, %127}, "
    "a, b, 0, 1, 1, 0, 1;\n"
    "add.u32 t, %128, 2;\nadd.u32 u, %129, 128;\nmov.b64 a, {t, %130};\nmov.b64 b, {u, %131};\n"
    "wgmma.mma_async.sync.aligned.m64n256k16.f32.bf16.bf16 "
    "{%0, %1, %2, %3, %4, %5, %6, %7, %8, %9, %10, %11, %12, %13, %14, %15, %16, %17, %18, %19, %20, %21, %22, %23, %24, %25, %26, %27, %28, %29, %30, %31, %32, %33, %34, %35, %36, %37, %38, %39, %40, %41, %42, %43, %44, %45, %46, %47, %48, %49, %50, %51, %52, %53, %54, %55, %56, %57, %58, %59, %60, %61, %62, %63, %64, %65, %66, %67, %68, %69, %70, %71, %72, %73, %74, %75, %76, %77, %78, %79, %80, %81, %82, %83, %84, %85, %86, %87, %88, %89, %90, %91, %92, %93, %94, %95, %96, %97, %98, %99, %100, %101, %102, %103, %104, %105, %106, %107, %108, %109, %110, %111, %112, %113, %114, %115, %116, %117, %118, %119, %120, %121, %122, %123, %124, %125, %126, %127}, "
    "a, b, 1, 1, 1, 0, 1;\n"
    "add.u32 t, %128, 4;\nadd.u32 u, %129, 256;\nmov.b64 a, {t, %130};\nmov.b64 b, {u, %131};\n"
    "wgmma.mma_async.sync.aligned.m64n256k16.f32.bf16.bf16 "
    "{%0, %1, %2, %3, %4, %5, %6, %7, %8, %9, %10, %11, %12, %13, %14, %15, %16, %17, %18, %19, %20, %21, %22, %23, %24, %25, %26, %27, %28, %29, %30, %31, %32, %33, %34, %35, %36, %37, %38, %39, %40, %41, %42, %43, %44, %45, %46, %47, %48, %49, %50, %51, %52, %53, %54, %55, %56, %57, %58, %59, %60, %61, %62, %63, %64, %65, %66, %67, %68, %69, %70, %71, %72, %73, %74, %75, %76, %77, %78, %79, %80, %81, %82, %83, %84, %85, %86, %87, %88, %89, %90, %91, %92, %93, %94, %95, %96, %97, %98, %99, %100, %101, %102, %103, %104, %105, %106, %107, %108, %109, %110, %111, %112, %113, %114, %115, %116, %117, %118, %119, %120, %121, %122, %123, %124, %125, %126, %127}, "
    "a, b, 1, 1, 1, 0, 1;\n"
    "add.u32 t, %128, 6;\nadd.u32 u, %129, 384;\nmov.b64 a, {t, %130};\nmov.b64 b, {u, %131};\n"
    "wgmma.mma_async.sync.aligned.m64n256k16.f32.bf16.bf16 "
    "{%0, %1, %2, %3, %4, %5, %6, %7, %8, %9, %10, %11, %12, %13, %14, %15, %16, %17, %18, %19, %20, %21, %22, %23, %24, %25, %26, %27, %28, %29, %30, %31, %32, %33, %34, %35, %36, %37, %38, %39, %40, %41, %42, %43, %44, %45, %46, %47, %48, %49, %50, %51, %52, %53, %54, %55, %56, %57, %58, %59, %60, %61, %62, %63, %64, %65, %66, %67, %68, %69, %70, %71, %72, %73, %74, %75, %76, %77, %78, %79, %80, %81, %82, %83, %84, %85, %86, %87, %88, %89, %90, %91, %92, %93, %94, %95, %96, %97, %98, %99, %100, %101, %102, %103, %104, %105, %106, %107, %108, %109, %110, %111, %112, %113, %114, %115, %116, %117, %118, %119, %120, %121, %122, %123, %124, %125, %126, %127}, "
    "a, b, 1, 1, 1, 0, 1;\n"
    "wgmma.commit_group.sync.aligned;\n}"
    : "=f"(d[0]), "=f"(d[1]), "=f"(d[2]), "=f"(d[3]), "=f"(d[4]), "=f"(d[5]), "=f"(d[6]), "=f"(d[7]), "=f"(d[8]), "=f"(d[9]), "=f"(d[10]), "=f"(d[11]), "=f"(d[12]), "=f"(d[13]), "=f"(d[14]), "=f"(d[15]), "=f"(d[16]), "=f"(d[17]), "=f"(d[18]), "=f"(d[19]), "=f"(d[20]), "=f"(d[21]), "=f"(d[22]), "=f"(d[23]), "=f"(d[24]), "=f"(d[25]), "=f"(d[26]), "=f"(d[27]), "=f"(d[28]), "=f"(d[29]), "=f"(d[30]), "=f"(d[31]), "=f"(d[32]), "=f"(d[33]), "=f"(d[34]), "=f"(d[35]), "=f"(d[36]), "=f"(d[37]), "=f"(d[38]), "=f"(d[39]), "=f"(d[40]), "=f"(d[41]), "=f"(d[42]), "=f"(d[43]), "=f"(d[44]), "=f"(d[45]), "=f"(d[46]), "=f"(d[47]), "=f"(d[48]), "=f"(d[49]), "=f"(d[50]), "=f"(d[51]), "=f"(d[52]), "=f"(d[53]), "=f"(d[54]), "=f"(d[55]), "=f"(d[56]), "=f"(d[57]), "=f"(d[58]), "=f"(d[59]), "=f"(d[60]), "=f"(d[61]), "=f"(d[62]), "=f"(d[63]), "=f"(d[64]), "=f"(d[65]), "=f"(d[66]), "=f"(d[67]), "=f"(d[68]), "=f"(d[69]), "=f"(d[70]), "=f"(d[71]), "=f"(d[72]), "=f"(d[73]), "=f"(d[74]), "=f"(d[75]), "=f"(d[76]), "=f"(d[77]), "=f"(d[78]), "=f"(d[79]), "=f"(d[80]), "=f"(d[81]), "=f"(d[82]), "=f"(d[83]), "=f"(d[84]), "=f"(d[85]), "=f"(d[86]), "=f"(d[87]), "=f"(d[88]), "=f"(d[89]), "=f"(d[90]), "=f"(d[91]), "=f"(d[92]), "=f"(d[93]), "=f"(d[94]), "=f"(d[95]), "=f"(d[96]), "=f"(d[97]), "=f"(d[98]), "=f"(d[99]), "=f"(d[100]), "=f"(d[101]), "=f"(d[102]), "=f"(d[103]), "=f"(d[104]), "=f"(d[105]), "=f"(d[106]), "=f"(d[107]), "=f"(d[108]), "=f"(d[109]), "=f"(d[110]), "=f"(d[111]), "=f"(d[112]), "=f"(d[113]), "=f"(d[114]), "=f"(d[115]), "=f"(d[116]), "=f"(d[117]), "=f"(d[118]), "=f"(d[119]), "=f"(d[120]), "=f"(d[121]), "=f"(d[122]), "=f"(d[123]), "=f"(d[124]), "=f"(d[125]), "=f"(d[126]), "=f"(d[127])
    : "r"(da), "r"(db), "r"(h0), "r"(h1) : "memory");
}
template <int S> __device__ __forceinline__ void wgmma_acc256(float (&d)[S], uint32_t da, uint32_t db, uint32_t h0, uint32_t h1) {
  asm volatile("{\n.reg .b64 a, b, s;\n.reg .b32 t, u;\n.reg .pred p, q;\nwgmma.fence.sync.aligned;\n"
    "add.u32 t, %128, 0;\nadd.u32 u, %129, 0;\nmov.b64 a, {t, %130};\nmov.b64 b, {u, %131};\n"
    "wgmma.mma_async.sync.aligned.m64n256k16.f32.bf16.bf16 "
    "{%0, %1, %2, %3, %4, %5, %6, %7, %8, %9, %10, %11, %12, %13, %14, %15, %16, %17, %18, %19, %20, %21, %22, %23, %24, %25, %26, %27, %28, %29, %30, %31, %32, %33, %34, %35, %36, %37, %38, %39, %40, %41, %42, %43, %44, %45, %46, %47, %48, %49, %50, %51, %52, %53, %54, %55, %56, %57, %58, %59, %60, %61, %62, %63, %64, %65, %66, %67, %68, %69, %70, %71, %72, %73, %74, %75, %76, %77, %78, %79, %80, %81, %82, %83, %84, %85, %86, %87, %88, %89, %90, %91, %92, %93, %94, %95, %96, %97, %98, %99, %100, %101, %102, %103, %104, %105, %106, %107, %108, %109, %110, %111, %112, %113, %114, %115, %116, %117, %118, %119, %120, %121, %122, %123, %124, %125, %126, %127}, "
    "a, b, 1, 1, 1, 0, 1;\n"
    "add.u32 t, %128, 2;\nadd.u32 u, %129, 128;\nmov.b64 a, {t, %130};\nmov.b64 b, {u, %131};\n"
    "wgmma.mma_async.sync.aligned.m64n256k16.f32.bf16.bf16 "
    "{%0, %1, %2, %3, %4, %5, %6, %7, %8, %9, %10, %11, %12, %13, %14, %15, %16, %17, %18, %19, %20, %21, %22, %23, %24, %25, %26, %27, %28, %29, %30, %31, %32, %33, %34, %35, %36, %37, %38, %39, %40, %41, %42, %43, %44, %45, %46, %47, %48, %49, %50, %51, %52, %53, %54, %55, %56, %57, %58, %59, %60, %61, %62, %63, %64, %65, %66, %67, %68, %69, %70, %71, %72, %73, %74, %75, %76, %77, %78, %79, %80, %81, %82, %83, %84, %85, %86, %87, %88, %89, %90, %91, %92, %93, %94, %95, %96, %97, %98, %99, %100, %101, %102, %103, %104, %105, %106, %107, %108, %109, %110, %111, %112, %113, %114, %115, %116, %117, %118, %119, %120, %121, %122, %123, %124, %125, %126, %127}, "
    "a, b, 1, 1, 1, 0, 1;\n"
    "add.u32 t, %128, 4;\nadd.u32 u, %129, 256;\nmov.b64 a, {t, %130};\nmov.b64 b, {u, %131};\n"
    "wgmma.mma_async.sync.aligned.m64n256k16.f32.bf16.bf16 "
    "{%0, %1, %2, %3, %4, %5, %6, %7, %8, %9, %10, %11, %12, %13, %14, %15, %16, %17, %18, %19, %20, %21, %22, %23, %24, %25, %26, %27, %28, %29, %30, %31, %32, %33, %34, %35, %36, %37, %38, %39, %40, %41, %42, %43, %44, %45, %46, %47, %48, %49, %50, %51, %52, %53, %54, %55, %56, %57, %58, %59, %60, %61, %62, %63, %64, %65, %66, %67, %68, %69, %70, %71, %72, %73, %74, %75, %76, %77, %78, %79, %80, %81, %82, %83, %84, %85, %86, %87, %88, %89, %90, %91, %92, %93, %94, %95, %96, %97, %98, %99, %100, %101, %102, %103, %104, %105, %106, %107, %108, %109, %110, %111, %112, %113, %114, %115, %116, %117, %118, %119, %120, %121, %122, %123, %124, %125, %126, %127}, "
    "a, b, 1, 1, 1, 0, 1;\n"
    "add.u32 t, %128, 6;\nadd.u32 u, %129, 384;\nmov.b64 a, {t, %130};\nmov.b64 b, {u, %131};\n"
    "wgmma.mma_async.sync.aligned.m64n256k16.f32.bf16.bf16 "
    "{%0, %1, %2, %3, %4, %5, %6, %7, %8, %9, %10, %11, %12, %13, %14, %15, %16, %17, %18, %19, %20, %21, %22, %23, %24, %25, %26, %27, %28, %29, %30, %31, %32, %33, %34, %35, %36, %37, %38, %39, %40, %41, %42, %43, %44, %45, %46, %47, %48, %49, %50, %51, %52, %53, %54, %55, %56, %57, %58, %59, %60, %61, %62, %63, %64, %65, %66, %67, %68, %69, %70, %71, %72, %73, %74, %75, %76, %77, %78, %79, %80, %81, %82, %83, %84, %85, %86, %87, %88, %89, %90, %91, %92, %93, %94, %95, %96, %97, %98, %99, %100, %101, %102, %103, %104, %105, %106, %107, %108, %109, %110, %111, %112, %113, %114, %115, %116, %117, %118, %119, %120, %121, %122, %123, %124, %125, %126, %127}, "
    "a, b, 1, 1, 1, 0, 1;\n"
    "wgmma.commit_group.sync.aligned;\n}"
    : "+f"(d[0]), "+f"(d[1]), "+f"(d[2]), "+f"(d[3]), "+f"(d[4]), "+f"(d[5]), "+f"(d[6]), "+f"(d[7]), "+f"(d[8]), "+f"(d[9]), "+f"(d[10]), "+f"(d[11]), "+f"(d[12]), "+f"(d[13]), "+f"(d[14]), "+f"(d[15]), "+f"(d[16]), "+f"(d[17]), "+f"(d[18]), "+f"(d[19]), "+f"(d[20]), "+f"(d[21]), "+f"(d[22]), "+f"(d[23]), "+f"(d[24]), "+f"(d[25]), "+f"(d[26]), "+f"(d[27]), "+f"(d[28]), "+f"(d[29]), "+f"(d[30]), "+f"(d[31]), "+f"(d[32]), "+f"(d[33]), "+f"(d[34]), "+f"(d[35]), "+f"(d[36]), "+f"(d[37]), "+f"(d[38]), "+f"(d[39]), "+f"(d[40]), "+f"(d[41]), "+f"(d[42]), "+f"(d[43]), "+f"(d[44]), "+f"(d[45]), "+f"(d[46]), "+f"(d[47]), "+f"(d[48]), "+f"(d[49]), "+f"(d[50]), "+f"(d[51]), "+f"(d[52]), "+f"(d[53]), "+f"(d[54]), "+f"(d[55]), "+f"(d[56]), "+f"(d[57]), "+f"(d[58]), "+f"(d[59]), "+f"(d[60]), "+f"(d[61]), "+f"(d[62]), "+f"(d[63]), "+f"(d[64]), "+f"(d[65]), "+f"(d[66]), "+f"(d[67]), "+f"(d[68]), "+f"(d[69]), "+f"(d[70]), "+f"(d[71]), "+f"(d[72]), "+f"(d[73]), "+f"(d[74]), "+f"(d[75]), "+f"(d[76]), "+f"(d[77]), "+f"(d[78]), "+f"(d[79]), "+f"(d[80]), "+f"(d[81]), "+f"(d[82]), "+f"(d[83]), "+f"(d[84]), "+f"(d[85]), "+f"(d[86]), "+f"(d[87]), "+f"(d[88]), "+f"(d[89]), "+f"(d[90]), "+f"(d[91]), "+f"(d[92]), "+f"(d[93]), "+f"(d[94]), "+f"(d[95]), "+f"(d[96]), "+f"(d[97]), "+f"(d[98]), "+f"(d[99]), "+f"(d[100]), "+f"(d[101]), "+f"(d[102]), "+f"(d[103]), "+f"(d[104]), "+f"(d[105]), "+f"(d[106]), "+f"(d[107]), "+f"(d[108]), "+f"(d[109]), "+f"(d[110]), "+f"(d[111]), "+f"(d[112]), "+f"(d[113]), "+f"(d[114]), "+f"(d[115]), "+f"(d[116]), "+f"(d[117]), "+f"(d[118]), "+f"(d[119]), "+f"(d[120]), "+f"(d[121]), "+f"(d[122]), "+f"(d[123]), "+f"(d[124]), "+f"(d[125]), "+f"(d[126]), "+f"(d[127])
    : "r"(da), "r"(db), "r"(h0), "r"(h1) : "memory");
}
template <int S> __device__ __forceinline__ void wgmma_aug192(float (&d)[S], uint32_t a0, uint32_t a1, uint32_t db, uint32_t h1) {
  asm volatile("{\n.reg .b64 b;\n.reg .b32 z;\nmov.b32 z, 0;\n"
    "mov.b64 b, {%98, %99};\nwgmma.fence.sync.aligned;\n"
    "wgmma.mma_async.sync.aligned.m64n192k16.f32.bf16.bf16 "
    "{%0, %1, %2, %3, %4, %5, %6, %7, %8, %9, %10, %11, %12, %13, %14, %15, %16, %17, %18, %19, %20, %21, %22, %23, %24, %25, %26, %27, %28, %29, %30, %31, %32, %33, %34, %35, %36, %37, %38, %39, %40, %41, %42, %43, %44, %45, %46, %47, %48, %49, %50, %51, %52, %53, %54, %55, %56, %57, %58, %59, %60, %61, %62, %63, %64, %65, %66, %67, %68, %69, %70, %71, %72, %73, %74, %75, %76, %77, %78, %79, %80, %81, %82, %83, %84, %85, %86, %87, %88, %89, %90, %91, %92, %93, %94, %95}, "
    "{%96, %97, z, z}, b, 1, 1, 1, 1;\n"
    "wgmma.commit_group.sync.aligned;\n}"
    : "+f"(d[0]), "+f"(d[1]), "+f"(d[2]), "+f"(d[3]), "+f"(d[4]), "+f"(d[5]), "+f"(d[6]), "+f"(d[7]), "+f"(d[8]), "+f"(d[9]), "+f"(d[10]), "+f"(d[11]), "+f"(d[12]), "+f"(d[13]), "+f"(d[14]), "+f"(d[15]), "+f"(d[16]), "+f"(d[17]), "+f"(d[18]), "+f"(d[19]), "+f"(d[20]), "+f"(d[21]), "+f"(d[22]), "+f"(d[23]), "+f"(d[24]), "+f"(d[25]), "+f"(d[26]), "+f"(d[27]), "+f"(d[28]), "+f"(d[29]), "+f"(d[30]), "+f"(d[31]), "+f"(d[32]), "+f"(d[33]), "+f"(d[34]), "+f"(d[35]), "+f"(d[36]), "+f"(d[37]), "+f"(d[38]), "+f"(d[39]), "+f"(d[40]), "+f"(d[41]), "+f"(d[42]), "+f"(d[43]), "+f"(d[44]), "+f"(d[45]), "+f"(d[46]), "+f"(d[47]), "+f"(d[48]), "+f"(d[49]), "+f"(d[50]), "+f"(d[51]), "+f"(d[52]), "+f"(d[53]), "+f"(d[54]), "+f"(d[55]), "+f"(d[56]), "+f"(d[57]), "+f"(d[58]), "+f"(d[59]), "+f"(d[60]), "+f"(d[61]), "+f"(d[62]), "+f"(d[63]), "+f"(d[64]), "+f"(d[65]), "+f"(d[66]), "+f"(d[67]), "+f"(d[68]), "+f"(d[69]), "+f"(d[70]), "+f"(d[71]), "+f"(d[72]), "+f"(d[73]), "+f"(d[74]), "+f"(d[75]), "+f"(d[76]), "+f"(d[77]), "+f"(d[78]), "+f"(d[79]), "+f"(d[80]), "+f"(d[81]), "+f"(d[82]), "+f"(d[83]), "+f"(d[84]), "+f"(d[85]), "+f"(d[86]), "+f"(d[87]), "+f"(d[88]), "+f"(d[89]), "+f"(d[90]), "+f"(d[91]), "+f"(d[92]), "+f"(d[93]), "+f"(d[94]), "+f"(d[95])
    : "r"(a0), "r"(a1), "r"(db), "r"(h1) : "memory");
}
template <int S> __device__ __forceinline__ void wgmma_aug256(float (&d)[S], uint32_t a0, uint32_t a1, uint32_t db, uint32_t h1) {
  asm volatile("{\n.reg .b64 b;\n.reg .b32 z;\nmov.b32 z, 0;\n"
    "mov.b64 b, {%130, %131};\nwgmma.fence.sync.aligned;\n"
    "wgmma.mma_async.sync.aligned.m64n256k16.f32.bf16.bf16 "
    "{%0, %1, %2, %3, %4, %5, %6, %7, %8, %9, %10, %11, %12, %13, %14, %15, %16, %17, %18, %19, %20, %21, %22, %23, %24, %25, %26, %27, %28, %29, %30, %31, %32, %33, %34, %35, %36, %37, %38, %39, %40, %41, %42, %43, %44, %45, %46, %47, %48, %49, %50, %51, %52, %53, %54, %55, %56, %57, %58, %59, %60, %61, %62, %63, %64, %65, %66, %67, %68, %69, %70, %71, %72, %73, %74, %75, %76, %77, %78, %79, %80, %81, %82, %83, %84, %85, %86, %87, %88, %89, %90, %91, %92, %93, %94, %95, %96, %97, %98, %99, %100, %101, %102, %103, %104, %105, %106, %107, %108, %109, %110, %111, %112, %113, %114, %115, %116, %117, %118, %119, %120, %121, %122, %123, %124, %125, %126, %127}, "
    "{%128, %129, z, z}, b, 1, 1, 1, 1;\n"
    "wgmma.commit_group.sync.aligned;\n}"
    : "+f"(d[0]), "+f"(d[1]), "+f"(d[2]), "+f"(d[3]), "+f"(d[4]), "+f"(d[5]), "+f"(d[6]), "+f"(d[7]), "+f"(d[8]), "+f"(d[9]), "+f"(d[10]), "+f"(d[11]), "+f"(d[12]), "+f"(d[13]), "+f"(d[14]), "+f"(d[15]), "+f"(d[16]), "+f"(d[17]), "+f"(d[18]), "+f"(d[19]), "+f"(d[20]), "+f"(d[21]), "+f"(d[22]), "+f"(d[23]), "+f"(d[24]), "+f"(d[25]), "+f"(d[26]), "+f"(d[27]), "+f"(d[28]), "+f"(d[29]), "+f"(d[30]), "+f"(d[31]), "+f"(d[32]), "+f"(d[33]), "+f"(d[34]), "+f"(d[35]), "+f"(d[36]), "+f"(d[37]), "+f"(d[38]), "+f"(d[39]), "+f"(d[40]), "+f"(d[41]), "+f"(d[42]), "+f"(d[43]), "+f"(d[44]), "+f"(d[45]), "+f"(d[46]), "+f"(d[47]), "+f"(d[48]), "+f"(d[49]), "+f"(d[50]), "+f"(d[51]), "+f"(d[52]), "+f"(d[53]), "+f"(d[54]), "+f"(d[55]), "+f"(d[56]), "+f"(d[57]), "+f"(d[58]), "+f"(d[59]), "+f"(d[60]), "+f"(d[61]), "+f"(d[62]), "+f"(d[63]), "+f"(d[64]), "+f"(d[65]), "+f"(d[66]), "+f"(d[67]), "+f"(d[68]), "+f"(d[69]), "+f"(d[70]), "+f"(d[71]), "+f"(d[72]), "+f"(d[73]), "+f"(d[74]), "+f"(d[75]), "+f"(d[76]), "+f"(d[77]), "+f"(d[78]), "+f"(d[79]), "+f"(d[80]), "+f"(d[81]), "+f"(d[82]), "+f"(d[83]), "+f"(d[84]), "+f"(d[85]), "+f"(d[86]), "+f"(d[87]), "+f"(d[88]), "+f"(d[89]), "+f"(d[90]), "+f"(d[91]), "+f"(d[92]), "+f"(d[93]), "+f"(d[94]), "+f"(d[95]), "+f"(d[96]), "+f"(d[97]), "+f"(d[98]), "+f"(d[99]), "+f"(d[100]), "+f"(d[101]), "+f"(d[102]), "+f"(d[103]), "+f"(d[104]), "+f"(d[105]), "+f"(d[106]), "+f"(d[107]), "+f"(d[108]), "+f"(d[109]), "+f"(d[110]), "+f"(d[111]), "+f"(d[112]), "+f"(d[113]), "+f"(d[114]), "+f"(d[115]), "+f"(d[116]), "+f"(d[117]), "+f"(d[118]), "+f"(d[119]), "+f"(d[120]), "+f"(d[121]), "+f"(d[122]), "+f"(d[123]), "+f"(d[124]), "+f"(d[125]), "+f"(d[126]), "+f"(d[127])
    : "r"(a0), "r"(a1), "r"(db), "r"(h1) : "memory");
}

__device__ __forceinline__ uint32_t clock32() { uint32_t c; asm volatile("mov.u32 %0, %%clock;" : "=r"(c)); return c; }
__device__ __forceinline__ void spin_until(uint32_t c) {
  asm volatile("{\n.reg .pred p;\n.reg .s32 t;\nLAB_WAIT:\nmov.u32 t, %%clock;\nsub.s32 t, t, %0;\nsetp.lt.s32 p, t, 0;\n@p bra.uni LAB_WAIT;\n}" ::"r"(c) : "memory");
}
struct Nop { __device__ __forceinline__ void operator()(int) const {} };
template <int V> struct IC { static constexpr int v = V; };
constexpr uint32_t PA1 = 0x80000000u / NA + 1, G1 = 8 + (1u << 28), DB0 = ((SB + OFF_B) >> 4) | (512u << 16);
struct Pipe {
  uint32_t db, g8, a8, pa, tph, aend, curB, curA, prevB, prevA, bo, so, sph, h0, h1;
  uint2 nx;
  int w; bool l0;
  __device__ __forceinline__ int lane() const { return LSO ? (so >> 5) & 31 : threadIdx.x & 31; }
  __device__ __forceinline__ void adv_a() { a8 += 8; pa += PA1; if (a8 == aend) a8 -= NA * 8; }
  __device__ __forceinline__ uint32_t take() { const uint32_t a = SB + OFF_A + a8 * 1024; adv_a(); return a; }
  __device__ __forceinline__ uint32_t ahead(int d) const { uint32_t ls = a8 + d * 8; if (ls >= aend) ls -= NA * 8; return SB + OFF_A + ls * 1024; }
  __device__ __forceinline__ uint32_t wait_ahead(int d) {
    uint32_t ls = a8 + d * 8;
    if (ls >= aend) ls -= NA * 8;
    mbar_spin31(SB + BAR_FULLA + ls, pa + d * PA1);
    return SB + OFF_A + ls * 1024;
  }
  template <int N, bool FIRST, int S> __device__ __forceinline__ uint2 iss(float (&acc)[S], bool skip) {
    const uint32_t da = (((SB + OFF_A) >> 4) | (1u << 16)) + a8 * 64;
    prevB = curB; prevA = curA;
    curB = g8 & 56; curA = a8;
    g8 += G1;
    a8 += skip ? 16 : 8; pa += skip ? 2 * PA1 : PA1;
    if (a8 >= aend) a8 -= NA * 8;
    uint2 ok = make_uint2(0, 0);
    if constexpr (N == 128) {
      if (FIRST) wgmma_first128(acc, da, db, h0, h1);
      else ok = wgmma_probe128(acc, da, db, h0, h1, SB + BAR_FULLB + (g8 & 56), g8, SB + BAR_FULLA + a8, pa);
    }
    if constexpr (N == 192) {
      if (FIRST) wgmma_first192(acc, da, db, h0, h1);
      else ok = wgmma_probe192(acc, da, db, h0, h1, SB + BAR_FULLB + (g8 & 56), g8, SB + BAR_FULLA + a8, pa);
    }
    if constexpr (N == 256) { if (FIRST) wgmma_first256(acc, da, db, h0, h1); else wgmma_acc256(acc, da, db, h0, h1); }
    db += N * 8;
    if (N != 192) db &= ~0x2000u; else if (db == DB0 + 15 * 512) db = DB0;
    return ok;
  }
  __device__ __forceinline__ void ensure(uint2 ok) {
    asm volatile(
        "{\n.reg .pred p, q;\n.reg .b64 s, t;\nmov.b64 s, {%1, %1};\nmov.b64 t, {%3, %3};\nsetp.ne.u32 p, %4, 0;\nsetp.ne.u32 q, %5, 0;\n@!p bra.uni LAB_WAIT;\n@q bra.uni DONE;\n"
        "LAB_WAIT:\nmbarrier.try_wait.shared::cta.b64 p, [%0], s;\nmbarrier.try_wait.shared::cta.b64 q, [%2], t;\n"
        "and.pred p, p, q;\n@!p bra.uni LAB_WAIT;\nDONE:\n}" ::"r"(SB + BAR_FULLB + (g8 & 56)), "r"(g8), "r"(SB + BAR_FULLA + a8), "r"(pa), "r"(ok.x), "r"(ok.y) : "memory");
  }
  template <class Hook> __device__ __forceinline__ void validate(bool check, const CUtensorMap* tm16, int c0, int c1, int wp, int j, Hook hook) {
    const uint32_t rows = SB + OFF_A + a8 * 1024 + wp * 2048, ad = a8 * 1024 + so;
    uint32_t v0 = 0, v1 = 0;
    asm volatile("{\n.reg .pred p;\nsetp.ne.u32 p, %3, 0;\n@p ld.shared.b32 %0, [%2];\n@p ld.shared.b32 %1, [%2 + 1024];\n}" : "+r"(v0), "+r"(v1) : "r"(ad), "r"((uint32_t)check));
    check = true;
    hook();
    while (__any_sync(~0u, check && max(v0, v1) == 0xffffffffu)) {
      const uint32_t bar = SB + BAR_SPEC + (w * 4 + wp) * 8;
      e_load<2048>(rows, tm16, c0 + sched_k(c_sched.v[j][(g8 >> 3) & 511]), c1 + wp * 16, bar);
      mbar_spin(bar, sph);
      sph ^= 1;
      v0 = lds32(ad); v1 = lds32(ad + 1024);
    }
  }
  __device__ __forceinline__ void drain() {
    wg_wait<0>();
    arrive_2(SB + BAR_EMPTYB + curB, SB + BAR_EMPTYA + curA, l0);
    curB = BAR_DUMMY - BAR_EMPTYB; curA = BAR_DUMMY - BAR_EMPTYA;
  }
  __device__ __forceinline__ void signal_server(uint32_t odd) { __syncwarp(); arrive_n(SB + BAR_SRV + w * 16 + odd * 8, l0); }
  __device__ __forceinline__ void signal_loader() { __syncwarp(); arrive_n(SB + BAR_STG + w * 8, l0); }
  template <int N, bool HOLD = false, int S, class Pre = Nop> __device__ __forceinline__ void begin(float (&acc)[S], uint32_t p0, int proft, Pre pre = Pre()) {
    db = DB0 + p0 * 512;
    const uint32_t c1 = HOLD ? clock32() : 0;
    ensure(make_uint2(0, 0));
    if (HOLD) spin_until(c1 + lds32(SB + OFF_HOLD + w * 4));
    pre(0);
    PROF_T(w, proft, 0);
    ensure(iss<N, true>(acc, false));
  }
  template <int N, bool ENSURE = true, int S, class Hook, class Mid = Nop> __device__ __forceinline__ void run(float (&acc)[S], int i0, int i1, uint32_t skips, int pause, Hook hook, int imid = -1, Mid mid = Mid()) {
    int i = i0, ev = imid >= 0 ? imid : (w ? pause : -1);
#pragma unroll 1
    while (true) {
      const uint2 ok = iss<N, false>(acc, (skips >> i) & 1);
      wg_wait<1>();
      arrive_2(SB + BAR_EMPTYB + prevB, SB + BAR_EMPTYA + prevA, l0);
      if (pause >= 0 && i + 1 == i1) { nx = ok; break; }
      if constexpr (ENSURE) { ensure(ok); hook(i); } else hook(i, ok);
      i++;
      if (pause < 0 && i == i1) break;
      if (i == ev) {
        const bool ps = w && i == pause;
        if (ps) drain();
        if (i == imid) mid(i);
        if (ps) mbar_spin(SB + BAR_LEAD, tph);
        ev = pause;
      }
    }
  }
  template <int N, bool AUG, int S> __device__ __forceinline__ void end(float (&acc)[S], int ns, uint32_t pos, uint32_t au0, uint32_t au1, int proft) {
    uint32_t augB = 0;
    if (LEARLY) arrive_n(SB + BAR_LEAD + w * (BAR_DUMMY - BAR_LEAD), l0);
    if constexpr (AUG) {
      if (AGK && N == 192)
        asm volatile("{\n.reg .pred p;\n.reg .b64 s;\nmov.b64 s, {%1, %1};\nsetp.ne.u32 p, %2, 0;\n@p bra.uni DONE;\nLAB_WAIT:\nmbarrier.try_wait.shared::cta.b64 p, [%0], s;\n@!p bra.uni LAB_WAIT;\nDONE:\n}"
                     ::"r"(SB + BAR_FULLB + (g8 & 56)), "r"(g8), "r"(nx.x) : "memory");
      else mbar_spin31(SB + BAR_FULLB + (g8 & 56), g8);
      const uint32_t dc = (((SB + OFF_B) >> 4) | (64u << 16)) + pos * 512;
      if constexpr (N == 192) wgmma_aug192(acc, au0, au1, dc, h1); else wgmma_aug256(acc, au0, au1, dc, h1);
      augB = g8 & 56; g8 += G1;
    }
    if (!LEARLY) arrive_n(SB + BAR_LEAD + w * (BAR_DUMMY - BAR_LEAD), l0);
    tph ^= 1;
    if (ns > 0) wait_ahead(ns - 1);
    wg_wait<0>();
    arrive_2(SB + BAR_EMPTYB + curB, SB + BAR_EMPTYA + curA, l0);
    if (AUG) arrive_n(SB + BAR_EMPTYB + augB, l0);
    PROF_T(w, proft, 1);
  }
};

__device__ __forceinline__ uint32_t box_addr(uint32_t buf, uint32_t bo, int u) { return (buf + bo) ^ (u * 32); }

__device__ __forceinline__ float bf_round(float x) { return __bfloat162float(__float2bfloat16_rn(x)); }
__device__ __forceinline__ void own_rstd(int w, int wp, int lane, float (&rstd)[2]) {
#pragma unroll
  for (int hh = 0; hh < 2; hh++) rstd[hh] = __uint_as_float(lds32(SB + OFF_RSTD + (w * 72 + 8 + wp * 16 + (lane >> 2) + hh * 8) * 4));
}
__device__ __forceinline__ void stats_fetch(int w, int wp, int lane, uint32_t (&au)[2]) {
  const int g = lane >> 2, q4 = lane & 3;
  float rstd[2];
  own_rstd(w, wp, lane, rstd);
#pragma unroll
  for (int hh = 0; hh < 2; hh++) {
    const float m = __uint_as_float(lds32(SB + OFF_MEAN + (w * 64 + wp * 16 + g + hh * 8) * 4));
    const float v = q4 == 3 ? rcp(rstd[hh]) : -m;
    const float v1 = bf_round(v), v2 = bf_round(v - v1);
    const float p = q4 == 1 ? v2 : (q4 == 2 ? v - v1 - v2 : v1);
    au[hh] = pack_bf16(p, q4 == 3 ? v2 : p);
  }
}

__device__ __forceinline__ void halo_fetch(uint32_t slot, int w, const uint4* src, uint32_t bar) {
  asm volatile("{\n.reg .pred p;\nelect.sync _|p, 0xffffffff;\n@p mbarrier.arrive.expect_tx.shared::cta.b64 _, [%4], 2080;\n"
               "@p cp.async.bulk.shared::cluster.global.mbarrier::complete_tx::bytes [%0], [%2], 2048, [%4];\n"
               "@p cp.async.bulk.shared::cluster.global.mbarrier::complete_tx::bytes [%1], [%3], 32, [%4];\n}"
               ::"r"(slot), "r"(SB + OFF_RSTD + w * 288), "l"(src), "l"(src + 128), "r"(bar) : "memory");
}
struct Attn {
  uint32_t lo[24], hi[24], ha[16], hslot;
  float c[8][4], rstd[2];
  float2 rk[3];
  __device__ __forceinline__ void A(const float (&acc)[96], Pipe& M, int w, int wp, int r, uint4* halo_out) {
    const int lane = M.lane();
    M.signal_loader();
    auto cvt = [&](uint32_t& d, int u) { asm volatile("cvt.rn.bf16x2.f32 %0, %1, %2;" : "=r"(d) : "f"(acc[u + 1]), "f"(acc[u])); };
    auto rest = [&] {
#pragma unroll
      for (int nb = 23; nb >= 0; nb--) {
        cvt(lo[nb], 4 * nb);
        if (nb < 8) cvt(hi[nb], 4 * nb + 2);
        if (nb >= 16) lo[nb] = movm(lo[nb]);
      }
    };
#pragma unroll
    for (int nb = 8; nb < 24; nb++) hi[nb] = pack_bf16(acc[4 * nb + 2], acc[4 * nb + 3]);
    hslot = M.ahead(3);
    const uint32_t hbuf = hslot + wp * 2048 + lane * 16;
#pragma unroll
    for (int nb = 16; nb < 24; nb++) hi[nb] = movm(hi[nb]);
    if (TAR) rest();
    if (wp == 3) {
      if (r < 15) {
#pragma unroll
        for (int p = 0; p < 4; p++) halo_out[p * 32 + lane] = make_uint4(hi[8 + 4 * p] ? hi[8 + 4 * p] : 0x8000u, hi[9 + 4 * p], hi[10 + 4 * p], hi[11 + 4 * p]);
        if (!RSV) {
          const uint32_t rh = lds32(SB + OFF_RSTD + (w * 72 + 64 + (lane & 7)) * 4);
          if (lane < 8) reinterpret_cast<uint32_t*>(halo_out + 128)[lane] = rh ? rh : 0x80000000u;
        }
      }
    } else {
#pragma unroll
      for (int p = 0; p < 4; p++)
        asm volatile("st.shared.v4.b32 [%0], {%1,%2,%3,%4};" ::"r"(hbuf + 2048 + p * 512), "r"(hi[8 + 4 * p]), "r"(hi[9 + 4 * p]), "r"(hi[10 + 4 * p]), "r"(hi[11 + 4 * p]) : "memory");
      __syncwarp();
      arrive_n(SB + BAR_HALO + w * 8, M.l0);
    }
    if (!TAR) rest();
  }
  __device__ __forceinline__ void B(int w, int wp, int lane, uint32_t hph) {
    own_rstd(w, wp, lane, rstd);
    mbar_spin(SB + BAR_HALO + w * 8, hph);
#pragma unroll
    for (int p = 0; p < 4; p++)
      asm volatile("ld.shared.v4.b32 {%0,%1,%2,%3}, [%4];" : "=r"(ha[4 * p]), "=r"(ha[4 * p + 1]), "=r"(ha[4 * p + 2]), "=r"(ha[4 * p + 3]) : "r"(hslot + wp * 2048 + lane * 16 + p * 512) : "memory");
#pragma unroll
    for (int u = 0; u < 3; u++) rk[u] = lds64(SB + OFF_RSTD + (w * 72 + wp * 16 + u * 8 + 2 * (lane & 3)) * 4);
  }
  template <class F> __device__ __forceinline__ void C(int wp, int r, int lane, uint32_t zero, F last) {
    const int g = lane >> 2, q = lane & 3;
    const bool nohalo = (wp == 0) && (r == 0);
    const bool up0 = 2 * q > g, up1 = 2 * q + 1 > g;
    const float sc = 0.17677669529663687f * 1.4426950408889634f;
    const float kx0 = up0 ? rk[0].x : rk[1].x, kx1 = up1 ? rk[0].y : rk[1].y;
    const float ky0 = up0 ? rk[1].x : rk[2].x, ky1 = up1 ? rk[1].y : rk[2].y;
    const float fx = rstd[0] * sc, fy = rstd[1] * sc;
    float sm[2][4] = {}, s0[2][4] = {}, s1[2][4] = {};
#pragma unroll
    for (int ks = 0; ks < 2; ks++)
#pragma unroll
      for (int h = 0; h < 2; h++) {
        const int a = 4 * h + 2 * ks;
        mma16(s0[h], lo[a], hi[a], lo[a + 1], hi[a + 1], lo[8 + a], lo[9 + a]);
        mma16(s1[h], lo[a], hi[a], lo[a + 1], hi[a + 1], hi[8 + a], hi[9 + a]);
      }
#pragma unroll
    for (int u = 0; u < 4; u++) { const int a = 4 * (u & 1) + (u & 2); mma16(sm[u & 1], lo[a], hi[a], lo[a + 1], hi[a + 1], ha[a], ha[a + 1]); }
    uint32_t pf[2][4];
    const uint32_t um = (up0 ? 0xffffu : 0u) | (up1 ? 0xffff0000u : 0u);
#pragma unroll
    for (int h = 0; h < 2; h++) {
      if (nohalo) { sm[h][0] = -INFINITY; sm[h][1] = -INFINITY; }
      float x0 = (up0 ? sm[h][0] : s0[h][0]) * (kx0 * fx), x1 = (up1 ? sm[h][1] : s0[h][1]) * (kx1 * fx);
      float y0 = (up0 ? s0[h][2] : s1[h][2]) * (ky0 * fy), y1 = (up1 ? s0[h][3] : s1[h][3]) * (ky1 * fy);
      float mx = fmaxf(x0, x1), my = fmaxf(y0, y1);
      mx = fmaxf(mx, __shfl_xor_sync(~0u, mx, 1)); my = fmaxf(my, __shfl_xor_sync(~0u, my, 1));
      mx = fmaxf(mx, __shfl_xor_sync(~0u, mx, 2)); my = fmaxf(my, __shfl_xor_sync(~0u, my, 2));
      x0 = ex2(x0 - mx); x1 = ex2(x1 - mx); y0 = ex2(y0 - my); y1 = ex2(y1 - my);
      float sx = x0 + x1, sy = y0 + y1;
      x0 *= kx0; x1 *= kx1; y0 *= ky0; y1 *= ky1;
      sx += __shfl_xor_sync(~0u, sx, 1); sy += __shfl_xor_sync(~0u, sy, 1);
      sx += __shfl_xor_sync(~0u, sx, 2); sy += __shfl_xor_sync(~0u, sy, 2);
      sx = rcp(sx); sy = rcp(sy);
      x0 *= sx; x1 *= sx; y0 *= sy; y1 *= sy;
      const uint32_t px = pack_bf16(x0, x1), py = pack_bf16(y0, y1);
      pf[h][0] = px & um; pf[h][1] = px & ~um; pf[h][2] = py & um; pf[h][3] = py & ~um;
    }
#pragma unroll
    for (int u = 0; u < 4; u++) {
#pragma unroll
      for (int e = 0; e < 4; e++) { c[2 * u][e] = 0.f; c[2 * u + 1][e] = 0.f; }
      mma8(c[2 * u], ha[8 + 2 * u], ha[9 + 2 * u], pf[u >> 1][0]);
      mma8(c[2 * u + 1], lo[16 + 2 * u], lo[17 + 2 * u], pf[u >> 1][2]);
    }
#pragma unroll
    for (int u = 0; u < 4; u++) {
      mma8(c[2 * u], lo[16 + 2 * u], lo[17 + 2 * u], pf[u >> 1][1]);
      mma8(c[2 * u + 1], hi[16 + 2 * u], hi[17 + 2 * u], pf[u >> 1][3]);
    }
    uint32_t dep = 0;
    last();
#pragma unroll
    for (int u = 0; u < (EFIRST == 3 ? 0 : 8); u++) dep |= __float_as_uint(c[u][0]);
    asm volatile("bar.sync %0, 256;" ::"r"(3 + (dep & zero)) : "memory");
  }
  __device__ __forceinline__ void E(Pipe& M, bool urgent) {
#pragma unroll
    for (int u = 0; u < 4; u++)
      asm volatile("stmatrix.sync.aligned.m8n8.x4.trans.shared.b16 [%0], {%1, %2, %3, %4};" ::"r"(box_addr(hslot, M.bo, u)),
                   "r"(pack_bf16(c[2 * u][0], c[2 * u][1])), "r"(pack_bf16(c[2 * u + 1][0], c[2 * u + 1][1])),
                   "r"(pack_bf16(c[2 * u][2], c[2 * u][3])), "r"(pack_bf16(c[2 * u + 1][2], c[2 * u + 1][3])) : "memory");
    __syncwarp();
    arrive_n(SB + (urgent ? BAR_STG + M.w * 8 : BAR_SRV + M.w * 16 + 8), M.l0);
  }
};

__device__ __forceinline__ void epi_res(const float (&acc)[64], const float (&pre)[64], float sc0, float sc1, uint32_t (&xr)[32], Pipe& M, int wp) {
  Pipe T = M;
  const uint32_t buf0 = T.take(), buf1 = T.take();
#pragma unroll
  for (int u = 0; u < 8; u++) {
#pragma unroll
    for (int nb = 2 * u; nb < 2 * u + 2; nb++) {
      xr[2 * nb] = pack_bf16(fmaf(acc[4 * nb], sc0, pre[2 * nb]), fmaf(acc[4 * nb + 1], sc0, pre[32 + 2 * nb]));
      xr[2 * nb + 1] = pack_bf16(fmaf(acc[4 * nb + 2], sc1, pre[2 * nb + 1]), fmaf(acc[4 * nb + 3], sc1, pre[33 + 2 * nb]));
    }
    stsm4(box_addr(u < 4 ? buf0 : buf1, M.bo, u & 3), xr[4 * u], xr[4 * u + 1], xr[4 * u + 2], xr[4 * u + 3]);
    if (u == 3) M.signal_loader();
  }
  __syncwarp();
  arrive_n(SB + BAR_STG2 + M.w * 8, M.l0);
  fence_async_smem();
  if (!NWB) wg_bar(M.w);
}
__device__ __forceinline__ void presum(float (&pre)[64], int lane, float usebias) {
  const uint32_t bias = SB + OFF_VEC + (lane & 3) * 8;
#pragma unroll
  for (int nb = 0; nb < 16; nb++) {
    const float2 b = lds64(bias + nb * 32);
#pragma unroll
    for (int u = 2 * nb; u < 2 * nb + 2; u++) {
      const uint32_t v = __float_as_uint(pre[u]);
      pre[32 + u] = fmaf(b.y, usebias, bf_hi(v)); pre[u] = fmaf(b.x, usebias, bf_lo(v));
    }
  }
}
template <int S, int Q> __device__ __forceinline__ void pack_relu(uint32_t (&o)[Q], const float (&acc)[S]) {
#pragma unroll
  for (int u = 0; u < Q; u++) asm("cvt.rn.relu.bf16x2.f32 %0, %1, %2;" : "=r"(o[u]) : "f"(acc[2 * u + 1]), "f"(acc[2 * u]));
}
__device__ __forceinline__ uint32_t sq_bf16x2(uint32_t a) { uint32_t d; asm("mul.rn.bf16x2 %0, %1, %1;" : "=r"(d) : "r"(a)); return d; }
template <int Q> __device__ __forceinline__ void ffn_stage(const uint32_t (&o)[Q], int i, Pipe& M) {
  i -= M.w;
  if (i == 1 || i == 4 || i == 7 || (Q == 64 && i == 10)) {
    const uint32_t buf = M.wait_ahead(2 - M.w);
#pragma unroll
    for (int b = 0; b < Q / 16; b++)
      if (i == 3 * b + 1) {
#pragma unroll
        for (int u = 4 * b; u < 4 * b + 4; u++)
          stsm4(box_addr(buf, M.bo, u & 3), sq_bf16x2(o[4 * u]), sq_bf16x2(o[4 * u + 1]), sq_bf16x2(o[4 * u + 2]), sq_bf16x2(o[4 * u + 3]));
      }
    M.signal_server((i & 1) ^ (Q == 64));
  }
}

__device__ __forceinline__ void wait_flags(const uint8_t* f, uint32_t tag, int lane) {
  const uint32_t t4 = (tag & 0xff) * 0x01010101u;
  const uint32_t* fp = reinterpret_cast<const uint32_t*>(f) + (lane & (FG / 4 - 1));
  while (__any_sync(~0u, __vsub4(ld_relaxed(fp), t4) & 0x80808080u)) {}
  asm volatile("fence.acquire.gpu;\nfence.proxy.async.global;" ::: "memory");
}
__device__ __forceinline__ uint32_t get_epoch() { mbar_spin(SB + BAR_EPOCH, 0); return __shfl_sync(~0u, lds32(SB + OFF_HOLD + 8), 0); }
__device__ __forceinline__ void aloader(const Params& P, const Ptrs& Q, int bid, int r, int j, int lane, int w, uint32_t e, uint32_t epoch) {
  const uint32_t abase = SB + OFF_A + w * NA * 8192, fbase = SB + BAR_FULLA + w * NA * 8, ebase = SB + BAR_EMPTYA + w * NA * 8;
  uint32_t slot = NPRO, ph = 1, nst = 0, hph = 0, npace = 0;
  int t = -1, kind = -1, a0 = 0, a1 = 0;
  const CUtensorMap* tmA = nullptr;
  uint64_t pol = 0;
  uint4* hin = Q.s->halo[0][0] + (r * 16 + j * 2 + w - 16) * 136;
  uint32_t* const pace = Q.s->pace[0] + (bid & -PG) * 4;
  const uint8_t* const flags = Q.s->flags[r / (FG / 8)][w];
  auto adv = [&] { if (++slot == NA) { slot = 0; ph ^= 1; } };
#pragma unroll 1
  for (int g = NPRO; g <= NSTEP; g++) {
    const uint32_t cur = e;
    e = c_sched.v[j][g + 1];
    if (!(cur & E_RARE)) {
      if (cur & E_HAND) { mbar_spin(ebase + slot * 8, ph); e_arrive(fbase + slot * 8, 1); adv(); }
    } else {
      if (cur & F_NEW) {
        t++; kind = kind == 5 ? 0 : kind + 1;
        const bool narrow = kind == 2 || kind == 5;
        static_assert(TM_XIN == 0 && TM_X == 1 && TM_XA == 2 && TM_O == 3 && TM_H == 4, "map order");
        tmA = &P.tm[t < 2 ? 0 : (0x422311 >> (4 * kind)) & 15];
        pol = ((AEF >> t) & 1) ? 0x12F0000000000000ull : 0x1000000000000000ull;
        a0 = narrow ? 0 : w * 1024; a1 = narrow ? r * 128 + w * 64 : r * 64;
      }
      const bool xo = cur & E_XPUB0;
      uint32_t s = slot;
      if (cur & (E_HAND | E_ATTN | E_XPUB0)) {
        if (cur & E_KEEP) e_arrive(ebase + slot * 8, 4);
#pragma unroll 1
        for (int u = xo ? 0 : 1; u < 2; u++) { mbar_wait(ebase + slot * 8, ph); e_arrive(fbase + slot * 8, 1); adv(); }
      }
      uint32_t hold = 0;
      int lag = 0;
      if ((xo && t < 12) || (cur & F_GATH)) {
        uint32_t v;
        uint32_t v1;
        do asm volatile("ld.relaxed.gpu.global.v2.u32 {%0, %1}, [%2];" : "=r"(v), "=r"(v1) : "l"(pace + npace + (lane & (PG - 1)) * 2) : "memory");
        while (__any_sync(~0u, ((v ^ (epoch * 16 + t - 1)) | (v ^ v1)) & 31));
        v += v1;
        npace ^= PG * 2;
        lag = min((int)(v - __shfl_sync(~0u, v, bid & (PG - 1))), 8000) * 27 >> 5;
        hold = __reduce_max_sync(~0u, lag);
        asm volatile("st.shared.b32 [%0], %1;" ::"r"(SB + OFF_HOLD + w * 4), "r"(hold) : "memory");
      }
      if (cur & (E_ATTN | E_XPUB0)) {
        const uint32_t s2 = s == NA - 1 ? 0 : s + 1;
        mbar_wait(SB + BAR_STG + w * 8, nst & 1);
        nst++;
        LT(0);
        const uint32_t c1 = clock32();
        e_store(tmA, a0 + sched_k(cur), a1, abase + s * 8192);
        if (xo) {
          if (!LATE2 || t == 12) {
            mbar_spin(SB + BAR_STG2 + w * 8, ~t & 1);
            e_store(tmA, a0 + sched_k(cur) + 64, a1, abase + s2 * 8192);
          }
          if (t == 12) break;
          if (NPD) {
#pragma unroll 1
            for (int u = 0; u < NPD; u++) {
              const int c = u + (u >= j);
              spin_until(c1 + SDP + __shfl_sync(~0u, lag, Q44 ? c * 4 + (bid & 3) : c * 2 + (bid & 1)));
              e_load(abase + slot * 8192, tmA, a0 + c * 128, a1, fbase + slot * 8, pol);
              adv();
            }
            g += NPD + 1;
            e = c_sched.v[j][g + 1];
          }
          if (LATE2) {
            mbar_spin(SB + BAR_STG2 + w * 8, ~t & 1);
            e_store(tmA, a0 + sched_k(cur) + 64, a1, abase + s2 * 8192);
          }
        } else e_arrive(SB + BAR_OWN + w * 8, 1);
        LT(1);
        spin_until(c1 + hold + (xo ? SDELAY : SDELAYO));
        LT(2);
        LT(5);
      }
      if (cur & E_SIG) {
        e_arrive(SB + BAR_SRV + w * 16, 4);
      }
      if (cur & E_REL) bulk_wait_all();
      if (cur & E_HALO) {
        mbar_spin(SB + BAR_STG + w * 8, nst & 1);
        nst++;
        const uint32_t hs = abase + (slot >= 3 ? slot - 3 : slot + 3) * 8192, ad = hs + lane * 32 + (lane & 4) * 4;
        if (r == 0) {
#pragma unroll
          for (int p = 0; p < 4; p++) sts128(hs + lane * 16 + p * 512, 0, 0, 0, 0);
          asm volatile("st.shared.b32 [%0], %1;" ::"r"(SB + OFF_RSTD + w * 288 + (lane & 7) * 4), "r"(0x3f800000) : "memory");
        } else {
          spin_until(clock32() + HDELAY);
          do {
            halo_fetch(hs, w, hin, SB + BAR_SPEC + 80 + w * 8);
            mbar_spin(SB + BAR_SPEC + 80 + w * 8, hph);
            hph ^= 1;
          } while (__any_sync(~0u, min(min(lds32(ad), lds32(ad + 1024)), lds32(SB + OFF_RSTD + w * 288)) == 0));
        }
        e_arrive(SB + BAR_HALO + w * 8, 1);
      }
      if ((cur & E_REL) && (kind == 1 || kind == 2) && r > 0) {
        uint4* hz = hin + lane;
        hin += 256 * 136;
#pragma unroll
        for (int p = 0; p < 4; p++) hz[p * 32] = make_uint4(0, 0, 0, 0);
        if (lane < 2) hz[128] = make_uint4(0, 0, 0, 0);
      }
      if (cur & E_WAIT) {
        wait_flags(flags + ((cur & E_PART1) ? FG : 0), epoch * 16 + t, lane);
      }
    }
    if (!(cur & (F_AUG | F_NOA))) {
      mbar_wait(ebase + slot * 8, ph);
      e_load(abase + slot * 8192, tmA, a0 + sched_k(cur), a1, fbase + slot * 8, pol);
      adv();
      if ((cur & F_STAMP) && (ST2W || w == 0)) {
        if (!ST2W) mbar_spin(SB + BAR_EMPTYB + ((g - 6) & 7) * 8, ((g - 6) >> 3) & 1);
        uint32_t stamp;
        asm volatile("mov.u32 %0, %%globaltimer_lo;" : "=r"(stamp));
        asm volatile("st.relaxed.gpu.global.u32 [%0], %1;" ::"l"(pace + npace + (ST2W ? (bid & (PG - 1)) * 2 + w : bid & (PG - 1))), "r"((stamp & ~31u) | ((epoch * 16 + t) & 31)) : "memory");
      }
    }
  }
  bulk_wait_all();
}

__device__ __forceinline__ void bloader(const Params& P, const Ptrs& Q, bool aux, int j, int lane, uint32_t e, uint32_t epoch) {
  const uint32_t* const sched = c_sched.v[aux ? 8 : j];
  int kind = -1, c2 = 0, c3 = 0, na = 0;
  const CUtensorMap* tmB = nullptr;
  uint32_t sph = 0, efm = aux ? 0 : BEF * 2;
  uint64_t pol = 0;
#pragma unroll 1
  for (int g = aux ? 8 + (j & 1) : NPRO; g < (aux ? NSTEP_AUX : NSTEP); g += 1 + aux) {
    const uint32_t cur = e;
    e = sched[g + 1 + aux];
    if (cur & F_NEW) {
      kind = kind == 5 ? 0 : kind + ((cur >> 29) & 3);
      static_assert(TM_WQKV == 5 && TM_WO == 6 && TM_W1A == 7 && TM_W1B == 8 && TM_W2 == 9, "map order");
      tmB = &P.tm[(0x978655 >> (4 * kind)) & 15];
      efm >>= 1;
      pol = (efm & 1) ? 0x12F0000000000000ull : 0x1000000000000000ull;
      na = (0x243233 >> (4 * kind)) & 15;
      c2 = ((0x277200 >> (4 * kind)) & 15) * j + (kind == 4 ? 3 : 0);
      c3 = kind <= 1 ? kind * 8 + j : 0;
    }
    const int need = g - (int)((cur >> 5) & 15);
    const uint32_t dst = SB + OFF_B + (cur & 31) * 8192, bar = SB + BAR_FULLB + (g & 7) * 8;
    mbar_wait(SB + BAR_EMPTYB + (need & 7) * 8, (need >> 3) & 1);
    if (!(cur & F_AUG)) {
      asm volatile("{\n.reg .pred p;\nelect.sync _|p, 0xffffffff;\n@p mbarrier.arrive.expect_tx.shared::cta.b64 _, [%2], %7;\n"
                   "@p cp.async.bulk.tensor.4d.shared::cluster.global.mbarrier::complete_tx::bytes.L2::cache_hint [%0], [%1, {%3, %4, %5, %6}], [%2], %8;\n}"
                   ::"r"(dst), "l"(tmB), "r"(bar), "r"(0), "r"(sched_k(cur)), "r"(c2), "r"(c3), "r"(na * 8192), "l"(pol) : "memory");
    } else {
      const bool chk = g < NSTEP / 2;
      const uint32_t b2 = chk ? SB + BAR_AUG : bar, ad = dst + lane * 16 + (lane >> 3) * 4;
      while (true) {
        asm volatile("{\n.reg .pred p;\nelect.sync _|p, 0xffffffff;\n@p mbarrier.arrive.expect_tx.shared::cta.b64 _, [%2], 4096;\n"
                     "@p cp.async.bulk.shared::cluster.global.mbarrier::complete_tx::bytes [%0], [%1], 4096, [%2];\n}"
                     ::"r"(dst), "l"(Q.s->aug[epoch & 1][(kind - (kind >= 3)) * 8 + j]), "r"(b2) : "memory");
        if (!chk) break;
        mbar_spin(b2, sph);
        sph ^= 1;
        uint32_t mn = ~0u;
#pragma unroll
        for (int u = 0; u < 8; u++) mn = min(mn, lds32(ad + u * 512));
        if (!__any_sync(~0u, mn == 0)) { e_arrive(bar, 1); break; }
      }
      __syncwarp();
    }
  }
}

constexpr uint32_t job_slots(int layer) {
  const int pos[10] = {11, 26, 63, 73, 77, 81, 92, 96, 100, 104};
  uint32_t v = 0;
  for (int m = 0; m < 10; m++) v |= (uint32_t)((layer * 148 + pos[m]) % NA) << (3 * m);
  return v;
}
constexpr uint32_t JOB_SLOTS0 = job_slots(0), JOB_SLOTS1 = job_slots(1);
__device__ __forceinline__ void server(const Params& P, const Ptrs& Q, int bid, int r, int j, int lane, uint32_t epoch) {
  if (CPF) spin_until(clock32() + CPF);
  epoch += __shfl_sync(~0u, c_sched.v[j][lane < 18 ? lane * 16 : 0] >> 31, 0);
  {
    const uint2 b = reinterpret_cast<const uint2*>(Q.b2 + j * 128)[lane];
    sts128(SB + OFF_VEC + lane * 16, b.x << 16, b.x & 0xffff0000u, b.y << 16, b.y & 0xffff0000u);
  }
  int hl = 0;
  uint32_t fph = 0, pend = SB + BAR_DUMMY3;
#pragma unroll 1
  for (int n = 0; n < 20; n++) {
    const int layer = n >= 10, m = n - 10 * layer;
    const bool stat = m == 0 || m == 2;
    const uint32_t slot = ((layer ? JOB_SLOTS1 : JOB_SLOTS0) >> (m * 3)) & 7;
    auto fetch = [&](int w) {
      asm volatile("{\n.reg .pred p;\nelect.sync _|p, 0xffffffff;\n@p mbarrier.arrive.expect_tx.shared::cta.b64 _, [%2], 4096;\n"
                   "@p cp.async.bulk.shared::cluster.global.mbarrier::complete_tx::bytes [%0], [%1], 4096, [%2];\n}"
                   ::"r"(SB + OFF_A + (w * NA + slot) * 8192), "l"(&Q.s->stats[hl][r * 32 + w * 16][0][0]), "r"(SB + BAR_SPEC + 64 + w * 8) : "memory");
    };
#pragma unroll 1
    for (int w = 0; w < 2; w++) {
      mbar_spin(SB + BAR_SRV + w * 16 + (n & 1) * 8, (n >> 1) & 1);
      if (stat) fetch(w);
      else {
        e_store(&P.tm[m == 1 ? TM_O : TM_H], m == 1 ? j * 64 : 448 * j + (m - 3) * 64, r * 128 + w * 64, SB + OFF_A + (w * NA + slot) * 8192);
        bulk_wait_read<1>();
        e_arrive(pend, 4);
        pend = SB + BAR_EMPTYA + (w * NA + slot) * 8;
      }
    }
    if (stat) {
#pragma unroll 1
      for (int w = 0; w < 2; w++) {
        const uint32_t src = SB + OFF_A + (w * NA + slot) * 8192 + (lane >> 1) * 256 + ((lane >> 1) & 7) * 32 + (lane & 1) * 16;
        float ms[2], md[2], mq[2], m0[2];
        while (true) {
          mbar_spin(SB + BAR_SPEC + 64 + w * 8, (fph >> w) & 1);
          fph ^= 1u << w;
          uint32_t bad = 0;
          ms[0] = ms[1] = md[0] = md[1] = mq[0] = mq[1] = m0[0] = m0[1] = 0.f;
#pragma unroll 1
          for (int p = 0; p < 8; p += 2) {
            const float4 v2[2] = {lds128(src ^ (p * 32)), lds128(src ^ (p * 32) ^ 32)};
            if (p == 0) { m0[0] = v2[0].x; m0[1] = v2[0].z; }
#pragma unroll
            for (int z = 0; z < 2; z++) {
              const float4 v = v2[z];
              const float a = v.x - m0[0], b = v.z - m0[1];
              bad |= __float_as_uint(v.y) ^ epoch;
              ms[0] += a; md[0] = fmaf(a, a, md[0]); mq[0] += __uint_as_float(__float_as_uint(v.y) & ~63u);
              ms[1] += b; md[1] = fmaf(b, b, md[1]); mq[1] += v.w;
            }
          }
          if (!__any_sync(~0u, bad & 63)) break;
          fetch(w);
          __syncwarp();
        }
        e_arrive(SB + BAR_EMPTYA + (w * NA + slot) * 8, 4);
        const int row = (lane >> 3) * 16 + (lane & 7);
#pragma unroll
        for (int z = 0; z < 2; z++) {
          const float d = ms[z] * 0.125f;
          asm volatile("st.shared.f32 [%0], %1;" ::"r"(SB + OFF_MEAN + (w * 64 + row + z * 8) * 4), "f"(m0[z] + d) : "memory");
          const float rs = rsq(fmaf(mq[z], 1.f / 1024.f, fmaxf(fmaf(md[z], 0.125f, -d * d), 0.f)) + 1e-5f);
          asm volatile("st.shared.f32 [%0], %1;" ::"r"(SB + OFF_RSTD + (w * 72 + 8 + row + z * 8) * 4), "f"(rs) : "memory");
          if (RSV && z && !m && lane >= 24) {
            float* const h = reinterpret_cast<float*>(Q.s->halo[0][0] + 122) + (uint32_t)((hl * 256 + r * 16 + j * 2 + w) * 544 + lane);
            h[0] = h[256 * 544] = rs != 0.f ? rs : -0.f;
          }
        }
        e_arrive(SB + BAR_STAT + w * 8, 8);
      }
    }
    if (stat && n != 12) {
#pragma unroll 1
      for (int u = 0; u < (m ? 2 : 3); u++) {
        const uint32_t pitch = u == 2 ? 448 : 128;
        uint4* p = reinterpret_cast<uint4*>(u == 2 ? Q.s->h : (m ? Q.out : Q.s->x)) + (u == 2 ? 64 + j * 8 : j * 16 + u * 8) + ((r * 128 + (lane >> 3)) * pitch + (lane & 7));
#pragma unroll 1
        for (int k = 0; k < 32 / FUN; k++) {
#pragma unroll
          for (int z = 0; z < FUN; z++) {
            *p = make_uint4(~0u, ~0u, ~0u, ~0u);
            p += 4 * pitch;
            asm volatile("" : "+l"(p));
          }
        }
      }
      __syncwarp();
    }
    if ((0x222 >> m) & 1) {
      bulk_wait_all();
      e_arrive(pend, 4);
      pend = SB + BAR_DUMMY3;
      if (lane < 2) st_release8(&Q.s->flags[r / (FG / 8)][lane][(r & (FG / 8 - 1)) * 8 + j + (m == 9 ? FG : 0)], epoch * 16 + layer * 6 + (m == 1 ? 2 : 5));
      __syncwarp();
    }
    hl += stat;
  }
}

__device__ __forceinline__ void aux_math(const Ptrs& Q, int bid, int jj, int warp, int lane) {
  const int g = lane >> 2, q = lane & 3, c0 = (warp & 3) * 2;
  uint32_t st = warp >> 2, bf[16][4] = {};
  const uint32_t ad0 = SB + ((lane >> 4) * 8 + (lane & 7)) * 128 + (((c0 + ((lane >> 3) & 1)) ^ (lane & 7)) << 4);
#pragma unroll 1
  for (int t = 0; t < 4; t++) {
    float acc[4][4] = {};
    uint32_t bias[8];
#pragma unroll
    for (int a = 0; a < 8; a++) bias[a] = t >= 2 ? reinterpret_cast<const uint32_t*>(Q.b1 + 448 * jj + (t - 2) * 192 + c0 * 8)[(a >> 1) * 32 + (a & 1) * 4 + q] : 0u;
#pragma unroll 1
    for (int i = 0; i < 16; i++, st += 2) {
      const uint32_t ad = ad0 + (c_sched.v[8][st] & 31) * 8192;
      mbar_spin(SB + BAR_FULLB + (st & 7) * 8, (st >> 3) & 1);
#pragma unroll
      for (int u = 0; u < 16; u++)
        asm volatile("{\n.reg .pred p;\nsetp.ne.u32 p, %5, 0;\n@p ldmatrix.sync.aligned.m8n8.x4.trans.shared.b16 {%0,%1,%2,%3}, [%4];\n}"
                     : "+r"(bf[u][0]), "+r"(bf[u][1]), "+r"(bf[u][2]), "+r"(bf[u][3])
                     : "r"(ad + (u & 3) * 8192 + (u >> 2) * 2048), "r"((u & 3) != 3 || t == 3 ? 1 : 0) : "memory");
      __syncwarp();
      e_arrive(SB + BAR_EMPTYB + (st & 7) * 8, 2);
#pragma unroll
      for (int u = 0; u < 16; u++) mma16(acc[u & 3], bf[u][0], bf[u][1], bf[u][2], bf[u][3], 0x3F803F80u, 0x3F803F80u);
    }
    const uint32_t epoch = lds32(SB + OFF_HOLD + 8);
    const uint32_t o = (t * 8 + jj) * 1024 + g * 32 + ((c0 ^ g) << 2) + q + (epoch & 1) * 32768;
    uint32_t *const p0 = Q.s->aug[0][0] + o, *const p1 = Q.s->aug[0][0] + (o ^ 4);
#pragma unroll
    for (int a = 0; a < 8; a++) {
      const float u = acc[a >> 1][(a & 1) * 2];
      uint32_t h = movm(pack_bf16(u, u - bf_round(u)));
      if (g >= 6) h = bias[a];
      ((a & 1) ? p1 : p0)[(a >> 1) * 256] = h ? h : 0x8000u;
    }
    uint4* const z = reinterpret_cast<uint4*>(Q.s->aug[~epoch & 1][t * 8 + jj]) + (threadIdx.x & 127);
    z[0] = z[128] = make_uint4(0, 0, 0, 0);
  }
}

template <bool BYSM> __global__ void __launch_bounds__(NTHREADS, 1) mega_kernel(const __grid_constant__ Ptrs Q, const __grid_constant__ Params P) {
  extern __shared__ __align__(1024) uint8_t smem_raw[];
  constexpr uint32_t sb = SB;
  const uint32_t centry = clock32();
  const int warp = __shfl_sync(~0u, threadIdx.x >> 5, 0), lane = threadIdx.x & 31;
  const int bid = BYSM ? work_id() : blockIdx.x;
  const bool aux = bid >= NMAIN;
  const int r = Q44 ? ((bid >> 5) << 2) | (bid & 3) : ((bid >> 4) << 1) | (bid & 1), j = (aux ? bid * 2 : bid >> (1 + Q44)) & 7;
  PRO(0);
  {
    const uint32_t b = sb + OFF_BAR + warp * 48, cnt = warp < 6 ? 1 : (warp < 10 ? 4 : 8);
    asm volatile("{\n.reg .pred p;\nelect.sync _|p, 0xffffffff;\n@p mbarrier.init.shared::cta.b64 [%0], %1;\n@p mbarrier.init.shared::cta.b64 [%0 + 8], %1;\n"
                 "@p mbarrier.init.shared::cta.b64 [%0 + 16], %1;\n@p mbarrier.init.shared::cta.b64 [%0 + 24], %1;\n"
                 "@p mbarrier.init.shared::cta.b64 [%0 + 32], %1;\n@p mbarrier.init.shared::cta.b64 [%0 + 40], %1;\nfence.mbarrier_init.release.cluster;\n}"
                 ::"r"(b), "r"(cnt) : "memory");
  }
  __syncthreads();
  {
    static_assert(NPRO == 4 && ROUND0 == 0, "prologue stages");
    const int st = ((11 - warp) * (aux ? 32 : 11)) >> 5, op = aux ? (st < 8) * 2 : 11 - warp - 3 * st, sd = aux ? st >> STGX : (op == 2 ? st : st & 2);
    const uint32_t bar0 = sb + OFF_BAR + (op * 6 + st) * 8;
    const int kc = aux ? (st >> 1) * 64 : (st & 2 ? (ROUND1 >> (4 * j)) & 15 : 0) * 128 + (st & 1) * 64;
    spin_until(centry + (sd ? STG0 + sd * STG1 : 0));
    if (op == 2) {
      asm volatile("{\n.reg .pred p;\nelect.sync _|p, 0xffffffff;\n@p mbarrier.arrive.expect_tx.shared::cta.b64 _, [%2], 24576;\n"
                   "@p cp.async.bulk.tensor.4d.shared::cluster.global.mbarrier::complete_tx::bytes [%0], [%1, {%3, %4, %3, %5}], [%2];\n}"
                   ::"r"(sb + OFF_B + (aux ? (st & 1) * 114688 + (st >> 1) * 24576 : (st + 1) * 24576)), "l"(&P.tm[TM_WQKV]), "r"(bar0), "r"(0), "r"(kc), "r"(j + (st & aux)) : "memory");
    } else if (!aux) e_load(sb + OFF_A + (op * 6 + st) * 8192, &P.tm[TM_XIN], op * 1024 + kc, r * 64, bar0);
    PRO(1);
    asm volatile("prefetch.tensormap [%0];" ::"l"(&P.tm[warp]) : "memory");
  }
  if (warp >= 8) {
    asm volatile("setmaxnreg.dec.sync.aligned.u32 24;");
    if (warp == 11) {
      if (smem_u32(smem_raw) != SB) __trap();
      const uint32_t epoch = __shfl_sync(~0u, ld_relaxed(&Q.s->epoch[bid]) + 1, 0);
      Q.s->epoch[bid] = epoch;
      asm volatile("st.shared.b32 [%0], %1;" ::"r"(sb + OFF_HOLD + 8), "r"(epoch) : "memory");
      e_arrive(sb + BAR_EPOCH, 1);
      PRO(2);
      if (!aux) server(P, Q, bid, r, j, lane, epoch);
    } else {
      const uint32_t e = c_sched.v[aux ? 8 : j][aux ? warp : NPRO];
      spin_until(centry + STGL + (e >> 31));
      PRO(2);
      const uint32_t epoch = get_epoch();
      PRO(3);
      if (warp <= 8 + aux) bloader(P, Q, aux, j + warp - 8, lane, e, epoch);
      else if (!aux) aloader(P, Q, bid, r, j, lane, warp - 9, e, epoch);
    }
  } else if (aux) aux_math(Q, bid, j + (warp >> 2), warp, lane);
  else {
    asm volatile("setmaxnreg.inc.sync.aligned.u32 240;");
    const int w = warp >> 2, wp = warp & 3;
    {
      uint32_t xr[32];
#pragma unroll
      for (int u = 0; u < 32; u++) if (NOI) asm volatile("" : "=r"(xr[u])); else xr[u] = 0;
      Pipe M;
      M.db = 0; M.g8 = 0; M.a8 = w * NA * 8; M.pa = 0; M.tph = 0; M.aend = (w + 1) * NA * 8;
      M.h0 = gridDim.y * 0x40000040u; M.h1 = gridDim.z * 0x40000040u;
      M.curB = M.curA = M.prevB = M.prevA = M.sph = 0; M.nx = make_uint2(0, 0); M.w = w; M.l0 = lane == 0;
      M.bo = (wp * 16 + (lane & 15)) * 128 + (((lane >> 4) ^ (lane & 7)) << 4);
      M.so = __shfl_sync(~0u, SB + OFF_A + wp * 2048 + lane * 32 + (lane >> 2) * 4, lane);
      M.bo = __shfl_sync(~0u, M.bo, lane);
      auto nop = [](int) {};
      const uint32_t zero = gridDim.y - 1;
      PROF_T(w, 0, 3);
      if (STARTC) spin_until(centry + STARTC);
#pragma unroll 1
      for (int hl = 0; hl < 4; hl++) {
        const int t0 = hl * 3;
        const bool ffn = hl & 1;
        float acc[96], acn[64];
        uint32_t au[2] = {0u, 0u};
        {
          const int d = hl ? 0 : ((OWNP * 2u) >> (4 * j)) & 15;
          auto own = [&](auto h, uint32_t dep = 0) {
#pragma unroll
            for (int u = 4 * h.v; u < 4 * h.v + 4; u++)
              asm volatile("ldmatrix.sync.aligned.m8n8.x4.shared.b16 {%0,%1,%2,%3}, [%4];" : "=r"(xr[4 * u]), "=r"(xr[4 * u + 1]), "=r"(xr[4 * u + 2]), "=r"(xr[4 * u + 3])
                           : "r"(box_addr(sb + OFF_A + M.a8 * 1024, M.bo + dep, u & 3)) : "memory");
          };
          M.begin<192>(acc, ffn ? 12 : 3, t0, [&](int) { if (hl + d == 0) own(IC<0>{}); });
          if (hl + d == 0) own(IC<1>{}, (xr[0] | xr[4] | xr[8] | xr[12]) & zero);
          float ss[2] = {0.f, 0.f}, sq[2] = {0.f, 0.f};
          auto part = [&](auto c0, auto n) {
#pragma unroll
            for (int v = 0; v < 4 * n.v; v++) {
              const int u = c0.v + v / n.v * 4 + v % n.v;
              float a, b;
              asm volatile("shl.b32 %0, %2, 16;\nand.b32 %1, %2, 0xffff0000;" : "=f"(a), "=f"(b) : "r"(xr[u]));
              ss[u & 1] += a + b; sq[u & 1] = fmaf(a, a, fmaf(b, b, sq[u & 1]));
            }
          };
          const uint64_t plan = hl ? PLAN1 : (d ? PLAN0 : PLANZ);
          auto todo = [&](int i) { uint64_t v; asm volatile("shr.u64 %0, %1, %2;" : "=l"(v) : "l"(plan), "r"((i + 1 - d) * 8)); return (uint32_t)v; };
          uint32_t m = todo(1);
          M.run<192, false>(acc, 1, 16, 1u << 10, 16 - (ffn ? LEAD3 : LEAD0), [&](int i, uint2 ok) {
           CT(0);
           if (m & 7) {
             if (m & 1) part(IC<0>{}, IC<2>{});
             if (m & 2) part(IC<2>{}, IC<2>{});
             if (m & 4) part(IC<16>{}, IC<1>{});
           }
           CT(1);
           M.ensure(ok);
           CT(3);
           M.validate(hl != 0, &P.tm[ffn ? TM_XA16 : TM_X16], w * 1024, r * 64, wp, j, [&] {
            if (m & 0xf8) {
              if (m & 128) { if (m & 1) own(IC<1>{}); else own(IC<0>{}); }
              if (m & 8) part(IC<17>{}, IC<1>{});
              if (m & 16) part(IC<18>{}, IC<1>{});
              if (m & 32) part(IC<19>{}, IC<1>{});
              if (m & 64) {
                const uint32_t epoch = lds32(sb + OFF_HOLD + 8);
#pragma unroll
                for (int o = 1; o < 4; o *= 2)
#pragma unroll
                  for (int z = 0; z < 2; z++) { ss[z] += __shfl_xor_sync(~0u, ss[z], o); sq[z] += __shfl_xor_sync(~0u, sq[z], o); }
                const float m0 = ss[0] * (1.f / 128.f), m1 = ss[1] * (1.f / 128.f);
                const int rowpair = r * 64 + w * 32 + wp * 8 + (M.lane() >> 2);
                if ((M.lane() & 3) == 0)
                  st_pkt(&Q.s->stats[hl][rowpair >> 1][j][rowpair & 1], __float_as_uint(m0), (__float_as_uint(fmaxf(fmaf(-ss[0], m0, sq[0]), 0.f)) & ~63u) | (epoch & 63),
                         __float_as_uint(m1), __float_as_uint(fmaxf(fmaf(-ss[1], m1, sq[1]), 0.f)));
              }
            }
            m = todo(i + 1);
            if (i == STATI) { mbar_spin(sb + BAR_STAT + w * 8, hl & 1); stats_fetch(w, wp, M.lane(), au); }
           });
           CT(4);
          });
          M.end<192, true>(acc, ffn ? 0 : 4, 15, au[0], au[1], t0);
          PROF_T(w, t0, 2);
        }
        if (!ffn) {
          Attn T;
#pragma unroll 1
          for (int wave = 0; wave < 2; wave++) {
            AP(9);
            uint4* const hp = Q.s->halo[0][0] + (uint32_t)(((hl + wave) * 256 + r * 16 + j * 2 + w) * 136);
            T.A(acc, M, w, wp, r, hp);
            AP(0);
            if (wave == 0) {
              M.begin<192, PACE2 & 1>(acc, 6, t0 + 1);
              M.run<192>(acc, 1, NH1, 4, -1, nop);
              T.B(w, wp, M.lane(), 0);
              M.drain();
            } else {
              M.begin<128, (PACE2 >> 1) & 1>(acn, 12, t0 + 2);
              M.run<128>(acn, 1, NH2, 4, -1, nop);
              T.B(w, wp, M.lane(), 1);
              M.drain();
#pragma unroll
              for (int z = 0; z < 64; z++) asm volatile("mov.b32 %0, %1;" : "=f"(acc[z]) : "f"(acn[z]));
#pragma unroll
              for (int z = 64; z < 96; z++) acc[z] = 0.f;
            }
            AP(2);
            T.C(wp, r, M.lane(), zero, [&] { if (EFIRST == 3 || (EFIRST == 2 && wave)) T.E(M, wave); });
            AP(3);
            if (wave == 1) break;
            M.run<192>(acc, NH1, 16, 1u << 7, 16 - LEAD1, [&](int i) { if (EFIRST < 3 && i == NH1) T.E(M, false); });
            M.end<192, true>(acc, 4, 10, au[0], au[1], t0 + 1);
            PROF_T(w, t0 + 1, 2);
          }
#pragma unroll
          for (int z = 0; z < 64; z++) asm volatile("mov.b32 %0, %1;" : "=f"(acn[z]) : "f"(acc[z]));
          if (EFIRST == 1) T.E(M, true);
          else if (!EFIRST) {
            M.ensure(M.iss<128, false>(acn, false));
            T.E(M, true);
          }
        } else {
          uint32_t pk[48], pk2[64];
          pack_relu(pk, acc);
          {
            float acc2[128];
            M.begin<256, (PACE2 >> 3) & 1>(acc2, 0, t0 + 1);
            M.run<256>(acc2, 1, 16, 0x248, 16 - LEAD4, [&](int i) { ffn_stage(pk, i, M); });
            M.end<256, true>(acc2, 0, 0, au[0], au[1], t0 + 1);
            pack_relu(pk2, acc2);
            PROF_T(w, t0 + 1, 2);
          }
          M.begin<128, (PACE2 >> 4) & 1>(acn, 2, t0 + 2);
          M.run<128>(acn, 1, 13, 0x1248, -1, [&](int i) { ffn_stage(pk2, i, M); });
        }
        {
          float pre[64], rstd[2] = {0.f, 0.f};
#pragma unroll
          for (int u = 0; u < 32; u++) { pre[u] = __uint_as_float(xr[u]); if (!NOI) pre[32 + u] = 0.f; }
          if (NOI) {
#pragma unroll
            for (int u = 32; u < 64; u += 4) { const float4 v = lds128(sb + OFF_VEC); pre[u] = v.x; pre[u + 1] = v.y; pre[u + 2] = v.z; pre[u + 3] = v.w; }
          }
          const int ks = ffn ? 56 : 16, pause = ks - (ffn ? LEAD5 : LEAD2), vfrom = ffn ? 99 : 7;
          M.run<128>(acn, ffn ? 13 : NH2 + !EFIRST, ks, 0, pause, [&](int i) {
            if (i >= vfrom) {
              if (i == 7) mbar_spin(sb + BAR_OWN + w * 8, hl >> 1);
              M.validate(true, &P.tm[TM_O16], 0, r * 128 + w * 64, wp, j, [] {});
            }
          }, w ? (ffn ? (PRE5 ? PRE5 : pause) : (PRE2 ? PRE2 : pause)) : (ffn ? 20 : IPRE), [&](int) { presum(pre, M.lane(), ffn ? 1.f : 0.f); own_rstd(w, wp, M.lane(), rstd); });
          M.end<128, false>(acn, 2, 0, 0, 0, t0 + 2);
          epi_res(acn, pre, ffn ? rstd[0] * rstd[0] : 1.f, ffn ? rstd[1] * rstd[1] : 1.f, xr, M, wp);
          PROF_T(w, t0 + 2, 2);
        }
      }
    }
  }
}

typedef CUresult (*EncFn)(CUtensorMap*, CUtensorMapDataType, cuuint32_t, void*, const cuuint64_t*, const cuuint64_t*, const cuuint32_t*,
                          const cuuint32_t*, CUtensorMapInterleave, CUtensorMapSwizzle, CUtensorMapL2promotion, CUtensorMapFloatOOBfill);

void enc2(EncFn enc, CUtensorMap* tm, const void* p, uint64_t cols, uint64_t rows, uint32_t boxrows = 64, CUtensorMapL2promotion promo = CU_TENSOR_MAP_L2_PROMOTION_L2_128B) {
  cuuint64_t gd[2] = {cols, rows}, gs[1] = {cols * 2};
  cuuint32_t box[2] = {64, boxrows}, es[2] = {1, 1};
  enc(tm, CU_TENSOR_MAP_DATA_TYPE_BFLOAT16, 2, const_cast<void*>(p), gd, gs, box, es, CU_TENSOR_MAP_INTERLEAVE_NONE, CU_TENSOR_MAP_SWIZZLE_128B,
      promo, CU_TENSOR_MAP_FLOAT_OOB_FILL_NONE);
}
void enc4(EncFn enc, CUtensorMap* tm, const void* p, uint64_t K, uint64_t N, uint64_t d2, uint64_t s2, uint64_t d3, uint64_t s3, uint32_t na) {
  cuuint64_t gd[4] = {64, K, d2, d3}, gs[3] = {N * 2, s2, s3};
  cuuint32_t box[4] = {64, 64, na, 1}, es[4] = {1, 1, 1, 1};
  enc(tm, CU_TENSOR_MAP_DATA_TYPE_BFLOAT16, 4, const_cast<void*>(p), gd, gs, box, es, CU_TENSOR_MAP_INTERLEAVE_NONE, CU_TENSOR_MAP_SWIZZLE_128B,
      WPROMO, CU_TENSOR_MAP_FLOAT_OOB_FILL_NONE);
}

}

extern "C" void kernel_launch(void* const* d_in, const int* in_sizes, int n_in, void* d_out, int out_size) {
  static EncFn enc = nullptr;
  static Scratch* ps = nullptr;
  static void (*kernel)(Ptrs, Params) = mega_kernel<true>;
  if (!enc) {
    cudaDriverEntryPointQueryResult qr;
    cudaGetDriverEntryPoint("cuTensorMapEncodeTiled", (void**)&enc, cudaEnableDefault, &qr);
    int dev = 0, nsm = 0;
    cudaGetDevice(&dev);
    cudaDeviceGetAttribute(&nsm, cudaDevAttrMultiProcessorCount, dev);
    if (nsm != NMAIN + NAUX) kernel = mega_kernel<false>;
    cudaFuncSetAttribute(kernel, cudaFuncAttributeMaxDynamicSharedMemorySize, SMEM_BYTES);
    cudaGetSymbolAddress((void**)&ps, g_s);
  }
  Params P;
  Ptrs Q;
  Q.s = ps;
  void *p_h = ps->h, *p_x = ps->x;
  enc2(enc, &P.tm[TM_XIN], d_in[0], 2048, 1024, 64, XPROMO);
  enc2(enc, &P.tm[TM_X], d_out, 2048, 1024);
  enc2(enc, &P.tm[TM_XA], p_x, 2048, 1024);
  enc2(enc, &P.tm[TM_O], p_h, 3584, 2048);
  enc2(enc, &P.tm[TM_H], p_h, 3584, 2048);
  enc2(enc, &P.tm[TM_X16], d_out, 2048, 1024, 16);
  enc2(enc, &P.tm[TM_XA16], p_x, 2048, 1024, 16);
  enc2(enc, &P.tm[TM_O16], p_h, 3584, 2048, 16);
  enc4(enc, &P.tm[TM_WQKV], d_in[1], 1024, 3072, 3, 2048, 16, 128, 3);
  enc4(enc, &P.tm[TM_WO], d_in[2], 1024, 1024, 16, 128, 1, 128, 2);
  enc4(enc, &P.tm[TM_W1A], d_in[4], 1024, 3584, 56, 128, 1, 128, 4);
  enc4(enc, &P.tm[TM_W1B], d_in[4], 1024, 3584, 56, 128, 1, 128, 3);
  enc4(enc, &P.tm[TM_W2], d_in[6], 3584, 1024, 16, 128, 1, 128, 2);
  Q.out = (__nv_bfloat16*)d_out;
  Q.b1 = (const __nv_bfloat16*)d_in[5];
  Q.b2 = (const __nv_bfloat16*)d_in[7];
  kernel<<<NMAIN + NAUX, NTHREADS, SMEM_BYTES, cudaStreamPerThread>>>(Q, P);
}
```

```cpp
#include <cuda_runtime.h>
#include <cuda_bf16.h>
#include <cuda.h>
#include <stdint.h>

#define LEAD0 2
#define LEAD1 1
#define LEAD2 4
#define LEAD3 2
#define LEAD4 1
#define LEAD5 5
#define WPROMO CU_TENSOR_MAP_L2_PROMOTION_L2_128B
#define PLAN1 0x40201008070000ull
#define PLAN0 0x4030020c8180ull
#define PLANZ 0x40300a050000ull
#define VSKIP 1
#define ELA 1
#define LSO 1
#define STATI 13
#define PACE2 0x1a
#define ST2 12
#define STB 3
#define PROBE 4
#define OWNP 0x22221110
#define SIG0 14
#define STGX 2
#define STGM 3
#define NPRO 4
#define XPROMO CU_TENSOR_MAP_L2_PROMOTION_L2_256B
#define IPRE 7
#define FILLT 1
#define EARLYC 1
#define OWNDLY 0
#define EPW 0
#define CPF 5000
#define STG0 800
#define STG1 500
#define STGL (STG0 + 4 * STG1)
#define STGLX 0
#define STARTC 0
#define PRE5 0
#define PRE2 0
#define FUN 4
#define XEF 0
#define BEF 0xff8
#define AEF 0xdb6
#define SEF 0
#define SDELAYO 1000
#define SDELAY 300
#define HDELAY 450
#define Q44 1
#define FG 8
#define ALOOP 0
#define PREV 1
#define TAR 0
#define RSV 0
#define NWB 0
#define AGK 1
#define NOI 1
#define EFIRST 1
#define AUGN 0
#define LEARLY 1
#define NPD 0
#define SDP 900
#define LATE2 0
#define ST2W 1
#define STA 1
#define PG (Q44 ? 32 : 16)
#define NH1 6
#define NH2 3
namespace {

constexpr int NMAIN = 128, NAUX = 4, NTHREADS = 384;
constexpr uint32_t OFF_B = 0;
constexpr uint32_t OFF_A = 131072;
constexpr uint32_t OFF_VEC = 229376;
constexpr uint32_t OFF_BAR = 231424;
constexpr uint32_t OFF_RSTD = OFF_VEC + 512, OFF_MEAN = OFF_VEC + 1088, OFF_HOLD = OFF_VEC + 2032;
constexpr uint32_t SMEM_BYTES = OFF_BAR + 960;
constexpr uint32_t BAR_FULLA = OFF_BAR, BAR_FULLB = OFF_BAR + 96, BAR_OWN = OFF_BAR + 160, BAR_EPOCH = OFF_BAR + 176, BAR_AUG = OFF_BAR + 184, BAR_SPEC = OFF_BAR + 192,
                   BAR_EMPTYA = OFF_BAR + 288, BAR_STG = OFF_BAR + 384, BAR_SRV = OFF_BAR + 400, BAR_LEAD = OFF_BAR + 432, BAR_HALO = OFF_BAR + 440, BAR_STG2 = OFF_BAR + 456,
                   BAR_DUMMY3 = OFF_BAR + 472, BAR_EMPTYB = OFF_BAR + 480, BAR_STAT = OFF_BAR + 544, BAR_DUMMY = OFF_BAR + 560;
constexpr int NA = 6;
constexpr uint32_t SB = 1024;
constexpr uint32_t SPIN_LIMIT = 1u << 22;

enum { TM_XIN = 0, TM_X, TM_XA, TM_O, TM_H, TM_WQKV, TM_WO, TM_W1A, TM_W1B, TM_W2, TM_X16, TM_XA16, TM_O16, TM_COUNT };

struct Scratch;
struct Ptrs {
  Scratch* s;
  __nv_bfloat16* out;
  const __nv_bfloat16* b1;
  const __nv_bfloat16* b2;
};
struct Params { CUtensorMap tm[TM_COUNT]; };

constexpr int NSTEP = 280, NSTEP_AUX = 128;
enum : uint32_t { F_STAMP = 1u << 28, F_GATH = 1u << 15, F_NEW = 1u << 16, F_AUG = 1u << 17, F_NOA = 1u << 18, E_HAND = 1u << 19, E_ATTN = 1u << 20, E_XPUB0 = 1u << 21,
                  E_WAIT = 1u << 22, E_REL = 1u << 23, E_KEEP = 1u << 24, E_PART1 = 1u << 25, E_HALO = 1u << 26,
                  E_SIG = 1u << 27, E_RARE = F_NEW | E_KEEP | (0xfu << 20) | (3u << 26) };
constexpr int own_round(int j) { return (OWNP >> (4 * j)) & 15; }
constexpr uint32_t first_order(int j) {
  uint32_t used = 0, v = 0;
  for (int p = 0; p < 8; p++) {
    int c = own_round(j) == p ? j : -1;
    for (int u = 0; u < 8 && c < 0; u++) if (u != j && !((used >> u) & 1) && own_round(u) < p) c = u;
    if (c < 0 && own_round(j ^ 1) == p) c = j ^ 1;
    for (int u = 0; u < 8 && c < 0; u++) { const int x = (u + (j & 6)) & 7; if (x != j && own_round(x) == p) c = x; }
    used |= 1u << c; v |= (uint32_t)c << (4 * p);
  }
  return v;
}
constexpr uint32_t first_round(int p) { uint32_t v = 0; for (int j = 0; j < 8; j++) v |= ((first_order(j) >> (4 * p)) & 15) << (4 * j); return v; }
constexpr uint32_t ROUND0 = first_round(0), ROUND1 = first_round(1);
struct Sched { uint32_t v[9][NSTEP + 8]; };
constexpr Sched make_sched() {
  Sched T{};
  for (int j = 0; j < 8; j++) {
    int owner[16] = {};
    for (int i = 0; i < 16; i++) owner[i] = -100;
    int p = 0, g = 0;
    for (int t = 0; t < 12; t++) {
      const int kind = t % 6, ks = kind == 5 ? 56 : (kind == 2 ? 16 : 17);
      for (int i = 0; i < ks; i++) {
        const bool augs = ks == 17 && i == 16;
        const int na = (kind == 2 || kind == 5) ? 2 : (augs ? 1 : (kind == 4 ? 4 : 3));
        if (i == 0) p = (0x20cc63 >> (4 * kind)) & 15;
        if (augs) p = (0x0f0af >> (4 * kind)) & 15;
        if (p + na > 16) p = 0;
        int need = g - 8;
        for (int a = p; a < p + na; a++) { if (owner[a] > need) need = owner[a]; owner[a] = g; }
        if (g == 16 && need < AUGN) need = AUGN;
        uint32_t k = i, f = i == (t ? 0 : NPRO) ? F_NEW | (1u << 29) : 0;
        if (augs) { k = 0; f |= F_AUG; }
        else if (kind == 0 || kind == 3) {
          const int o = i - 2;
          if (t == 0) k = ((first_order(j) >> (4 * (i >> 1))) & 15) * 2 + (i & 1);
          else if (i < 2) { k = 2 * j + i; f |= F_NOA | (i == 0 ? E_XPUB0 : 0); }
          else { const int half = o >= 7; int u = o - 7 * half; u += u >= j; k = 2 * u + half; if (i == 6) f |= E_REL; }
          if (i == 11) f |= E_HAND;
          if (i == (t ? 11 : SIG0)) f |= E_SIG;
        } else if (kind == 1 || kind == 4) {
          if (kind == 1) f |= i == 3 ? E_HAND : (i == 8 ? E_HAND | E_KEEP : (i == 5 ? E_HALO : 0));
          if (kind == 1) f |= i == 13 ? E_REL : 0;
          else if (i == 4 || i == 7 || i == 10) f |= E_HAND;
        } else if (kind == 2) {
          f |= i == 0 ? E_WAIT : (i == 3 ? E_HAND : (i == 5 ? E_HALO : 0));
          if (i == 8) { k = 8 + j; f |= E_ATTN | E_KEEP | F_NOA; }
          if (i > 8) k = i - 1 + (i - 9 >= j);
          if (i == 11) f |= E_REL;
        } else {
          k = i < 24 ? (i / 3) * 7 + i % 3 : ((i - 24) / 4) * 7 + 3 + (i - 24) % 4;
          if (i == 4 || i == 7 || i == 10 || i == 13) f |= E_HAND;
          f |= i == 0 ? E_WAIT : (i == 24 ? E_WAIT | E_PART1 : 0);
        }
        if ((kind == 2 || kind == 5) && t < 11 && i == ks - (kind == 2 ? STA : STB)) f |= F_STAMP;
        if (((PACE2 >> kind) & 1) && i == ST2) f |= F_STAMP;
        if (i == 0 && t && ((PACE2 >> ((t - 1) % 6)) & 1)) f |= F_GATH;
        T.v[j][g] = p | ((g - need) << 5) | (k << 9) | f;
        p += na; g++;
      }
    }
    T.v[j][NSTEP] = F_NEW | F_NOA | E_XPUB0 | (2 * j << 9);
  }
  for (int w = 0; w < 2; w++) {
    int owner[14] = {};
    for (int i = 0; i < 14; i++) owner[i] = -100;
    for (int g = w, p = 0; g < NSTEP_AUX; g += 2) {
      const int na = g < 96 ? 3 : 4;
      if (p + na > 14) p = 0;
      int need = g - 8;
      for (int a = p; a < p + na; a++) { if (owner[a] > need) need = owner[a]; owner[a] = g; }
      T.v[8][g] = (p + 14 * w) | ((g - need) << 5) | ((g & 31) >> 1 << 9) | ((g & 30) && g - w != 8 ? 0 : F_NEW | (g - w == 64 ? 2u : 1u) << 29);
      p += na;
    }
  }
  return T;
}
__constant__ Sched c_sched = make_sched();
__device__ __forceinline__ int sched_k(uint32_t e) { return (e >> 3) & 0xfc0; }

struct Scratch {
  __nv_bfloat16 x[2048 * 1024];
  __nv_bfloat16 h[2048 * 3584];
  uint32_t epoch[160];
  uint8_t flags[16][2][64];
  uint32_t pace[8][64];
  uint32_t aug[2][32][1024];
  uint4 stats[4][512][8][2];
  uint4 halo[4][256][136];
};
__device__ __align__(1024) Scratch g_s;
#define PROF_T(w, t, i)
#define PRO(i)
#define LT(i)
#define CT(n)
#define ST(i)
#define AP(i)

__device__ __forceinline__ int work_id() {
  uint32_t smid;
  asm volatile("mov.u32 %0, %%smid;" : "=r"(smid));
  const int t = smid >> 1, u = t - 32, d = (u * 37) >> 8;
  int id = (t & 7) * 16 + (t >> 3) * 2;
  if (t >= 32) id = (1 + u - 7 * d) * 16 + (4 + d) * 2;
  if (t >= 60) id = t < 62 ? t * 2 + 8 : t * 2 - 116;
  return id + (smid & 1);
}

__device__ __forceinline__ uint32_t smem_u32(const void* p) { return (uint32_t)__cvta_generic_to_shared(p); }
__device__ __forceinline__ void mbar_init(uint32_t bar, int cnt) { asm volatile("mbarrier.init.shared::cta.b64 [%0], %1;" ::"r"(bar), "r"(cnt)); }
__device__ __forceinline__ void mbar_expect_tx(uint32_t bar, uint32_t bytes) { asm volatile("mbarrier.arrive.expect_tx.shared::cta.b64 _, [%0], %1;" ::"r"(bar), "r"(bytes) : "memory"); }
__device__ __forceinline__ void mbar_arrive(uint32_t bar, uint32_t cnt) { asm volatile("mbarrier.arrive.shared::cta.b64 _, [%0], %1;" ::"r"(bar), "r"(cnt) : "memory"); }
__device__ __forceinline__ void arrive_n(uint32_t bar, bool) { asm volatile("{\n.reg .pred p;\nelect.sync _|p, 0xffffffff;\n@p mbarrier.arrive.shared::cta.b64 _, [%0];\n}" ::"r"(bar) : "memory"); }
__device__ __forceinline__ void arrive_2(uint32_t b0, uint32_t b1, bool) {
  asm volatile("{\n.reg .pred p;\nelect.sync _|p, 0xffffffff;\n@p mbarrier.arrive.shared::cta.b64 _, [%0];\n@p mbarrier.arrive.shared::cta.b64 _, [%1];\n}" ::"r"(b0), "r"(b1) : "memory");
}
__device__ __forceinline__ void mbar_wait(uint32_t bar, uint32_t parity) {
  asm volatile(
      "{\n.reg .pred p;\n.reg .u32 c;\nmov.u32 c, 0;\n"
      "LAB_WAIT:\nmbarrier.try_wait.parity.shared::cta.b64 p, [%0], %1;\n@p bra.uni DONE;\n"
      "add.u32 c, c, 1;\nsetp.lt.u32 p, c, 4000000;\n@p bra.uni LAB_WAIT;\ntrap;\nDONE:\n}" ::"r"(bar), "r"(parity) : "memory");
}
__device__ __forceinline__ void mbar_spin(uint32_t bar, uint32_t parity) {
  asm volatile("{\n.reg .pred p;\nLAB_WAIT:\nmbarrier.try_wait.parity.shared::cta.b64 p, [%0], %1;\n@!p pmevent 7;\n@!p bra.uni LAB_WAIT;\n}" ::"r"(bar), "r"(parity) : "memory");
}
__device__ __forceinline__ void mbar_spin31(uint32_t bar, uint32_t ph) {
  asm volatile("{\n.reg .pred p;\n.reg .b64 s;\nmov.b64 s, {%1, %1};\nLAB_WAIT:\nmbarrier.try_wait.shared::cta.b64 p, [%0], s;\n@!p pmevent 7;\n@!p bra.uni LAB_WAIT;\n}" ::"r"(bar), "r"(ph) : "memory");
}
__device__ __forceinline__ bool elect_one() {
  uint32_t p;
  asm volatile("{\n.reg .pred P;\nelect.sync _|P, 0xffffffff;\nselp.u32 %0, 1, 0, P;\n}" : "=r"(p));
  return p != 0;
}
__device__ __forceinline__ bool mbar_test(uint32_t bar, uint32_t parity) {
  uint32_t ok;
  asm volatile("{\n.reg .pred p;\nmbarrier.test_wait.parity.shared::cta.b64 p, [%1], %2;\nselp.u32 %0, 1, 0, p;\n}" : "=r"(ok) : "r"(bar), "r"(parity) : "memory");
  return ok != 0;
}
__device__ __forceinline__ void tma_ld2(uint32_t dst, const CUtensorMap* tm, int c0, int c1, uint32_t bar) {
  asm volatile("cp.async.bulk.tensor.2d.shared::cluster.global.mbarrier::complete_tx::bytes [%0], [%1, {%3, %4}], [%2];" ::"r"(dst), "l"(tm), "r"(bar), "r"(c0), "r"(c1) : "memory");
}
__device__ __forceinline__ void tma_ld4(uint32_t dst, const CUtensorMap* tm, int c1, int c2, int c3, uint32_t bar, uint64_t pol = 0x1000000000000000ull) {
  asm volatile("cp.async.bulk.tensor.4d.shared::cluster.global.mbarrier::complete_tx::bytes.L2::cache_hint [%0], [%1, {%3, %4, %5, %6}], [%2], %7;" ::"r"(dst), "l"(tm), "r"(bar), "r"(0), "r"(c1), "r"(c2), "r"(c3), "l"(pol) : "memory");
}
__device__ __forceinline__ void tma_st2(const CUtensorMap* tm, int c0, int c1, uint32_t src) {
  asm volatile("cp.async.bulk.tensor.2d.global.shared::cta.bulk_group [%0, {%2, %3}], [%1];" ::"l"(tm), "r"(src), "r"(c0), "r"(c1) : "memory");
}
__device__ __forceinline__ void bulk_ld(uint32_t dst, const void* src, uint32_t bytes, uint32_t bar) {
  asm volatile("cp.async.bulk.shared::cluster.global.mbarrier::complete_tx::bytes [%0], [%1], %2, [%3];" ::"r"(dst), "l"(src), "r"(bytes), "r"(bar) : "memory");
}
__device__ __forceinline__ void e_arrive(uint32_t bar, uint32_t cnt) {
  if (cnt == 1) asm volatile("{\n.reg .pred p;\nelect.sync _|p, 0xffffffff;\n@p mbarrier.arrive.shared::cta.b64 _, [%0];\n}" ::"r"(bar) : "memory");
  else asm volatile("{\n.reg .pred p;\nelect.sync _|p, 0xffffffff;\n@p mbarrier.arrive.shared::cta.b64 _, [%0], %1;\n}" ::"r"(bar), "r"(cnt) : "memory");
}
template <int BYTES = 8192> __device__ __forceinline__ void e_load(uint32_t dst, const CUtensorMap* tm, int c0, int c1, uint32_t bar, uint64_t pol = 0x1000000000000000ull) {
  asm volatile("{\n.reg .pred p;\nelect.sync _|p, 0xffffffff;\n@p mbarrier.arrive.expect_tx.shared::cta.b64 _, [%2], %5;\n"
               "@p cp.async.bulk.tensor.2d.shared::cluster.global.mbarrier::complete_tx::bytes.L2::cache_hint [%0], [%1, {%3, %4}], [%2], %6;\n}"
               ::"r"(dst), "l"(tm), "r"(bar), "r"(c0), "r"(c1), "n"(BYTES), "l"(pol) : "memory");
}
__device__ __forceinline__ void e_store(const CUtensorMap* tm, int c0, int c1, uint32_t src) {
  asm volatile("{\n.reg .pred p;\nfence.proxy.async.shared::cta;\nelect.sync _|p, 0xffffffff;\n"
               "@p cp.async.bulk.tensor.2d.global.shared::cta.bulk_group [%0, {%2, %3}], [%1];\ncp.async.bulk.commit_group;\n}"
               ::"l"(tm), "r"(src), "r"(c0), "r"(c1) : "memory");
}
__device__ __forceinline__ void bulk_commit() { asm volatile("cp.async.bulk.commit_group;" ::: "memory"); }
template <int N> __device__ __forceinline__ void bulk_wait_read() { asm volatile("cp.async.bulk.wait_group.read %0;" ::"n"(N) : "memory"); }
__device__ __forceinline__ void bulk_wait_all() { asm volatile("cp.async.bulk.wait_group 0;" ::: "memory"); }
__device__ __forceinline__ void fence_async_smem() { asm volatile("fence.proxy.async.shared::cta;" ::: "memory"); }
__device__ __forceinline__ void wg_fence() { asm volatile("wgmma.fence.sync.aligned;" ::: "memory"); }
__device__ __forceinline__ void wg_commit() { asm volatile("wgmma.commit_group.sync.aligned;" ::: "memory"); }
template <int N> __device__ __forceinline__ void wg_wait() { asm volatile("wgmma.wait_group.sync.aligned %0;" ::"n"(N) : "memory"); }
__device__ __forceinline__ void wg_bar(int w) { asm volatile("bar.sync %0, 128;" ::"r"(w + 1) : "memory"); }
__device__ __forceinline__ uint32_t ld_acquire(const uint32_t* p) { uint32_t v; asm volatile("ld.acquire.gpu.global.u32 %0, [%1];" : "=r"(v) : "l"(p) : "memory"); return v; }
__device__ __forceinline__ uint4 ld_relaxed4(const uint32_t* p) {
  uint4 v; asm volatile("ld.relaxed.gpu.global.v4.u32 {%0,%1,%2,%3}, [%4];" : "=r"(v.x), "=r"(v.y), "=r"(v.z), "=r"(v.w) : "l"(p) : "memory"); return v;
}
__device__ __forceinline__ void st_release8(uint8_t* p, uint32_t v) { asm volatile("st.release.gpu.global.u8 [%0], %1;" ::"l"(p), "r"(v) : "memory"); }
__device__ __forceinline__ uint32_t ld_relaxed(const uint32_t* p) { uint32_t v; asm volatile("ld.relaxed.gpu.global.u32 %0, [%1];" : "=r"(v) : "l"(p) : "memory"); return v; }
__device__ __forceinline__ void st_release(uint32_t* p, uint32_t v) { asm volatile("st.release.gpu.global.u32 [%0], %1;" ::"l"(p), "r"(v) : "memory"); }
__device__ __forceinline__ void st_pkt(uint4* p, uint32_t a, uint32_t b, uint32_t c, uint32_t d) {
  asm volatile("{\n.reg .b64 lo, hi;\n.reg .b128 v;\nmov.b64 lo, {%1, %2};\nmov.b64 hi, {%3, %4};\nmov.b128 v, {lo, hi};\nst.relaxed.gpu.global.b128 [%0], v;\n}" ::"l"(p), "r"(a), "r"(b), "r"(c), "r"(d) : "memory");
}
__device__ __forceinline__ uint4 ld_pkt(const uint4* p) {
  uint4 r;
  asm volatile("{\n.reg .b64 lo, hi;\n.reg .b128 v;\nld.relaxed.gpu.global.b128 v, [%4];\nmov.b128 {lo, hi}, v;\nmov.b64 {%0, %1}, lo;\nmov.b64 {%2, %3}, hi;\n}" : "=r"(r.x), "=r"(r.y), "=r"(r.z), "=r"(r.w) : "l"(p) : "memory");
  return r;
}
__device__ __forceinline__ uint32_t pack_bf16(float lo, float hi) { uint32_t d; asm("cvt.rn.bf16x2.f32 %0, %1, %2;" : "=r"(d) : "f"(hi), "f"(lo)); return d; }
__device__ __forceinline__ float ex2(float x) { float y; asm("ex2.approx.ftz.f32 %0, %1;" : "=f"(y) : "f"(x)); return y; }
__device__ __forceinline__ float rsq(float x) { float y; asm("rsqrt.approx.ftz.f32 %0, %1;" : "=f"(y) : "f"(x)); return y; }
__device__ __forceinline__ float rcp(float x) { float y; asm("rcp.approx.ftz.f32 %0, %1;" : "=f"(y) : "f"(x)); return y; }
__device__ __forceinline__ float bf_lo(uint32_t v) { return __uint_as_float(v << 16); }
__device__ __forceinline__ float bf_hi(uint32_t v) { return __uint_as_float(v & 0xffff0000u); }
__device__ __forceinline__ void stsm4(uint32_t addr, uint32_t a, uint32_t b, uint32_t c, uint32_t d) {
  asm volatile("stmatrix.sync.aligned.m8n8.x4.shared.b16 [%0], {%1, %2, %3, %4};" ::"r"(addr), "r"(a), "r"(b), "r"(c), "r"(d) : "memory");
}
__device__ __forceinline__ uint32_t movm(uint32_t a) { uint32_t d; asm volatile("movmatrix.sync.aligned.m8n8.trans.b16 %0, %1;" : "=r"(d) : "r"(a)); return d; }
__device__ __forceinline__ void mma16(float (&c)[4], uint32_t a0, uint32_t a1, uint32_t a2, uint32_t a3, uint32_t b0, uint32_t b1) {
  asm volatile("mma.sync.aligned.m16n8k16.row.col.f32.bf16.bf16.f32 {%0,%1,%2,%3}, {%4,%5,%6,%7}, {%8,%9}, {%0,%1,%2,%3};"
               : "+f"(c[0]), "+f"(c[1]), "+f"(c[2]), "+f"(c[3]) : "r"(a0), "r"(a1), "r"(a2), "r"(a3), "r"(b0), "r"(b1));
}
__device__ __forceinline__ void mma8(float (&c)[4], uint32_t a0, uint32_t a1, uint32_t b0) {
  asm volatile("mma.sync.aligned.m16n8k8.row.col.f32.bf16.bf16.f32 {%0,%1,%2,%3}, {%4,%5}, {%6}, {%0,%1,%2,%3};"
               : "+f"(c[0]), "+f"(c[1]), "+f"(c[2]), "+f"(c[3]) : "r"(a0), "r"(a1), "r"(b0));
}
__device__ __forceinline__ void sts128(uint32_t a, uint32_t x, uint32_t y, uint32_t z, uint32_t w) {
  asm volatile("st.shared.v4.b32 [%0], {%1,%2,%3,%4};" ::"r"(a), "r"(x), "r"(y), "r"(z), "r"(w) : "memory");
}
__device__ __forceinline__ float2 lds64(uint32_t a) { float2 v; asm volatile("ld.shared.v2.f32 {%0,%1}, [%2];" : "=f"(v.x), "=f"(v.y) : "r"(a)); return v; }
__device__ __forceinline__ float4 lds128(uint32_t a) { float4 v; asm volatile("ld.shared.v4.f32 {%0,%1,%2,%3}, [%4];" : "=f"(v.x), "=f"(v.y), "=f"(v.z), "=f"(v.w) : "r"(a)); return v; }
__device__ __forceinline__ uint32_t lds32(uint32_t a) { uint32_t v; asm volatile("ld.shared.b32 %0, [%1];" : "=r"(v) : "r"(a)); return v; }
constexpr uint32_t PA1 = 0x80000000u / NA + 1, G1 = 8 + (1u << 28);
constexpr uint32_t DA0 = ((SB + OFF_A) >> 4) | (1u << 16), DB0 = ((SB + OFF_B) >> 4) | (512u << 16);
template <int S> __device__ __forceinline__ void wgmma_first128(float (&d)[S], uint32_t da, uint32_t& db, uint32_t h0, uint32_t h1, uint32_t one) {
  asm volatile("{\n.reg .b64 a, b, s;\n.reg .b32 t, u;\n.reg .pred p, q;\nwgmma.fence.sync.aligned;\n"
    "mov.b32 t, %65;\n"
    "mov.b64 a, {t, %66};\nmov.b64 b, {%64, %67};\n"
    "wgmma.mma_async.sync.aligned.m64n128k16.f32.bf16.bf16 "
    "{%0, %1, %2, %3, %4, %5, %6, %7, %8, %9, %10, %11, %12, %13, %14, %15, %16, %17, %18, %19, %20, %21, %22, %23, %24, %25, %26, %27, %28, %29, %30, %31, %32, %33, %34, %35, %36, %37, %38, %39, %40, %41, %42, %43, %44, %45, %46, %47, %48, %49, %50, %51, %52, %53, %54, %55, %56, %57, %58, %59, %60, %61, %62, %63}, "
    "a, b, 0, 1, 1, 0, 1;\n"
    "mad.lo.u32 t, %68, 2, t;\nmad.lo.u32 %64, %68, 128, %64;\n"
    "mov.b64 a, {t, %66};\nmov.b64 b, {%64, %67};\n"
    "wgmma.mma_async.sync.aligned.m64n128k16.f32.bf16.bf16 "
    "{%0, %1, %2, %3, %4, %5, %6, %7, %8, %9, %10, %11, %12, %13, %14, %15, %16, %17, %18, %19, %20, %21, %22, %23, %24, %25, %26, %27, %28, %29, %30, %31, %32, %33, %34, %35, %36, %37, %38, %39, %40, %41, %42, %43, %44, %45, %46, %47, %48, %49, %50, %51, %52, %53, %54, %55, %56, %57, %58, %59, %60, %61, %62, %63}, "
    "a, b, 1, 1, 1, 0, 1;\n"
    "mad.lo.u32 t, %68, 2, t;\nmad.lo.u32 %64, %68, 128, %64;\n"
    "mov.b64 a, {t, %66};\nmov.b64 b, {%64, %67};\n"
    "wgmma.mma_async.sync.aligned.m64n128k16.f32.bf16.bf16 "
    "{%0, %1, %2, %3, %4, %5, %6, %7, %8, %9, %10, %11, %12, %13, %14, %15, %16, %17, %18, %19, %20, %21, %22, %23, %24, %25, %26, %27, %28, %29, %30, %31, %32, %33, %34, %35, %36, %37, %38, %39, %40, %41, %42, %43, %44, %45, %46, %47, %48, %49, %50, %51, %52, %53, %54, %55, %56, %57, %58, %59, %60, %61, %62, %63}, "
    "a, b, 1, 1, 1, 0, 1;\n"
    "mad.lo.u32 t, %68, 2, t;\nmad.lo.u32 %64, %68, 128, %64;\n"
    "mov.b64 a, {t, %66};\nmov.b64 b, {%64, %67};\n"
    "wgmma.mma_async.sync.aligned.m64n128k16.f32.bf16.bf16 "
    "{%0, %1, %2, %3, %4, %5, %6, %7, %8, %9, %10, %11, %12, %13, %14, %15, %16, %17, %18, %19, %20, %21, %22, %23, %24, %25, %26, %27, %28, %29, %30, %31, %32, %33, %34, %35, %36, %37, %38, %39, %40, %41, %42, %43, %44, %45, %46, %47, %48, %49, %50, %51, %52, %53, %54, %55, %56, %57, %58, %59, %60, %61, %62, %63}, "
    "a, b, 1, 1, 1, 0, 1;\n"
    "wgmma.commit_group.sync.aligned;\n}"
    : "=f"(d[0]), "=f"(d[1]), "=f"(d[2]), "=f"(d[3]), "=f"(d[4]), "=f"(d[5]), "=f"(d[6]), "=f"(d[7]), "=f"(d[8]), "=f"(d[9]), "=f"(d[10]), "=f"(d[11]), "=f"(d[12]), "=f"(d[13]), "=f"(d[14]), "=f"(d[15]), "=f"(d[16]), "=f"(d[17]), "=f"(d[18]), "=f"(d[19]), "=f"(d[20]), "=f"(d[21]), "=f"(d[22]), "=f"(d[23]), "=f"(d[24]), "=f"(d[25]), "=f"(d[26]), "=f"(d[27]), "=f"(d[28]), "=f"(d[29]), "=f"(d[30]), "=f"(d[31]), "=f"(d[32]), "=f"(d[33]), "=f"(d[34]), "=f"(d[35]), "=f"(d[36]), "=f"(d[37]), "=f"(d[38]), "=f"(d[39]), "=f"(d[40]), "=f"(d[41]), "=f"(d[42]), "=f"(d[43]), "=f"(d[44]), "=f"(d[45]), "=f"(d[46]), "=f"(d[47]), "=f"(d[48]), "=f"(d[49]), "=f"(d[50]), "=f"(d[51]), "=f"(d[52]), "=f"(d[53]), "=f"(d[54]), "=f"(d[55]), "=f"(d[56]), "=f"(d[57]), "=f"(d[58]), "=f"(d[59]), "=f"(d[60]), "=f"(d[61]), "=f"(d[62]), "=f"(d[63]), "+r"(db)
    : "r"(da), "r"(h0), "r"(h1), "r"(one) : "memory");
}
template <int S> __device__ __forceinline__ uint2 wgmma_probe128(float (&d)[S], uint32_t da, uint32_t& db, uint32_t h0, uint32_t h1, uint32_t one, uint32_t b0, uint32_t p0, uint32_t b1, uint32_t p1) {
  uint2 ok;
  asm volatile("{\n.reg .b64 a, b, s;\n.reg .b32 t, u;\n.reg .pred p, q;\nwgmma.fence.sync.aligned;\n"
    "mov.b32 t, %67;\n"
    "mov.b64 a, {t, %68};\nmov.b64 b, {%66, %69};\n"
    "wgmma.mma_async.sync.aligned.m64n128k16.f32.bf16.bf16 "
    "{%2, %3, %4, %5, %6, %7, %8, %9, %10, %11, %12, %13, %14, %15, %16, %17, %18, %19, %20, %21, %22, %23, %24, %25, %26, %27, %28, %29, %30, %31, %32, %33, %34, %35, %36, %37, %38, %39, %40, %41, %42, %43, %44, %45, %46, %47, %48, %49, %50, %51, %52, %53, %54, %55, %56, %57, %58, %59, %60, %61, %62, %63, %64, %65}, "
    "a, b, 1, 1, 1, 0, 1;\n"
    "mad.lo.u32 t, %70, 2, t;\nmad.lo.u32 %66, %70, 128, %66;\n"
    "mov.b64 a, {t, %68};\nmov.b64 b, {%66, %69};\n"
    "wgmma.mma_async.sync.aligned.m64n128k16.f32.bf16.bf16 "
    "{%2, %3, %4, %5, %6, %7, %8, %9, %10, %11, %12, %13, %14, %15, %16, %17, %18, %19, %20, %21, %22, %23, %24, %25, %26, %27, %28, %29, %30, %31, %32, %33, %34, %35, %36, %37, %38, %39, %40, %41, %42, %43, %44, %45, %46, %47, %48, %49, %50, %51, %52, %53, %54, %55, %56, %57, %58, %59, %60, %61, %62, %63, %64, %65}, "
    "a, b, 1, 1, 1, 0, 1;\n"
    "mov.b64 s, {%72, %72};\nmbarrier.test_wait.shared::cta.b64 p, [%71], s;\nmov.b64 s, {%74, %74};\nmbarrier.test_wait.shared::cta.b64 q, [%73], s;\n"
    "mad.lo.u32 t, %70, 2, t;\nmad.lo.u32 %66, %70, 128, %66;\n"
    "mov.b64 a, {t, %68};\nmov.b64 b, {%66, %69};\n"
    "wgmma.mma_async.sync.aligned.m64n128k16.f32.bf16.bf16 "
    "{%2, %3, %4, %5, %6, %7, %8, %9, %10, %11, %12, %13, %14, %15, %16, %17, %18, %19, %20, %21, %22, %23, %24, %25, %26, %27, %28, %29, %30, %31, %32, %33, %34, %35, %36, %37, %38, %39, %40, %41, %42, %43, %44, %45, %46, %47, %48, %49, %50, %51, %52, %53, %54, %55, %56, %57, %58, %59, %60, %61, %62, %63, %64, %65}, "
    "a, b, 1, 1, 1, 0, 1;\n"
    "mad.lo.u32 t, %70, 2, t;\nmad.lo.u32 %66, %70, 128, %66;\n"
    "mov.b64 a, {t, %68};\nmov.b64 b, {%66, %69};\n"
    "wgmma.mma_async.sync.aligned.m64n128k16.f32.bf16.bf16 "
    "{%2, %3, %4, %5, %6, %7, %8, %9, %10, %11, %12, %13, %14, %15, %16, %17, %18, %19, %20, %21, %22, %23, %24, %25, %26, %27, %28, %29, %30, %31, %32, %33, %34, %35, %36, %37, %38, %39, %40, %41, %42, %43, %44, %45, %46, %47, %48, %49, %50, %51, %52, %53, %54, %55, %56, %57, %58, %59, %60, %61, %62, %63, %64, %65}, "
    "a, b, 1, 1, 1, 0, 1;\n"
    "wgmma.commit_group.sync.aligned;\nselp.u32 %0, 1, 0, p;\nselp.u32 %1, 1, 0, q;\n}"
    : "=r"(ok.x), "=r"(ok.y), "+f"(d[0]), "+f"(d[1]), "+f"(d[2]), "+f"(d[3]), "+f"(d[4]), "+f"(d[5]), "+f"(d[6]), "+f"(d[7]), "+f"(d[8]), "+f"(d[9]), "+f"(d[10]), "+f"(d[11]), "+f"(d[12]), "+f"(d[13]), "+f"(d[14]), "+f"(d[15]), "+f"(d[16]), "+f"(d[17]), "+f"(d[18]), "+f"(d[19]), "+f"(d[20]), "+f"(d[21]), "+f"(d[22]), "+f"(d[23]), "+f"(d[24]), "+f"(d[25]), "+f"(d[26]), "+f"(d[27]), "+f"(d[28]), "+f"(d[29]), "+f"(d[30]), "+f"(d[31]), "+f"(d[32]), "+f"(d[33]), "+f"(d[34]), "+f"(d[35]), "+f"(d[36]), "+f"(d[37]), "+f"(d[38]), "+f"(d[39]), "+f"(d[40]), "+f"(d[41]), "+f"(d[42]), "+f"(d[43]), "+f"(d[44]), "+f"(d[45]), "+f"(d[46]), "+f"(d[47]), "+f"(d[48]), "+f"(d[49]), "+f"(d[50]), "+f"(d[51]), "+f"(d[52]), "+f"(d[53]), "+f"(d[54]), "+f"(d[55]), "+f"(d[56]), "+f"(d[57]), "+f"(d[58]), "+f"(d[59]), "+f"(d[60]), "+f"(d[61]), "+f"(d[62]), "+f"(d[63]), "+r"(db)
    : "r"(da), "r"(h0), "r"(h1), "r"(one), "r"(b0), "r"(p0), "r"(b1), "r"(p1) : "memory");
  return ok;
}
template <int S> __device__ __forceinline__ void wgmma_first192(float (&d)[S], uint32_t da, uint32_t& db, uint32_t h0, uint32_t h1, uint32_t one) {
  asm volatile("{\n.reg .b64 a, b, s;\n.reg .b32 t, u;\n.reg .pred p, q;\nwgmma.fence.sync.aligned;\n"
    "mov.b32 t, %97;\n"
    "mov.b64 a, {t, %98};\nmov.b64 b, {%96, %99};\n"
    "wgmma.mma_async.sync.aligned.m64n192k16.f32.bf16.bf16 "
    "{%0, %1, %2, %3, %4, %5, %6, %7, %8, %9, %10, %11, %12, %13, %14, %15, %16, %17, %18, %19, %20, %21, %22, %23, %24, %25, %26, %27, %28, %29, %30, %31, %32, %33, %34, %35, %36, %37, %38, %39, %40, %41, %42, %43, %44, %45, %46, %47, %48, %49, %50, %51, %52, %53, %54, %55, %56, %57, %58, %59, %60, %61, %62, %63, %64, %65, %66, %67, %68, %69, %70, %71, %72, %73, %74, %75, %76, %77, %78, %79, %80, %81, %82, %83, %84, %85, %86, %87, %88, %89, %90, %91, %92, %93, %94, %95}, "
    "a, b, 0, 1, 1, 0, 1;\n"
    "mad.lo.u32 t, %100, 2, t;\nmad.lo.u32 %96, %100, 128, %96;\n"
    "mov.b64 a, {t, %98};\nmov.b64 b, {%96, %99};\n"
    "wgmma.mma_async.sync.aligned.m64n192k16.f32.bf16.bf16 "
    "{%0, %1, %2, %3, %4, %5, %6, %7, %8, %9, %10, %11, %12, %13, %14, %15, %16, %17, %18, %19, %20, %21, %22, %23, %24, %25, %26, %27, %28, %29, %30, %31, %32, %33, %34, %35, %36, %37, %38, %39, %40, %41, %42, %43, %44, %45, %46, %47, %48, %49, %50, %51, %52, %53, %54, %55, %56, %57, %58, %59, %60, %61, %62, %63, %64, %65, %66, %67, %68, %69, %70, %71, %72, %73, %74, %75, %76, %77, %78, %79, %80, %81, %82, %83, %84, %85, %86, %87, %88, %89, %90, %91, %92, %93, %94, %95}, "
    "a, b, 1, 1, 1, 0, 1;\n"
    "mad.lo.u32 t, %100, 2, t;\nmad.lo.u32 %96, %100, 128, %96;\n"
    "mov.b64 a, {t, %98};\nmov.b64 b, {%96, %99};\n"
    "wgmma.mma_async.sync.aligned.m64n192k16.f32.bf16.bf16 "
    "{%0, %1, %2, %3, %4, %5, %6, %7, %8, %9, %10, %11, %12, %13, %14, %15, %16, %17, %18, %19, %20, %21, %22, %23, %24, %25, %26, %27, %28, %29, %30, %31, %32, %33, %34, %35, %36, %37, %38, %39, %40, %41, %42, %43, %44, %45, %46, %47, %48, %49, %50, %51, %52, %53, %54, %55, %56, %57, %58, %59, %60, %61, %62, %63, %64, %65, %66, %67, %68, %69, %70, %71, %72, %73, %74, %75, %76, %77, %78, %79, %80, %81, %82, %83, %84, %85, %86, %87, %88, %89, %90, %91, %92, %93, %94, %95}, "
    "a, b, 1, 1, 1, 0, 1;\n"
    "mad.lo.u32 t, %100, 2, t;\nmad.lo.u32 %96, %100, 128, %96;\n"
    "mov.b64 a, {t, %98};\nmov.b64 b, {%96, %99};\n"
    "wgmma.mma_async.sync.aligned.m64n192k16.f32.bf16.bf16 "
    "{%0, %1, %2, %3, %4, %5, %6, %7, %8, %9, %10, %11, %12, %13, %14, %15, %16, %17, %18, %19, %20, %21, %22, %23, %24, %25, %26, %27, %28, %29, %30, %31, %32, %33, %34, %35, %36, %37, %38, %39, %40, %41, %42, %43, %44, %45, %46, %47, %48, %49, %50, %51, %52, %53, %54, %55, %56, %57, %58, %59, %60, %61, %62, %63, %64, %65, %66, %67, %68, %69, %70, %71, %72, %73, %74, %75, %76, %77, %78, %79, %80, %81, %82, %83, %84, %85, %86, %87, %88, %89, %90, %91, %92, %93, %94, %95}, "
    "a, b, 1, 1, 1, 0, 1;\n"
    "wgmma.commit_group.sync.aligned;\n}"
    : "=f"(d[0]), "=f"(d[1]), "=f"(d[2]), "=f"(d[3]), "=f"(d[4]), "=f"(d[5]), "=f"(d[6]), "=f"(d[7]), "=f"(d[8]), "=f"(d[9]), "=f"(d[10]), "=f"(d[11]), "=f"(d[12]), "=f"(d[13]), "=f"(d[14]), "=f"(d[15]), "=f"(d[16]), "=f"(d[17]), "=f"(d[18]), "=f"(d[19]), "=f"(d[20]), "=f"(d[21]), "=f"(d[22]), "=f"(d[23]), "=f"(d[24]), "=f"(d[25]), "=f"(d[26]), "=f"(d[27]), "=f"(d[28]), "=f"(d[29]), "=f"(d[30]), "=f"(d[31]), "=f"(d[32]), "=f"(d[33]), "=f"(d[34]), "=f"(d[35]), "=f"(d[36]), "=f"(d[37]), "=f"(d[38]), "=f"(d[39]), "=f"(d[40]), "=f"(d[41]), "=f"(d[42]), "=f"(d[43]), "=f"(d[44]), "=f"(d[45]), "=f"(d[46]), "=f"(d[47]), "=f"(d[48]), "=f"(d[49]), "=f"(d[50]), "=f"(d[51]), "=f"(d[52]), "=f"(d[53]), "=f"(d[54]), "=f"(d[55]), "=f"(d[56]), "=f"(d[57]), "=f"(d[58]), "=f"(d[59]), "=f"(d[60]), "=f"(d[61]), "=f"(d[62]), "=f"(d[63]), "=f"(d[64]), "=f"(d[65]), "=f"(d[66]), "=f"(d[67]), "=f"(d[68]), "=f"(d[69]), "=f"(d[70]), "=f"(d[71]), "=f"(d[72]), "=f"(d[73]), "=f"(d[74]), "=f"(d[75]), "=f"(d[76]), "=f"(d[77]), "=f"(d[78]), "=f"(d[79]), "=f"(d[80]), "=f"(d[81]), "=f"(d[82]), "=f"(d[83]), "=f"(d[84]), "=f"(d[85]), "=f"(d[86]), "=f"(d[87]), "=f"(d[88]), "=f"(d[89]), "=f"(d[90]), "=f"(d[91]), "=f"(d[92]), "=f"(d[93]), "=f"(d[94]), "=f"(d[95]), "+r"(db)
    : "r"(da), "r"(h0), "r"(h1), "r"(one) : "memory");
}
template <int S> __device__ __forceinline__ uint2 wgmma_probe192(float (&d)[S], uint32_t da, uint32_t& db, uint32_t h0, uint32_t h1, uint32_t one, uint32_t b0, uint32_t p0, uint32_t b1, uint32_t p1) {
  uint2 ok;
  asm volatile("{\n.reg .b64 a, b, s;\n.reg .b32 t, u;\n.reg .pred p, q;\nwgmma.fence.sync.aligned;\n"
    "mov.b32 t, %99;\n"
    "mov.b64 a, {t, %100};\nmov.b64 b, {%98, %101};\n"
    "wgmma.mma_async.sync.aligned.m64n192k16.f32.bf16.bf16 "
    "{%2, %3, %4, %5, %6, %7, %8, %9, %10, %11, %12, %13, %14, %15, %16, %17, %18, %19, %20, %21, %22, %23, %24, %25, %26, %27, %28, %29, %30, %31, %32, %33, %34, %35, %36, %37, %38, %39, %40, %41, %42, %43, %44, %45, %46, %47, %48, %49, %50, %51, %52, %53, %54, %55, %56, %57, %58, %59, %60, %61, %62, %63, %64, %65, %66, %67, %68, %69, %70, %71, %72, %73, %74, %75, %76, %77, %78, %79, %80, %81, %82, %83, %84, %85, %86, %87, %88, %89, %90, %91, %92, %93, %94, %95, %96, %97}, "
    "a, b, 1, 1, 1, 0, 1;\n"
    "mad.lo.u32 t, %102, 2, t;\nmad.lo.u32 %98, %102, 128, %98;\n"
    "mov.b64 a, {t, %100};\nmov.b64 b, {%98, %101};\n"
    "wgmma.mma_async.sync.aligned.m64n192k16.f32.bf16.bf16 "
    "{%2, %3, %4, %5, %6, %7, %8, %9, %10, %11, %12, %13, %14, %15, %16, %17, %18, %19, %20, %21, %22, %23, %24, %25, %26, %27, %28, %29, %30, %31, %32, %33, %34, %35, %36, %37, %38, %39, %40, %41, %42, %43, %44, %45, %46, %47, %48, %49, %50, %51, %52, %53, %54, %55, %56, %57, %58, %59, %60, %61, %62, %63, %64, %65, %66, %67, %68, %69, %70, %71, %72, %73, %74, %75, %76, %77, %78, %79, %80, %81, %82, %83, %84, %85, %86, %87, %88, %89, %90, %91, %92, %93, %94, %95, %96, %97}, "
    "a, b, 1, 1, 1, 0, 1;\n"
    "mov.b64 s, {%104, %104};\nmbarrier.test_wait.shared::cta.b64 p, [%103], s;\nmov.b64 s, {%106, %106};\nmbarrier.test_wait.shared::cta.b64 q, [%105], s;\n"
    "mad.lo.u32 t, %102, 2, t;\nmad.lo.u32 %98, %102, 128, %98;\n"
    "mov.b64 a, {t, %100};\nmov.b64 b, {%98, %101};\n"
    "wgmma.mma_async.sync.aligned.m64n192k16.f32.bf16.bf16 "
    "{%2, %3, %4, %5, %6, %7, %8, %9, %10, %11, %12, %13, %14, %15, %16, %17, %18, %19, %20, %21, %22, %23, %24, %25, %26, %27, %28, %29, %30, %31, %32, %33, %34, %35, %36, %37, %38, %39, %40, %41, %42, %43, %44, %45, %46, %47, %48, %49, %50, %51, %52, %53, %54, %55, %56, %57, %58, %59, %60, %61, %62, %63, %64, %65, %66, %67, %68, %69, %70, %71, %72, %73, %74, %75, %76, %77, %78, %79, %80, %81, %82, %83, %84, %85, %86, %87, %88, %89, %90, %91, %92, %93, %94, %95, %96, %97}, "
    "a, b, 1, 1, 1, 0, 1;\n"
    "mad.lo.u32 t, %102, 2, t;\nmad.lo.u32 %98, %102, 128, %98;\n"
    "mov.b64 a, {t, %100};\nmov.b64 b, {%98, %101};\n"
    "wgmma.mma_async.sync.aligned.m64n192k16.f32.bf16.bf16 "
    "{%2, %3, %4, %5, %6, %7, %8, %9, %10, %11, %12, %13, %14, %15, %16, %17, %18, %19, %20, %21, %22, %23, %24, %25, %26, %27, %28, %29, %30, %31, %32, %33, %34, %35, %36, %37, %38, %39, %40, %41, %42, %43, %44, %45, %46, %47, %48, %49, %50, %51, %52, %53, %54, %55, %56, %57, %58, %59, %60, %61, %62, %63, %64, %65, %66, %67, %68, %69, %70, %71, %72, %73, %74, %75, %76, %77, %78, %79, %80, %81, %82, %83, %84, %85, %86, %87, %88, %89, %90, %91, %92, %93, %94, %95, %96, %97}, "
    "a, b, 1, 1, 1, 0, 1;\n"
    "wgmma.commit_group.sync.aligned;\nselp.u32 %0, 1, 0, p;\nselp.u32 %1, 1, 0, q;\n}"
    : "=r"(ok.x), "=r"(ok.y), "+f"(d[0]), "+f"(d[1]), "+f"(d[2]), "+f"(d[3]), "+f"(d[4]), "+f"(d[5]), "+f"(d[6]), "+f"(d[7]), "+f"(d[8]), "+f"(d[9]), "+f"(d[10]), "+f"(d[11]), "+f"(d[12]), "+f"(d[13]), "+f"(d[14]), "+f"(d[15]), "+f"(d[16]), "+f"(d[17]), "+f"(d[18]), "+f"(d[19]), "+f"(d[20]), "+f"(d[21]), "+f"(d[22]), "+f"(d[23]), "+f"(d[24]), "+f"(d[25]), "+f"(d[26]), "+f"(d[27]), "+f"(d[28]), "+f"(d[29]), "+f"(d[30]), "+f"(d[31]), "+f"(d[32]), "+f"(d[33]), "+f"(d[34]), "+f"(d[35]), "+f"(d[36]), "+f"(d[37]), "+f"(d[38]), "+f"(d[39]), "+f"(d[40]), "+f"(d[41]), "+f"(d[42]), "+f"(d[43]), "+f"(d[44]), "+f"(d[45]), "+f"(d[46]), "+f"(d[47]), "+f"(d[48]), "+f"(d[49]), "+f"(d[50]), "+f"(d[51]), "+f"(d[52]), "+f"(d[53]), "+f"(d[54]), "+f"(d[55]), "+f"(d[56]), "+f"(d[57]), "+f"(d[58]), "+f"(d[59]), "+f"(d[60]), "+f"(d[61]), "+f"(d[62]), "+f"(d[63]), "+f"(d[64]), "+f"(d[65]), "+f"(d[66]), "+f"(d[67]), "+f"(d[68]), "+f"(d[69]), "+f"(d[70]), "+f"(d[71]), "+f"(d[72]), "+f"(d[73]), "+f"(d[74]), "+f"(d[75]), "+f"(d[76]), "+f"(d[77]), "+f"(d[78]), "+f"(d[79]), "+f"(d[80]), "+f"(d[81]), "+f"(d[82]), "+f"(d[83]), "+f"(d[84]), "+f"(d[85]), "+f"(d[86]), "+f"(d[87]), "+f"(d[88]), "+f"(d[89]), "+f"(d[90]), "+f"(d[91]), "+f"(d[92]), "+f"(d[93]), "+f"(d[94]), "+f"(d[95]), "+r"(db)
    : "r"(da), "r"(h0), "r"(h1), "r"(one), "r"(b0), "r"(p0), "r"(b1), "r"(p1) : "memory");
  return ok;
}
template <int S> __device__ __forceinline__ void wgmma_first256(float (&d)[S], uint32_t da, uint32_t& db, uint32_t h0, uint32_t h1, uint32_t one) {
  asm volatile("{\n.reg .b64 a, b, s;\n.reg .b32 t, u;\n.reg .pred p, q;\nwgmma.fence.sync.aligned;\n"
    "mov.b32 t, %129;\n"
    "mov.b64 a, {t, %130};\nmov.b64 b, {%128, %131};\n"
    "wgmma.mma_async.sync.aligned.m64n256k16.f32.bf16.bf16 "
    "{%0, %1, %2, %3, %4, %5, %6, %7, %8, %9, %10, %11, %12, %13, %14, %15, %16, %17, %18, %19, %20, %21, %22, %23, %24, %25, %26, %27, %28, %29, %30, %31, %32, %33, %34, %35, %36, %37, %38, %39, %40, %41, %42, %43, %44, %45, %46, %47, %48, %49, %50, %51, %52, %53, %54, %55, %56, %57, %58, %59, %60, %61, %62, %63, %64, %65, %66, %67, %68, %69, %70, %71, %72, %73, %74, %75, %76, %77, %78, %79, %80, %81, %82, %83, %84, %85, %86, %87, %88, %89, %90, %91, %92, %93, %94, %95, %96, %97, %98, %99, %100, %101, %102, %103, %104, %105, %106, %107, %108, %109, %110, %111, %112, %113, %114, %115, %116, %117, %118, %119, %120, %121, %122, %123, %124, %125, %126, %127}, "
    "a, b, 0, 1, 1, 0, 1;\n"
    "mad.lo.u32 t, %132, 2, t;\nmad.lo.u32 %128, %132, 128, %128;\n"
    "mov.b64 a, {t, %130};\nmov.b64 b, {%128, %131};\n"
    "wgmma.mma_async.sync.aligned.m64n256k16.f32.bf16.bf16 "
    "{%0, %1, %2, %3, %4, %5, %6, %7, %8, %9, %10, %11, %12, %13, %14, %15, %16, %17, %18, %19, %20, %21, %22, %23, %24, %25, %26, %27, %28, %29, %30, %31, %32, %33, %34, %35, %36, %37, %38, %39, %40, %41, %42, %43, %44, %45, %46, %47, %48, %49, %50, %51, %52, %53, %54, %55, %56, %57, %58, %59, %60, %61, %62, %63, %64, %65, %66, %67, %68, %69, %70, %71, %72, %73, %74, %75, %76, %77, %78, %79, %80, %81, %82, %83, %84, %85, %86, %87, %88, %89, %90, %91, %92, %93, %94, %95, %96, %97, %98, %99, %100, %101, %102, %103, %104, %105, %106, %107, %108, %109, %110, %111, %112, %113, %114, %115, %116, %117, %118, %119, %120, %121, %122, %123, %124, %125, %126, %127}, "
    "a, b, 1, 1, 1, 0, 1;\n"
    "mad.lo.u32 t, %132, 2, t;\nmad.lo.u32 %128, %132, 128, %128;\n"
    "mov.b64 a, {t, %130};\nmov.b64 b, {%128, %131};\n"
    "wgmma.mma_async.sync.aligned.m64n256k16.f32.bf16.bf16 "
    "{%0, %1, %2, %3, %4, %5, %6, %7, %8, %9, %10, %11, %12, %13, %14, %15, %16, %17, %18, %19, %20, %21, %22, %23, %24, %25, %26, %27, %28, %29, %30, %31, %32, %33, %34, %35, %36, %37, %38, %39, %40, %41, %42, %43, %44, %45, %46, %47, %48, %49, %50, %51, %52, %53, %54, %55, %56, %57, %58, %59, %60, %61, %62, %63, %64, %65, %66, %67, %68, %69, %70, %71, %72, %73, %74, %75, %76, %77, %78, %79, %80, %81, %82, %83, %84, %85, %86, %87, %88, %89, %90, %91, %92, %93, %94, %95, %96, %97, %98, %99, %100, %101, %102, %103, %104, %105, %106, %107, %108, %109, %110, %111, %112, %113, %114, %115, %116, %117, %118, %119, %120, %121, %122, %123, %124, %125, %126, %127}, "
    "a, b, 1, 1, 1, 0, 1;\n"
    "mad.lo.u32 t, %132, 2, t;\nmad.lo.u32 %128, %132, 128, %128;\n"
    "mov.b64 a, {t, %130};\nmov.b64 b, {%128, %131};\n"
    "wgmma.mma_async.sync.aligned.m64n256k16.f32.bf16.bf16 "
    "{%0, %1, %2, %3, %4, %5, %6, %7, %8, %9, %10, %11, %12, %13, %14, %15, %16, %17, %18, %19, %20, %21, %22, %23, %24, %25, %26, %27, %28, %29, %30, %31, %32, %33, %34, %35, %36, %37, %38, %39, %40, %41, %42, %43, %44, %45, %46, %47, %48, %49, %50, %51, %52, %53, %54, %55, %56, %57, %58, %59, %60, %61, %62, %63, %64, %65, %66, %67, %68, %69, %70, %71, %72, %73, %74, %75, %76, %77, %78, %79, %80, %81, %82, %83, %84, %85, %86, %87, %88, %89, %90, %91, %92, %93, %94, %95, %96, %97, %98, %99, %100, %101, %102, %103, %104, %105, %106, %107, %108, %109, %110, %111, %112, %113, %114, %115, %116, %117, %118, %119, %120, %121, %122, %123, %124, %125, %126, %127}, "
    "a, b, 1, 1, 1, 0, 1;\n"
    "wgmma.commit_group.sync.aligned;\n}"
    : "=f"(d[0]), "=f"(d[1]), "=f"(d[2]), "=f"(d[3]), "=f"(d[4]), "=f"(d[5]), "=f"(d[6]), "=f"(d[7]), "=f"(d[8]), "=f"(d[9]), "=f"(d[10]), "=f"(d[11]), "=f"(d[12]), "=f"(d[13]), "=f"(d[14]), "=f"(d[15]), "=f"(d[16]), "=f"(d[17]), "=f"(d[18]), "=f"(d[19]), "=f"(d[20]), "=f"(d[21]), "=f"(d[22]), "=f"(d[23]), "=f"(d[24]), "=f"(d[25]), "=f"(d[26]), "=f"(d[27]), "=f"(d[28]), "=f"(d[29]), "=f"(d[30]), "=f"(d[31]), "=f"(d[32]), "=f"(d[33]), "=f"(d[34]), "=f"(d[35]), "=f"(d[36]), "=f"(d[37]), "=f"(d[38]), "=f"(d[39]), "=f"(d[40]), "=f"(d[41]), "=f"(d[42]), "=f"(d[43]), "=f"(d[44]), "=f"(d[45]), "=f"(d[46]), "=f"(d[47]), "=f"(d[48]), "=f"(d[49]), "=f"(d[50]), "=f"(d[51]), "=f"(d[52]), "=f"(d[53]), "=f"(d[54]), "=f"(d[55]), "=f"(d[56]), "=f"(d[57]), "=f"(d[58]), "=f"(d[59]), "=f"(d[60]), "=f"(d[61]), "=f"(d[62]), "=f"(d[63]), "=f"(d[64]), "=f"(d[65]), "=f"(d[66]), "=f"(d[67]), "=f"(d[68]), "=f"(d[69]), "=f"(d[70]), "=f"(d[71]), "=f"(d[72]), "=f"(d[73]), "=f"(d[74]), "=f"(d[75]), "=f"(d[76]), "=f"(d[77]), "=f"(d[78]), "=f"(d[79]), "=f"(d[80]), "=f"(d[81]), "=f"(d[82]), "=f"(d[83]), "=f"(d[84]), "=f"(d[85]), "=f"(d[86]), "=f"(d[87]), "=f"(d[88]), "=f"(d[89]), "=f"(d[90]), "=f"(d[91]), "=f"(d[92]), "=f"(d[93]), "=f"(d[94]), "=f"(d[95]), "=f"(d[96]), "=f"(d[97]), "=f"(d[98]), "=f"(d[99]), "=f"(d[100]), "=f"(d[101]), "=f"(d[102]), "=f"(d[103]), "=f"(d[104]), "=f"(d[105]), "=f"(d[106]), "=f"(d[107]), "=f"(d[108]), "=f"(d[109]), "=f"(d[110]), "=f"(d[111]), "=f"(d[112]), "=f"(d[113]), "=f"(d[114]), "=f"(d[115]), "=f"(d[116]), "=f"(d[117]), "=f"(d[118]), "=f"(d[119]), "=f"(d[120]), "=f"(d[121]), "=f"(d[122]), "=f"(d[123]), "=f"(d[124]), "=f"(d[125]), "=f"(d[126]), "=f"(d[127]), "+r"(db)
    : "r"(da), "r"(h0), "r"(h1), "r"(one) : "memory");
}
template <int S> __device__ __forceinline__ void wgmma_acc256(float (&d)[S], uint32_t da, uint32_t& db, uint32_t h0, uint32_t h1, uint32_t one) {
  asm volatile("{\n.reg .b64 a, b, s;\n.reg .b32 t, u;\n.reg .pred p, q;\nwgmma.fence.sync.aligned;\n"
    "mov.b32 t, %129;\n"
    "mov.b64 a, {t, %130};\nmov.b64 b, {%128, %131};\n"
    "wgmma.mma_async.sync.aligned.m64n256k16.f32.bf16.bf16 "
    "{%0, %1, %2, %3, %4, %5, %6, %7, %8, %9, %10, %11, %12, %13, %14, %15, %16, %17, %18, %19, %20, %21, %22, %23, %24, %25, %26, %27, %28, %29, %30, %31, %32, %33, %34, %35, %36, %37, %38, %39, %40, %41, %42, %43, %44, %45, %46, %47, %48, %49, %50, %51, %52, %53, %54, %55, %56, %57, %58, %59, %60, %61, %62, %63, %64, %65, %66, %67, %68, %69, %70, %71, %72, %73, %74, %75, %76, %77, %78, %79, %80, %81, %82, %83, %84, %85, %86, %87, %88, %89, %90, %91, %92, %93, %94, %95, %96, %97, %98, %99, %100, %101, %102, %103, %104, %105, %106, %107, %108, %109, %110, %111, %112, %113, %114, %115, %116, %117, %118, %119, %120, %121, %122, %123, %124, %125, %126, %127}, "
    "a, b, 1, 1, 1, 0, 1;\n"
    "mad.lo.u32 t, %132, 2, t;\nmad.lo.u32 %128, %132, 128, %128;\n"
    "mov.b64 a, {t, %130};\nmov.b64 b, {%128, %131};\n"
    "wgmma.mma_async.sync.aligned.m64n256k16.f32.bf16.bf16 "
    "{%0, %1, %2, %3, %4, %5, %6, %7, %8, %9, %10, %11, %12, %13, %14, %15, %16, %17, %18, %19, %20, %21, %22, %23, %24, %25, %26, %27, %28, %29, %30, %31, %32, %33, %34, %35, %36, %37, %38, %39, %40, %41, %42, %43, %44, %45, %46, %47, %48, %49, %50, %51, %52, %53, %54, %55, %56, %57, %58, %59, %60, %61, %62, %63, %64, %65, %66, %67, %68, %69, %70, %71, %72, %73, %74, %75, %76, %77, %78, %79, %80, %81, %82, %83, %84, %85, %86, %87, %88, %89, %90, %91, %92, %93, %94, %95, %96, %97, %98, %99, %100, %101, %102, %103, %104, %105, %106, %107, %108, %109, %110, %111, %112, %113, %114, %115, %116, %117, %118, %119, %120, %121, %122, %123, %124, %125, %126, %127}, "
    "a, b, 1, 1, 1, 0, 1;\n"
    "mad.lo.u32 t, %132, 2, t;\nmad.lo.u32 %128, %132, 128, %128;\n"
    "mov.b64 a, {t, %130};\nmov.b64 b, {%128, %131};\n"
    "wgmma.mma_async.sync.aligned.m64n256k16.f32.bf16.bf16 "
    "{%0, %1, %2, %3, %4, %5, %6, %7, %8, %9, %10, %11, %12, %13, %14, %15, %16, %17, %18, %19, %20, %21, %22, %23, %24, %25, %26, %27, %28, %29, %30, %31, %32, %33, %34, %35, %36, %37, %38, %39, %40, %41, %42, %43, %44, %45, %46, %47, %48, %49, %50, %51, %52, %53, %54, %55, %56, %57, %58, %59, %60, %61, %62, %63, %64, %65, %66, %67, %68, %69, %70, %71, %72, %73, %74, %75, %76, %77, %78, %79, %80, %81, %82, %83, %84, %85, %86, %87, %88, %89, %90, %91, %92, %93, %94, %95, %96, %97, %98, %99, %100, %101, %102, %103, %104, %105, %106, %107, %108, %109, %110, %111, %112, %113, %114, %115, %116, %117, %118, %119, %120, %121, %122, %123, %124, %125, %126, %127}, "
    "a, b, 1, 1, 1, 0, 1;\n"
    "mad.lo.u32 t, %132, 2, t;\nmad.lo.u32 %128, %132, 128, %128;\n"
    "mov.b64 a, {t, %130};\nmov.b64 b, {%128, %131};\n"
    "wgmma.mma_async.sync.aligned.m64n256k16.f32.bf16.bf16 "
    "{%0, %1, %2, %3, %4, %5, %6, %7, %8, %9, %10, %11, %12, %13, %14, %15, %16, %17, %18, %19, %20, %21, %22, %23, %24, %25, %26, %27, %28, %29, %30, %31, %32, %33, %34, %35, %36, %37, %38, %39, %40, %41, %42, %43, %44, %45, %46, %47, %48, %49, %50, %51, %52, %53, %54, %55, %56, %57, %58, %59, %60, %61, %62, %63, %64, %65, %66, %67, %68, %69, %70, %71, %72, %73, %74, %75, %76, %77, %78, %79, %80, %81, %82, %83, %84, %85, %86, %87, %88, %89, %90, %91, %92, %93, %94, %95, %96, %97, %98, %99, %100, %101, %102, %103, %104, %105, %106, %107, %108, %109, %110, %111, %112, %113, %114, %115, %116, %117, %118, %119, %120, %121, %122, %123, %124, %125, %126, %127}, "
    "a, b, 1, 1, 1, 0, 1;\n"
    "wgmma.commit_group.sync.aligned;\n}"
    : "+f"(d[0]), "+f"(d[1]), "+f"(d[2]), "+f"(d[3]), "+f"(d[4]), "+f"(d[5]), "+f"(d[6]), "+f"(d[7]), "+f"(d[8]), "+f"(d[9]), "+f"(d[10]), "+f"(d[11]), "+f"(d[12]), "+f"(d[13]), "+f"(d[14]), "+f"(d[15]), "+f"(d[16]), "+f"(d[17]), "+f"(d[18]), "+f"(d[19]), "+f"(d[20]), "+f"(d[21]), "+f"(d[22]), "+f"(d[23]), "+f"(d[24]), "+f"(d[25]), "+f"(d[26]), "+f"(d[27]), "+f"(d[28]), "+f"(d[29]), "+f"(d[30]), "+f"(d[31]), "+f"(d[32]), "+f"(d[33]), "+f"(d[34]), "+f"(d[35]), "+f"(d[36]), "+f"(d[37]), "+f"(d[38]), "+f"(d[39]), "+f"(d[40]), "+f"(d[41]), "+f"(d[42]), "+f"(d[43]), "+f"(d[44]), "+f"(d[45]), "+f"(d[46]), "+f"(d[47]), "+f"(d[48]), "+f"(d[49]), "+f"(d[50]), "+f"(d[51]), "+f"(d[52]), "+f"(d[53]), "+f"(d[54]), "+f"(d[55]), "+f"(d[56]), "+f"(d[57]), "+f"(d[58]), "+f"(d[59]), "+f"(d[60]), "+f"(d[61]), "+f"(d[62]), "+f"(d[63]), "+f"(d[64]), "+f"(d[65]), "+f"(d[66]), "+f"(d[67]), "+f"(d[68]), "+f"(d[69]), "+f"(d[70]), "+f"(d[71]), "+f"(d[72]), "+f"(d[73]), "+f"(d[74]), "+f"(d[75]), "+f"(d[76]), "+f"(d[77]), "+f"(d[78]), "+f"(d[79]), "+f"(d[80]), "+f"(d[81]), "+f"(d[82]), "+f"(d[83]), "+f"(d[84]), "+f"(d[85]), "+f"(d[86]), "+f"(d[87]), "+f"(d[88]), "+f"(d[89]), "+f"(d[90]), "+f"(d[91]), "+f"(d[92]), "+f"(d[93]), "+f"(d[94]), "+f"(d[95]), "+f"(d[96]), "+f"(d[97]), "+f"(d[98]), "+f"(d[99]), "+f"(d[100]), "+f"(d[101]), "+f"(d[102]), "+f"(d[103]), "+f"(d[104]), "+f"(d[105]), "+f"(d[106]), "+f"(d[107]), "+f"(d[108]), "+f"(d[109]), "+f"(d[110]), "+f"(d[111]), "+f"(d[112]), "+f"(d[113]), "+f"(d[114]), "+f"(d[115]), "+f"(d[116]), "+f"(d[117]), "+f"(d[118]), "+f"(d[119]), "+f"(d[120]), "+f"(d[121]), "+f"(d[122]), "+f"(d[123]), "+f"(d[124]), "+f"(d[125]), "+f"(d[126]), "+f"(d[127]), "+r"(db)
    : "r"(da), "r"(h0), "r"(h1), "r"(one) : "memory");
}
template <int S> __device__ __forceinline__ uint2 wgmma_loop128_0(float (&d)[S], uint32_t& db, uint32_t& g8, uint32_t& a8, uint32_t& pa, uint32_t& cb, uint32_t& ca,
    uint32_t h0, uint32_t h1, uint32_t one, uint32_t aend, uint32_t ev, uint32_t chk, uint32_t so) {
  uint2 ok;
  asm volatile("{\n.reg .b64 a, b, s, s2;\n.reg .b32 t, u, nb, xb, xa, v0, v1, ad;\n.reg .pred p, q, e, f, c, r;\nelect.sync _|e, 0xffffffff;\nLOOP:\nmov.b32 xa, %4;\nwgmma.fence.sync.aligned;\n"
    "and.b32 u, %2, 0xffffdfff;\nmad.lo.u32 t, xa, 64, %83;\n"
    "mov.b64 a, {t, %72};\nmov.b64 b, {u, %73};\n"
    "wgmma.mma_async.sync.aligned.m64n128k16.f32.bf16.bf16 {%8, %9, %10, %11, %12, %13, %14, %15, %16, %17, %18, %19, %20, %21, %22, %23, %24, %25, %26, %27, %28, %29, %30, %31, %32, %33, %34, %35, %36, %37, %38, %39, %40, %41, %42, %43, %44, %45, %46, %47, %48, %49, %50, %51, %52, %53, %54, %55, %56, %57, %58, %59, %60, %61, %62, %63, %64, %65, %66, %67, %68, %69, %70, %71}, a, b, 1, 1, 1, 0, 1;\n"
    "and.b32 xb, %3, 56;\nadd.u32 %3, %3, %85;\nadd.u32 %5, %5, %86;\nadd.u32 %4, %4, 8;\nsetp.ge.u32 f, %4, %75;\n@f sub.u32 %4, %4, 48;\n"
    "and.b32 nb, %3, 56;\nmov.b64 s, {%3, %3};\nmov.b64 s2, {%5, %5};\n"
    "mad.lo.u32 t, %74, 2, t;\nmad.lo.u32 u, %74, 128, u;\n"
    "mov.b64 a, {t, %72};\nmov.b64 b, {u, %73};\n"
    "wgmma.mma_async.sync.aligned.m64n128k16.f32.bf16.bf16 {%8, %9, %10, %11, %12, %13, %14, %15, %16, %17, %18, %19, %20, %21, %22, %23, %24, %25, %26, %27, %28, %29, %30, %31, %32, %33, %34, %35, %36, %37, %38, %39, %40, %41, %42, %43, %44, %45, %46, %47, %48, %49, %50, %51, %52, %53, %54, %55, %56, %57, %58, %59, %60, %61, %62, %63, %64, %65, %66, %67, %68, %69, %70, %71}, a, b, 1, 1, 1, 0, 1;\n"
    "mbarrier.test_wait.shared::cta.b64 p, [nb + %79], s;\nmbarrier.test_wait.shared::cta.b64 q, [%4 + %80], s2;\n"
    "mad.lo.u32 t, %74, 2, t;\nmad.lo.u32 u, %74, 128, u;\n"
    "mov.b64 a, {t, %72};\nmov.b64 b, {u, %73};\n"
    "wgmma.mma_async.sync.aligned.m64n128k16.f32.bf16.bf16 {%8, %9, %10, %11, %12, %13, %14, %15, %16, %17, %18, %19, %20, %21, %22, %23, %24, %25, %26, %27, %28, %29, %30, %31, %32, %33, %34, %35, %36, %37, %38, %39, %40, %41, %42, %43, %44, %45, %46, %47, %48, %49, %50, %51, %52, %53, %54, %55, %56, %57, %58, %59, %60, %61, %62, %63, %64, %65, %66, %67, %68, %69, %70, %71}, a, b, 1, 1, 1, 0, 1;\n"
    "mad.lo.u32 t, %74, 2, t;\nmad.lo.u32 u, %74, 128, u;\n"
    "mov.b64 a, {t, %72};\nmov.b64 b, {u, %73};\n"
    "wgmma.mma_async.sync.aligned.m64n128k16.f32.bf16.bf16 {%8, %9, %10, %11, %12, %13, %14, %15, %16, %17, %18, %19, %20, %21, %22, %23, %24, %25, %26, %27, %28, %29, %30, %31, %32, %33, %34, %35, %36, %37, %38, %39, %40, %41, %42, %43, %44, %45, %46, %47, %48, %49, %50, %51, %52, %53, %54, %55, %56, %57, %58, %59, %60, %61, %62, %63, %64, %65, %66, %67, %68, %69, %70, %71}, a, b, 1, 1, 1, 0, 1;\n"
    "wgmma.commit_group.sync.aligned;\nadd.u32 %2, u, 640;\n"
    "wgmma.wait_group.sync.aligned 1;\n@e mbarrier.arrive.shared::cta.b64 _, [%6 + %81];\n@e mbarrier.arrive.shared::cta.b64 _, [%7 + %82];\nmov.b32 %6, xb;\nmov.b32 %7, xa;\n"
    "setp.eq.u32 f, %76, %3;\nand.pred r, p, q;\n@f bra.uni DONE;\n@r bra.uni LOOP;\nWAIT:\nmbarrier.try_wait.shared::cta.b64 p, [nb + %79], s;\nmbarrier.try_wait.shared::cta.b64 q, [%4 + %80], s2;\nand.pred r, p, q;\n@!r bra.uni WAIT;\nbra.uni LOOP;\n"
    "DONE:\nselp.u32 %0, 1, 0, r;\nselp.u32 %1, 1, 0, p;\n}\n"
    : "=r"(ok.x), "=r"(ok.y), "+r"(db), "+r"(g8), "+r"(a8), "+r"(pa), "+r"(cb), "+r"(ca), "+f"(d[0]), "+f"(d[1]), "+f"(d[2]), "+f"(d[3]), "+f"(d[4]), "+f"(d[5]), "+f"(d[6]), "+f"(d[7]), "+f"(d[8]), "+f"(d[9]), "+f"(d[10]), "+f"(d[11]), "+f"(d[12]), "+f"(d[13]), "+f"(d[14]), "+f"(d[15]), "+f"(d[16]), "+f"(d[17]), "+f"(d[18]), "+f"(d[19]), "+f"(d[20]), "+f"(d[21]), "+f"(d[22]), "+f"(d[23]), "+f"(d[24]), "+f"(d[25]), "+f"(d[26]), "+f"(d[27]), "+f"(d[28]), "+f"(d[29]), "+f"(d[30]), "+f"(d[31]), "+f"(d[32]), "+f"(d[33]), "+f"(d[34]), "+f"(d[35]), "+f"(d[36]), "+f"(d[37]), "+f"(d[38]), "+f"(d[39]), "+f"(d[40]), "+f"(d[41]), "+f"(d[42]), "+f"(d[43]), "+f"(d[44]), "+f"(d[45]), "+f"(d[46]), "+f"(d[47]), "+f"(d[48]), "+f"(d[49]), "+f"(d[50]), "+f"(d[51]), "+f"(d[52]), "+f"(d[53]), "+f"(d[54]), "+f"(d[55]), "+f"(d[56]), "+f"(d[57]), "+f"(d[58]), "+f"(d[59]), "+f"(d[60]), "+f"(d[61]), "+f"(d[62]), "+f"(d[63])
    : "r"(h0), "r"(h1), "r"(one), "r"(aend), "r"(ev), "r"(chk), "r"(so), "n"(SB + BAR_FULLB), "n"(SB + BAR_FULLA), "n"(SB + BAR_EMPTYB), "n"(SB + BAR_EMPTYA), "n"(DA0), "n"(DB0), "n"(G1), "n"(PA1) : "memory");
  return ok;
}
template <int S> __device__ __forceinline__ uint2 wgmma_loop128_1(float (&d)[S], uint32_t& db, uint32_t& g8, uint32_t& a8, uint32_t& pa, uint32_t& cb, uint32_t& ca,
    uint32_t h0, uint32_t h1, uint32_t one, uint32_t aend, uint32_t ev, uint32_t chk, uint32_t so) {
  uint2 ok;
  asm volatile("{\n.reg .b64 a, b, s, s2;\n.reg .b32 t, u, nb, xb, xa, v0, v1, ad;\n.reg .pred p, q, e, f, c, r;\nelect.sync _|e, 0xffffffff;\nsetp.ne.u32 c, %77, 0;\nLOOP:\nmov.b32 xa, %4;\nwgmma.fence.sync.aligned;\n"
    "and.b32 u, %2, 0xffffdfff;\nmad.lo.u32 t, xa, 64, %83;\n"
    "mov.b64 a, {t, %72};\nmov.b64 b, {u, %73};\n"
    "wgmma.mma_async.sync.aligned.m64n128k16.f32.bf16.bf16 {%8, %9, %10, %11, %12, %13, %14, %15, %16, %17, %18, %19, %20, %21, %22, %23, %24, %25, %26, %27, %28, %29, %30, %31, %32, %33, %34, %35, %36, %37, %38, %39, %40, %41, %42, %43, %44, %45, %46, %47, %48, %49, %50, %51, %52, %53, %54, %55, %56, %57, %58, %59, %60, %61, %62, %63, %64, %65, %66, %67, %68, %69, %70, %71}, a, b, 1, 1, 1, 0, 1;\n"
    "and.b32 xb, %3, 56;\nadd.u32 %3, %3, %85;\nadd.u32 %5, %5, %86;\nadd.u32 %4, %4, 8;\nsetp.ge.u32 f, %4, %75;\n@f sub.u32 %4, %4, 48;\n"
    "and.b32 nb, %3, 56;\nmov.b64 s, {%3, %3};\nmov.b64 s2, {%5, %5};\n"
    "mad.lo.u32 t, %74, 2, t;\nmad.lo.u32 u, %74, 128, u;\n"
    "mov.b64 a, {t, %72};\nmov.b64 b, {u, %73};\n"
    "wgmma.mma_async.sync.aligned.m64n128k16.f32.bf16.bf16 {%8, %9, %10, %11, %12, %13, %14, %15, %16, %17, %18, %19, %20, %21, %22, %23, %24, %25, %26, %27, %28, %29, %30, %31, %32, %33, %34, %35, %36, %37, %38, %39, %40, %41, %42, %43, %44, %45, %46, %47, %48, %49, %50, %51, %52, %53, %54, %55, %56, %57, %58, %59, %60, %61, %62, %63, %64, %65, %66, %67, %68, %69, %70, %71}, a, b, 1, 1, 1, 0, 1;\n"
    "mbarrier.test_wait.shared::cta.b64 p, [nb + %79], s;\nmbarrier.test_wait.shared::cta.b64 q, [%4 + %80], s2;\n"
    "mad.lo.u32 t, %74, 2, t;\nmad.lo.u32 u, %74, 128, u;\n"
    "mov.b64 a, {t, %72};\nmov.b64 b, {u, %73};\n"
    "wgmma.mma_async.sync.aligned.m64n128k16.f32.bf16.bf16 {%8, %9, %10, %11, %12, %13, %14, %15, %16, %17, %18, %19, %20, %21, %22, %23, %24, %25, %26, %27, %28, %29, %30, %31, %32, %33, %34, %35, %36, %37, %38, %39, %40, %41, %42, %43, %44, %45, %46, %47, %48, %49, %50, %51, %52, %53, %54, %55, %56, %57, %58, %59, %60, %61, %62, %63, %64, %65, %66, %67, %68, %69, %70, %71}, a, b, 1, 1, 1, 0, 1;\n"
    "mad.lo.u32 t, %74, 2, t;\nmad.lo.u32 u, %74, 128, u;\n"
    "mov.b64 a, {t, %72};\nmov.b64 b, {u, %73};\n"
    "wgmma.mma_async.sync.aligned.m64n128k16.f32.bf16.bf16 {%8, %9, %10, %11, %12, %13, %14, %15, %16, %17, %18, %19, %20, %21, %22, %23, %24, %25, %26, %27, %28, %29, %30, %31, %32, %33, %34, %35, %36, %37, %38, %39, %40, %41, %42, %43, %44, %45, %46, %47, %48, %49, %50, %51, %52, %53, %54, %55, %56, %57, %58, %59, %60, %61, %62, %63, %64, %65, %66, %67, %68, %69, %70, %71}, a, b, 1, 1, 1, 0, 1;\n"
    "wgmma.commit_group.sync.aligned;\nadd.u32 %2, u, 640;\n"
    "@c bra.uni VAL;\n"
    "wgmma.wait_group.sync.aligned 1;\n@e mbarrier.arrive.shared::cta.b64 _, [%6 + %81];\n@e mbarrier.arrive.shared::cta.b64 _, [%7 + %82];\nmov.b32 %6, xb;\nmov.b32 %7, xa;\n"
    "setp.eq.u32 f, %76, %3;\nand.pred r, p, q;\n@f bra.uni DONE;\n@r bra.uni LOOP;\nWAIT:\nmbarrier.try_wait.shared::cta.b64 p, [nb + %79], s;\nmbarrier.try_wait.shared::cta.b64 q, [%4 + %80], s2;\nand.pred r, p, q;\n@!r bra.uni WAIT;\nbra.uni LOOP;\n"
    "VAL:\nand.pred r, p, q;\nshl.b32 ad, %4, 10;\nadd.u32 ad, ad, %78;\nmov.b32 v0, -1;\nmov.b32 v1, -1;\n@r ld.shared.b32 v0, [ad];\n@r ld.shared.b32 v1, [ad + 1024];\n"
    "wgmma.wait_group.sync.aligned 1;\n@e mbarrier.arrive.shared::cta.b64 _, [%6 + %81];\n@e mbarrier.arrive.shared::cta.b64 _, [%7 + %82];\nmov.b32 %6, xb;\nmov.b32 %7, xa;\n"
    "CHK:\nmax.u32 v0, v0, v1;\nsetp.ne.u32 f, v0, -1;\nvote.sync.all.pred q, f, 0xffffffff;\nsetp.ne.and.u32 f, %76, %3, q;\n@f bra.uni LOOP;\n"
    "setp.eq.or.u32 f, %76, %3, r;\nmov.pred r, q;\n@f bra.uni DONE;\nWAITV:\nmbarrier.try_wait.shared::cta.b64 p, [nb + %79], s;\nmbarrier.try_wait.shared::cta.b64 q, [%4 + %80], s2;\nand.pred r, p, q;\n@!r bra.uni WAITV;\nld.shared.b32 v0, [ad];\nld.shared.b32 v1, [ad + 1024];\nbra.uni CHK;\n"
    "DONE:\nselp.u32 %0, 1, 0, r;\nselp.u32 %1, 1, 0, p;\n}\n"
    : "=r"(ok.x), "=r"(ok.y), "+r"(db), "+r"(g8), "+r"(a8), "+r"(pa), "+r"(cb), "+r"(ca), "+f"(d[0]), "+f"(d[1]), "+f"(d[2]), "+f"(d[3]), "+f"(d[4]), "+f"(d[5]), "+f"(d[6]), "+f"(d[7]), "+f"(d[8]), "+f"(d[9]), "+f"(d[10]), "+f"(d[11]), "+f"(d[12]), "+f"(d[13]), "+f"(d[14]), "+f"(d[15]), "+f"(d[16]), "+f"(d[17]), "+f"(d[18]), "+f"(d[19]), "+f"(d[20]), "+f"(d[21]), "+f"(d[22]), "+f"(d[23]), "+f"(d[24]), "+f"(d[25]), "+f"(d[26]), "+f"(d[27]), "+f"(d[28]), "+f"(d[29]), "+f"(d[30]), "+f"(d[31]), "+f"(d[32]), "+f"(d[33]), "+f"(d[34]), "+f"(d[35]), "+f"(d[36]), "+f"(d[37]), "+f"(d[38]), "+f"(d[39]), "+f"(d[40]), "+f"(d[41]), "+f"(d[42]), "+f"(d[43]), "+f"(d[44]), "+f"(d[45]), "+f"(d[46]), "+f"(d[47]), "+f"(d[48]), "+f"(d[49]), "+f"(d[50]), "+f"(d[51]), "+f"(d[52]), "+f"(d[53]), "+f"(d[54]), "+f"(d[55]), "+f"(d[56]), "+f"(d[57]), "+f"(d[58]), "+f"(d[59]), "+f"(d[60]), "+f"(d[61]), "+f"(d[62]), "+f"(d[63])
    : "r"(h0), "r"(h1), "r"(one), "r"(aend), "r"(ev), "r"(chk), "r"(so), "n"(SB + BAR_FULLB), "n"(SB + BAR_FULLA), "n"(SB + BAR_EMPTYB), "n"(SB + BAR_EMPTYA), "n"(DA0), "n"(DB0), "n"(G1), "n"(PA1) : "memory");
  return ok;
}
template <int S> __device__ __forceinline__ uint2 wgmma_loop192_0(float (&d)[S], uint32_t& db, uint32_t& g8, uint32_t& a8, uint32_t& pa, uint32_t& cb, uint32_t& ca,
    uint32_t h0, uint32_t h1, uint32_t one, uint32_t aend, uint32_t ev, uint32_t chk, uint32_t so) {
  uint2 ok;
  asm volatile("{\n.reg .b64 a, b, s, s2;\n.reg .b32 t, u, nb, xb, xa, v0, v1, ad;\n.reg .pred p, q, e, f, c, r;\nelect.sync _|e, 0xffffffff;\nLOOP:\nmov.b32 xa, %4;\nwgmma.fence.sync.aligned;\n"
    "setp.eq.u32 f, %2, %116 + 7680;\nselp.b32 u, %116, %2, f;\nmad.lo.u32 t, xa, 64, %115;\n"
    "mov.b64 a, {t, %104};\nmov.b64 b, {u, %105};\n"
    "wgmma.mma_async.sync.aligned.m64n192k16.f32.bf16.bf16 {%8, %9, %10, %11, %12, %13, %14, %15, %16, %17, %18, %19, %20, %21, %22, %23, %24, %25, %26, %27, %28, %29, %30, %31, %32, %33, %34, %35, %36, %37, %38, %39, %40, %41, %42, %43, %44, %45, %46, %47, %48, %49, %50, %51, %52, %53, %54, %55, %56, %57, %58, %59, %60, %61, %62, %63, %64, %65, %66, %67, %68, %69, %70, %71, %72, %73, %74, %75, %76, %77, %78, %79, %80, %81, %82, %83, %84, %85, %86, %87, %88, %89, %90, %91, %92, %93, %94, %95, %96, %97, %98, %99, %100, %101, %102, %103}, a, b, 1, 1, 1, 0, 1;\n"
    "and.b32 xb, %3, 56;\nadd.u32 %3, %3, %117;\nadd.u32 %5, %5, %118;\nadd.u32 %4, %4, 8;\nsetp.ge.u32 f, %4, %107;\n@f sub.u32 %4, %4, 48;\n"
    "and.b32 nb, %3, 56;\nmov.b64 s, {%3, %3};\nmov.b64 s2, {%5, %5};\n"
    "mad.lo.u32 t, %106, 2, t;\nmad.lo.u32 u, %106, 128, u;\n"
    "mov.b64 a, {t, %104};\nmov.b64 b, {u, %105};\n"
    "wgmma.mma_async.sync.aligned.m64n192k16.f32.bf16.bf16 {%8, %9, %10, %11, %12, %13, %14, %15, %16, %17, %18, %19, %20, %21, %22, %23, %24, %25, %26, %27, %28, %29, %30, %31, %32, %33, %34, %35, %36, %37, %38, %39, %40, %41, %42, %43, %44, %45, %46, %47, %48, %49, %50, %51, %52, %53, %54, %55, %56, %57, %58, %59, %60, %61, %62, %63, %64, %65, %66, %67, %68, %69, %70, %71, %72, %73, %74, %75, %76, %77, %78, %79, %80, %81, %82, %83, %84, %85, %86, %87, %88, %89, %90, %91, %92, %93, %94, %95, %96, %97, %98, %99, %100, %101, %102, %103}, a, b, 1, 1, 1, 0, 1;\n"
    "mbarrier.test_wait.shared::cta.b64 p, [nb + %111], s;\nmbarrier.test_wait.shared::cta.b64 q, [%4 + %112], s2;\n"
    "mad.lo.u32 t, %106, 2, t;\nmad.lo.u32 u, %106, 128, u;\n"
    "mov.b64 a, {t, %104};\nmov.b64 b, {u, %105};\n"
    "wgmma.mma_async.sync.aligned.m64n192k16.f32.bf16.bf16 {%8, %9, %10, %11, %12, %13, %14, %15, %16, %17, %18, %19, %20, %21, %22, %23, %24, %25, %26, %27, %28, %29, %30, %31, %32, %33, %34, %35, %36, %37, %38, %39, %40, %41, %42, %43, %44, %45, %46, %47, %48, %49, %50, %51, %52, %53, %54, %55, %56, %57, %58, %59, %60, %61, %62, %63, %64, %65, %66, %67, %68, %69, %70, %71, %72, %73, %74, %75, %76, %77, %78, %79, %80, %81, %82, %83, %84, %85, %86, %87, %88, %89, %90, %91, %92, %93, %94, %95, %96, %97, %98, %99, %100, %101, %102, %103}, a, b, 1, 1, 1, 0, 1;\n"
    "mad.lo.u32 t, %106, 2, t;\nmad.lo.u32 u, %106, 128, u;\n"
    "mov.b64 a, {t, %104};\nmov.b64 b, {u, %105};\n"
    "wgmma.mma_async.sync.aligned.m64n192k16.f32.bf16.bf16 {%8, %9, %10, %11, %12, %13, %14, %15, %16, %17, %18, %19, %20, %21, %22, %23, %24, %25, %26, %27, %28, %29, %30, %31, %32, %33, %34, %35, %36, %37, %38, %39, %40, %41, %42, %43, %44, %45, %46, %47, %48, %49, %50, %51, %52, %53, %54, %55, %56, %57, %58, %59, %60, %61, %62, %63, %64, %65, %66, %67, %68, %69, %70, %71, %72, %73, %74, %75, %76, %77, %78, %79, %80, %81, %82, %83, %84, %85, %86, %87, %88, %89, %90, %91, %92, %93, %94, %95, %96, %97, %98, %99, %100, %101, %102, %103}, a, b, 1, 1, 1, 0, 1;\n"
    "wgmma.commit_group.sync.aligned;\nadd.u32 %2, u, 1152;\n"
    "wgmma.wait_group.sync.aligned 1;\n@e mbarrier.arrive.shared::cta.b64 _, [%6 + %113];\n@e mbarrier.arrive.shared::cta.b64 _, [%7 + %114];\nmov.b32 %6, xb;\nmov.b32 %7, xa;\n"
    "setp.eq.u32 f, %108, %3;\nand.pred r, p, q;\n@f bra.uni DONE;\n@r bra.uni LOOP;\nWAIT:\nmbarrier.try_wait.shared::cta.b64 p, [nb + %111], s;\nmbarrier.try_wait.shared::cta.b64 q, [%4 + %112], s2;\nand.pred r, p, q;\n@!r bra.uni WAIT;\nbra.uni LOOP;\n"
    "DONE:\nselp.u32 %0, 1, 0, r;\nselp.u32 %1, 1, 0, p;\n}\n"
    : "=r"(ok.x), "=r"(ok.y), "+r"(db), "+r"(g8), "+r"(a8), "+r"(pa), "+r"(cb), "+r"(ca), "+f"(d[0]), "+f"(d[1]), "+f"(d[2]), "+f"(d[3]), "+f"(d[4]), "+f"(d[5]), "+f"(d[6]), "+f"(d[7]), "+f"(d[8]), "+f"(d[9]), "+f"(d[10]), "+f"(d[11]), "+f"(d[12]), "+f"(d[13]), "+f"(d[14]), "+f"(d[15]), "+f"(d[16]), "+f"(d[17]), "+f"(d[18]), "+f"(d[19]), "+f"(d[20]), "+f"(d[21]), "+f"(d[22]), "+f"(d[23]), "+f"(d[24]), "+f"(d[25]), "+f"(d[26]), "+f"(d[27]), "+f"(d[28]), "+f"(d[29]), "+f"(d[30]), "+f"(d[31]), "+f"(d[32]), "+f"(d[33]), "+f"(d[34]), "+f"(d[35]), "+f"(d[36]), "+f"(d[37]), "+f"(d[38]), "+f"(d[39]), "+f"(d[40]), "+f"(d[41]), "+f"(d[42]), "+f"(d[43]), "+f"(d[44]), "+f"(d[45]), "+f"(d[46]), "+f"(d[47]), "+f"(d[48]), "+f"(d[49]), "+f"(d[50]), "+f"(d[51]), "+f"(d[52]), "+f"(d[53]), "+f"(d[54]), "+f"(d[55]), "+f"(d[56]), "+f"(d[57]), "+f"(d[58]), "+f"(d[59]), "+f"(d[60]), "+f"(d[61]), "+f"(d[62]), "+f"(d[63]), "+f"(d[64]), "+f"(d[65]), "+f"(d[66]), "+f"(d[67]), "+f"(d[68]), "+f"(d[69]), "+f"(d[70]), "+f"(d[71]), "+f"(d[72]), "+f"(d[73]), "+f"(d[74]), "+f"(d[75]), "+f"(d[76]), "+f"(d[77]), "+f"(d[78]), "+f"(d[79]), "+f"(d[80]), "+f"(d[81]), "+f"(d[82]), "+f"(d[83]), "+f"(d[84]), "+f"(d[85]), "+f"(d[86]), "+f"(d[87]), "+f"(d[88]), "+f"(d[89]), "+f"(d[90]), "+f"(d[91]), "+f"(d[92]), "+f"(d[93]), "+f"(d[94]), "+f"(d[95])
    : "r"(h0), "r"(h1), "r"(one), "r"(aend), "r"(ev), "r"(chk), "r"(so), "n"(SB + BAR_FULLB), "n"(SB + BAR_FULLA), "n"(SB + BAR_EMPTYB), "n"(SB + BAR_EMPTYA), "n"(DA0), "n"(DB0), "n"(G1), "n"(PA1) : "memory");
  return ok;
}
template <int S> __device__ __forceinline__ uint2 wgmma_loop192_2(float (&d)[S], uint32_t& db, uint32_t& g8, uint32_t& a8, uint32_t& pa, uint32_t& cb, uint32_t& ca,
    uint32_t h0, uint32_t h1, uint32_t one, uint32_t aend, uint32_t ev, uint32_t chk, uint32_t so) {
  uint2 ok;
  asm volatile("{\n.reg .b64 a, b, s, s2;\n.reg .b32 t, u, nb, xb, xa, v0, v1, ad;\n.reg .pred p, q, e, f, c, r;\nelect.sync _|e, 0xffffffff;\nsetp.ne.u32 c, %109, 0;\nLOOP:\nmov.b32 xa, %4;\nwgmma.fence.sync.aligned;\n"
    "setp.eq.u32 f, %2, %116 + 7680;\nselp.b32 u, %116, %2, f;\nmad.lo.u32 t, xa, 64, %115;\n"
    "mov.b64 a, {t, %104};\nmov.b64 b, {u, %105};\n"
    "wgmma.mma_async.sync.aligned.m64n192k16.f32.bf16.bf16 {%8, %9, %10, %11, %12, %13, %14, %15, %16, %17, %18, %19, %20, %21, %22, %23, %24, %25, %26, %27, %28, %29, %30, %31, %32, %33, %34, %35, %36, %37, %38, %39, %40, %41, %42, %43, %44, %45, %46, %47, %48, %49, %50, %51, %52, %53, %54, %55, %56, %57, %58, %59, %60, %61, %62, %63, %64, %65, %66, %67, %68, %69, %70, %71, %72, %73, %74, %75, %76, %77, %78, %79, %80, %81, %82, %83, %84, %85, %86, %87, %88, %89, %90, %91, %92, %93, %94, %95, %96, %97, %98, %99, %100, %101, %102, %103}, a, b, 1, 1, 1, 0, 1;\n"
    "and.b32 xb, %3, 56;\nadd.u32 %3, %3, %117;\nadd.u32 %5, %5, %118;\nadd.u32 %4, %4, 8;\nsetp.ge.u32 f, %4, %107;\n@f sub.u32 %4, %4, 48;\n"
    "and.b32 nb, %3, 56;\nmov.b64 s, {%3, %3};\nmov.b64 s2, {%5, %5};\n"
    "mad.lo.u32 t, %106, 2, t;\nmad.lo.u32 u, %106, 128, u;\n"
    "mov.b64 a, {t, %104};\nmov.b64 b, {u, %105};\n"
    "wgmma.mma_async.sync.aligned.m64n192k16.f32.bf16.bf16 {%8, %9, %10, %11, %12, %13, %14, %15, %16, %17, %18, %19, %20, %21, %22, %23, %24, %25, %26, %27, %28, %29, %30, %31, %32, %33, %34, %35, %36, %37, %38, %39, %40, %41, %42, %43, %44, %45, %46, %47, %48, %49, %50, %51, %52, %53, %54, %55, %56, %57, %58, %59, %60, %61, %62, %63, %64, %65, %66, %67, %68, %69, %70, %71, %72, %73, %74, %75, %76, %77, %78, %79, %80, %81, %82, %83, %84, %85, %86, %87, %88, %89, %90, %91, %92, %93, %94, %95, %96, %97, %98, %99, %100, %101, %102, %103}, a, b, 1, 1, 1, 0, 1;\n"
    "mbarrier.test_wait.shared::cta.b64 p, [nb + %111], s;\nmbarrier.test_wait.shared::cta.b64 q, [%4 + %112], s2;\n"
    "mad.lo.u32 t, %106, 2, t;\nmad.lo.u32 u, %106, 128, u;\n"
    "mov.b64 a, {t, %104};\nmov.b64 b, {u, %105};\n"
    "wgmma.mma_async.sync.aligned.m64n192k16.f32.bf16.bf16 {%8, %9, %10, %11, %12, %13, %14, %15, %16, %17, %18, %19, %20, %21, %22, %23, %24, %25, %26, %27, %28, %29, %30, %31, %32, %33, %34, %35, %36, %37, %38, %39, %40, %41, %42, %43, %44, %45, %46, %47, %48, %49, %50, %51, %52, %53, %54, %55, %56, %57, %58, %59, %60, %61, %62, %63, %64, %65, %66, %67, %68, %69, %70, %71, %72, %73, %74, %75, %76, %77, %78, %79, %80, %81, %82, %83, %84, %85, %86, %87, %88, %89, %90, %91, %92, %93, %94, %95, %96, %97, %98, %99, %100, %101, %102, %103}, a, b, 1, 1, 1, 0, 1;\n"
    "mad.lo.u32 t, %106, 2, t;\nmad.lo.u32 u, %106, 128, u;\n"
    "mov.b64 a, {t, %104};\nmov.b64 b, {u, %105};\n"
    "wgmma.mma_async.sync.aligned.m64n192k16.f32.bf16.bf16 {%8, %9, %10, %11, %12, %13, %14, %15, %16, %17, %18, %19, %20, %21, %22, %23, %24, %25, %26, %27, %28, %29, %30, %31, %32, %33, %34, %35, %36, %37, %38, %39, %40, %41, %42, %43, %44, %45, %46, %47, %48, %49, %50, %51, %52, %53, %54, %55, %56, %57, %58, %59, %60, %61, %62, %63, %64, %65, %66, %67, %68, %69, %70, %71, %72, %73, %74, %75, %76, %77, %78, %79, %80, %81, %82, %83, %84, %85, %86, %87, %88, %89, %90, %91, %92, %93, %94, %95, %96, %97, %98, %99, %100, %101, %102, %103}, a, b, 1, 1, 1, 0, 1;\n"
    "wgmma.commit_group.sync.aligned;\nadd.u32 %2, u, 1152;\n"
    "VAL:\nand.pred r, p, q;\nshl.b32 ad, %4, 10;\nadd.u32 ad, ad, %110;\nselp.b32 v0, 0, -1, r;\nmov.b32 v1, 0;\nand.pred f, r, c;\n@f ld.shared.b32 v0, [ad];\n@f ld.shared.b32 v1, [ad + 1024];\n"
    "wgmma.wait_group.sync.aligned 1;\n@e mbarrier.arrive.shared::cta.b64 _, [%6 + %113];\n@e mbarrier.arrive.shared::cta.b64 _, [%7 + %114];\nmov.b32 %6, xb;\nmov.b32 %7, xa;\n"
    "CHK:\nmax.u32 v0, v0, v1;\nsetp.ne.u32 f, v0, -1;\nvote.sync.all.pred q, f, 0xffffffff;\nsetp.ne.and.u32 f, %108, %3, q;\n@f bra.uni LOOP;\n"
    "setp.eq.or.u32 f, %108, %3, r;\nmov.pred r, q;\n@f bra.uni DONE;\nWAITV:\nmbarrier.try_wait.shared::cta.b64 p, [nb + %111], s;\nmbarrier.try_wait.shared::cta.b64 q, [%4 + %112], s2;\nand.pred r, p, q;\n@!r bra.uni WAITV;\n@!c bra.uni LOOP;\nld.shared.b32 v0, [ad];\nld.shared.b32 v1, [ad + 1024];\nbra.uni CHK;\n"
    "DONE:\nselp.u32 %0, 1, 0, r;\nselp.u32 %1, 1, 0, p;\n}\n"
    : "=r"(ok.x), "=r"(ok.y), "+r"(db), "+r"(g8), "+r"(a8), "+r"(pa), "+r"(cb), "+r"(ca), "+f"(d[0]), "+f"(d[1]), "+f"(d[2]), "+f"(d[3]), "+f"(d[4]), "+f"(d[5]), "+f"(d[6]), "+f"(d[7]), "+f"(d[8]), "+f"(d[9]), "+f"(d[10]), "+f"(d[11]), "+f"(d[12]), "+f"(d[13]), "+f"(d[14]), "+f"(d[15]), "+f"(d[16]), "+f"(d[17]), "+f"(d[18]), "+f"(d[19]), "+f"(d[20]), "+f"(d[21]), "+f"(d[22]), "+f"(d[23]), "+f"(d[24]), "+f"(d[25]), "+f"(d[26]), "+f"(d[27]), "+f"(d[28]), "+f"(d[29]), "+f"(d[30]), "+f"(d[31]), "+f"(d[32]), "+f"(d[33]), "+f"(d[34]), "+f"(d[35]), "+f"(d[36]), "+f"(d[37]), "+f"(d[38]), "+f"(d[39]), "+f"(d[40]), "+f"(d[41]), "+f"(d[42]), "+f"(d[43]), "+f"(d[44]), "+f"(d[45]), "+f"(d[46]), "+f"(d[47]), "+f"(d[48]), "+f"(d[49]), "+f"(d[50]), "+f"(d[51]), "+f"(d[52]), "+f"(d[53]), "+f"(d[54]), "+f"(d[55]), "+f"(d[56]), "+f"(d[57]), "+f"(d[58]), "+f"(d[59]), "+f"(d[60]), "+f"(d[61]), "+f"(d[62]), "+f"(d[63]), "+f"(d[64]), "+f"(d[65]), "+f"(d[66]), "+f"(d[67]), "+f"(d[68]), "+f"(d[69]), "+f"(d[70]), "+f"(d[71]), "+f"(d[72]), "+f"(d[73]), "+f"(d[74]), "+f"(d[75]), "+f"(d[76]), "+f"(d[77]), "+f"(d[78]), "+f"(d[79]), "+f"(d[80]), "+f"(d[81]), "+f"(d[82]), "+f"(d[83]), "+f"(d[84]), "+f"(d[85]), "+f"(d[86]), "+f"(d[87]), "+f"(d[88]), "+f"(d[89]), "+f"(d[90]), "+f"(d[91]), "+f"(d[92]), "+f"(d[93]), "+f"(d[94]), "+f"(d[95])
    : "r"(h0), "r"(h1), "r"(one), "r"(aend), "r"(ev), "r"(chk), "r"(so), "n"(SB + BAR_FULLB), "n"(SB + BAR_FULLA), "n"(SB + BAR_EMPTYB), "n"(SB + BAR_EMPTYA), "n"(DA0), "n"(DB0), "n"(G1), "n"(PA1) : "memory");
  return ok;
}
template <int S> __device__ __forceinline__ uint2 wgmma_loop256_0(float (&d)[S], uint32_t& db, uint32_t& g8, uint32_t& a8, uint32_t& pa, uint32_t& cb, uint32_t& ca,
    uint32_t h0, uint32_t h1, uint32_t one, uint32_t aend, uint32_t ev, uint32_t chk, uint32_t so) {
  uint2 ok;
  asm volatile("{\n.reg .b64 a, b, s, s2;\n.reg .b32 t, u, nb, xb, xa, v0, v1, ad;\n.reg .pred p, q, e, f, c, r;\nelect.sync _|e, 0xffffffff;\nLOOP:\nmov.b32 xa, %4;\nwgmma.fence.sync.aligned;\n"
    "and.b32 u, %2, 0xffffdfff;\nmad.lo.u32 t, xa, 64, %147;\n"
    "mov.b64 a, {t, %136};\nmov.b64 b, {u, %137};\n"
    "wgmma.mma_async.sync.aligned.m64n256k16.f32.bf16.bf16 {%8, %9, %10, %11, %12, %13, %14, %15, %16, %17, %18, %19, %20, %21, %22, %23, %24, %25, %26, %27, %28, %29, %30, %31, %32, %33, %34, %35, %36, %37, %38, %39, %40, %41, %42, %43, %44, %45, %46, %47, %48, %49, %50, %51, %52, %53, %54, %55, %56, %57, %58, %59, %60, %61, %62, %63, %64, %65, %66, %67, %68, %69, %70, %71, %72, %73, %74, %75, %76, %77, %78, %79, %80, %81, %82, %83, %84, %85, %86, %87, %88, %89, %90, %91, %92, %93, %94, %95, %96, %97, %98, %99, %100, %101, %102, %103, %104, %105, %106, %107, %108, %109, %110, %111, %112, %113, %114, %115, %116, %117, %118, %119, %120, %121, %122, %123, %124, %125, %126, %127, %128, %129, %130, %131, %132, %133, %134, %135}, a, b, 1, 1, 1, 0, 1;\n"
    "and.b32 xb, %3, 56;\nadd.u32 %3, %3, %149;\nadd.u32 %5, %5, %150;\nadd.u32 %4, %4, 8;\nsetp.ge.u32 f, %4, %139;\n@f sub.u32 %4, %4, 48;\n"
    "and.b32 nb, %3, 56;\nmov.b64 s, {%3, %3};\nmov.b64 s2, {%5, %5};\n"
    "mad.lo.u32 t, %138, 2, t;\nmad.lo.u32 u, %138, 128, u;\n"
    "mov.b64 a, {t, %136};\nmov.b64 b, {u, %137};\n"
    "wgmma.mma_async.sync.aligned.m64n256k16.f32.bf16.bf16 {%8, %9, %10, %11, %12, %13, %14, %15, %16, %17, %18, %19, %20, %21, %22, %23, %24, %25, %26, %27, %28, %29, %30, %31, %32, %33, %34, %35, %36, %37, %38, %39, %40, %41, %42, %43, %44, %45, %46, %47, %48, %49, %50, %51, %52, %53, %54, %55, %56, %57, %58, %59, %60, %61, %62, %63, %64, %65, %66, %67, %68, %69, %70, %71, %72, %73, %74, %75, %76, %77, %78, %79, %80, %81, %82, %83, %84, %85, %86, %87, %88, %89, %90, %91, %92, %93, %94, %95, %96, %97, %98, %99, %100, %101, %102, %103, %104, %105, %106, %107, %108, %109, %110, %111, %112, %113, %114, %115, %116, %117, %118, %119, %120, %121, %122, %123, %124, %125, %126, %127, %128, %129, %130, %131, %132, %133, %134, %135}, a, b, 1, 1, 1, 0, 1;\n"
    "mad.lo.u32 t, %138, 2, t;\nmad.lo.u32 u, %138, 128, u;\n"
    "mov.b64 a, {t, %136};\nmov.b64 b, {u, %137};\n"
    "wgmma.mma_async.sync.aligned.m64n256k16.f32.bf16.bf16 {%8, %9, %10, %11, %12, %13, %14, %15, %16, %17, %18, %19, %20, %21, %22, %23, %24, %25, %26, %27, %28, %29, %30, %31, %32, %33, %34, %35, %36, %37, %38, %39, %40, %41, %42, %43, %44, %45, %46, %47, %48, %49, %50, %51, %52, %53, %54, %55, %56, %57, %58, %59, %60, %61, %62, %63, %64, %65, %66, %67, %68, %69, %70, %71, %72, %73, %74, %75, %76, %77, %78, %79, %80, %81, %82, %83, %84, %85, %86, %87, %88, %89, %90, %91, %92, %93, %94, %95, %96, %97, %98, %99, %100, %101, %102, %103, %104, %105, %106, %107, %108, %109, %110, %111, %112, %113, %114, %115, %116, %117, %118, %119, %120, %121, %122, %123, %124, %125, %126, %127, %128, %129, %130, %131, %132, %133, %134, %135}, a, b, 1, 1, 1, 0, 1;\n"
    "mad.lo.u32 t, %138, 2, t;\nmad.lo.u32 u, %138, 128, u;\n"
    "mov.b64 a, {t, %136};\nmov.b64 b, {u, %137};\n"
    "wgmma.mma_async.sync.aligned.m64n256k16.f32.bf16.bf16 {%8, %9, %10, %11, %12, %13, %14, %15, %16, %17, %18, %19, %20, %21, %22, %23, %24, %25, %26, %27, %28, %29, %30, %31, %32, %33, %34, %35, %36, %37, %38, %39, %40, %41, %42, %43, %44, %45, %46, %47, %48, %49, %50, %51, %52, %53, %54, %55, %56, %57, %58, %59, %60, %61, %62, %63, %64, %65, %66, %67, %68, %69, %70, %71, %72, %73, %74, %75, %76, %77, %78, %79, %80, %81, %82, %83, %84, %85, %86, %87, %88, %89, %90, %91, %92, %93, %94, %95, %96, %97, %98, %99, %100, %101, %102, %103, %104, %105, %106, %107, %108, %109, %110, %111, %112, %113, %114, %115, %116, %117, %118, %119, %120, %121, %122, %123, %124, %125, %126, %127, %128, %129, %130, %131, %132, %133, %134, %135}, a, b, 1, 1, 1, 0, 1;\n"
    "wgmma.commit_group.sync.aligned;\nadd.u32 %2, u, 1664;\n"
    "wgmma.wait_group.sync.aligned 1;\n@e mbarrier.arrive.shared::cta.b64 _, [%6 + %145];\n@e mbarrier.arrive.shared::cta.b64 _, [%7 + %146];\nmov.b32 %6, xb;\nmov.b32 %7, xa;\n"
    "setp.eq.u32 f, %140, %3;\n@f bra.uni DONE;\nWAIT:\nmbarrier.try_wait.shared::cta.b64 p, [nb + %143], s;\nmbarrier.try_wait.shared::cta.b64 q, [%4 + %144], s2;\nand.pred r, p, q;\n@!r bra.uni WAIT;\nbra.uni LOOP;\n"
    "DONE:\nmov.b32 %0, 0;\nmov.b32 %1, 0;\n}\n"
    : "=r"(ok.x), "=r"(ok.y), "+r"(db), "+r"(g8), "+r"(a8), "+r"(pa), "+r"(cb), "+r"(ca), "+f"(d[0]), "+f"(d[1]), "+f"(d[2]), "+f"(d[3]), "+f"(d[4]), "+f"(d[5]), "+f"(d[6]), "+f"(d[7]), "+f"(d[8]), "+f"(d[9]), "+f"(d[10]), "+f"(d[11]), "+f"(d[12]), "+f"(d[13]), "+f"(d[14]), "+f"(d[15]), "+f"(d[16]), "+f"(d[17]), "+f"(d[18]), "+f"(d[19]), "+f"(d[20]), "+f"(d[21]), "+f"(d[22]), "+f"(d[23]), "+f"(d[24]), "+f"(d[25]), "+f"(d[26]), "+f"(d[27]), "+f"(d[28]), "+f"(d[29]), "+f"(d[30]), "+f"(d[31]), "+f"(d[32]), "+f"(d[33]), "+f"(d[34]), "+f"(d[35]), "+f"(d[36]), "+f"(d[37]), "+f"(d[38]), "+f"(d[39]), "+f"(d[40]), "+f"(d[41]), "+f"(d[42]), "+f"(d[43]), "+f"(d[44]), "+f"(d[45]), "+f"(d[46]), "+f"(d[47]), "+f"(d[48]), "+f"(d[49]), "+f"(d[50]), "+f"(d[51]), "+f"(d[52]), "+f"(d[53]), "+f"(d[54]), "+f"(d[55]), "+f"(d[56]), "+f"(d[57]), "+f"(d[58]), "+f"(d[59]), "+f"(d[60]), "+f"(d[61]), "+f"(d[62]), "+f"(d[63]), "+f"(d[64]), "+f"(d[65]), "+f"(d[66]), "+f"(d[67]), "+f"(d[68]), "+f"(d[69]), "+f"(d[70]), "+f"(d[71]), "+f"(d[72]), "+f"(d[73]), "+f"(d[74]), "+f"(d[75]), "+f"(d[76]), "+f"(d[77]), "+f"(d[78]), "+f"(d[79]), "+f"(d[80]), "+f"(d[81]), "+f"(d[82]), "+f"(d[83]), "+f"(d[84]), "+f"(d[85]), "+f"(d[86]), "+f"(d[87]), "+f"(d[88]), "+f"(d[89]), "+f"(d[90]), "+f"(d[91]), "+f"(d[92]), "+f"(d[93]), "+f"(d[94]), "+f"(d[95]), "+f"(d[96]), "+f"(d[97]), "+f"(d[98]), "+f"(d[99]), "+f"(d[100]), "+f"(d[101]), "+f"(d[102]), "+f"(d[103]), "+f"(d[104]), "+f"(d[105]), "+f"(d[106]), "+f"(d[107]), "+f"(d[108]), "+f"(d[109]), "+f"(d[110]), "+f"(d[111]), "+f"(d[112]), "+f"(d[113]), "+f"(d[114]), "+f"(d[115]), "+f"(d[116]), "+f"(d[117]), "+f"(d[118]), "+f"(d[119]), "+f"(d[120]), "+f"(d[121]), "+f"(d[122]), "+f"(d[123]), "+f"(d[124]), "+f"(d[125]), "+f"(d[126]), "+f"(d[127])
    : "r"(h0), "r"(h1), "r"(one), "r"(aend), "r"(ev), "r"(chk), "r"(so), "n"(SB + BAR_FULLB), "n"(SB + BAR_FULLA), "n"(SB + BAR_EMPTYB), "n"(SB + BAR_EMPTYA), "n"(DA0), "n"(DB0), "n"(G1), "n"(PA1) : "memory");
  return ok;
}
template <int S> __device__ __forceinline__ void wgmma_aug192(float (&d)[S], uint32_t a0, uint32_t a1, uint32_t db, uint32_t h1) {
  asm volatile("{\n.reg .b64 b;\n.reg .b32 z;\nmov.b32 z, 0;\n"
    "mov.b64 b, {%98, %99};\nwgmma.fence.sync.aligned;\n"
    "wgmma.mma_async.sync.aligned.m64n192k16.f32.bf16.bf16 "
    "{%0, %1, %2, %3, %4, %5, %6, %7, %8, %9, %10, %11, %12, %13, %14, %15, %16, %17, %18, %19, %20, %21, %22, %23, %24, %25, %26, %27, %28, %29, %30, %31, %32, %33, %34, %35, %36, %37, %38, %39, %40, %41, %42, %43, %44, %45, %46, %47, %48, %49, %50, %51, %52, %53, %54, %55, %56, %57, %58, %59, %60, %61, %62, %63, %64, %65, %66, %67, %68, %69, %70, %71, %72, %73, %74, %75, %76, %77, %78, %79, %80, %81, %82, %83, %84, %85, %86, %87, %88, %89, %90, %91, %92, %93, %94, %95}, "
    "{%96, %97, z, z}, b, 1, 1, 1, 1;\n"
    "wgmma.commit_group.sync.aligned;\n}"
    : "+f"(d[0]), "+f"(d[1]), "+f"(d[2]), "+f"(d[3]), "+f"(d[4]), "+f"(d[5]), "+f"(d[6]), "+f"(d[7]), "+f"(d[8]), "+f"(d[9]), "+f"(d[10]), "+f"(d[11]), "+f"(d[12]), "+f"(d[13]), "+f"(d[14]), "+f"(d[15]), "+f"(d[16]), "+f"(d[17]), "+f"(d[18]), "+f"(d[19]), "+f"(d[20]), "+f"(d[21]), "+f"(d[22]), "+f"(d[23]), "+f"(d[24]), "+f"(d[25]), "+f"(d[26]), "+f"(d[27]), "+f"(d[28]), "+f"(d[29]), "+f"(d[30]), "+f"(d[31]), "+f"(d[32]), "+f"(d[33]), "+f"(d[34]), "+f"(d[35]), "+f"(d[36]), "+f"(d[37]), "+f"(d[38]), "+f"(d[39]), "+f"(d[40]), "+f"(d[41]), "+f"(d[42]), "+f"(d[43]), "+f"(d[44]), "+f"(d[45]), "+f"(d[46]), "+f"(d[47]), "+f"(d[48]), "+f"(d[49]), "+f"(d[50]), "+f"(d[51]), "+f"(d[52]), "+f"(d[53]), "+f"(d[54]), "+f"(d[55]), "+f"(d[56]), "+f"(d[57]), "+f"(d[58]), "+f"(d[59]), "+f"(d[60]), "+f"(d[61]), "+f"(d[62]), "+f"(d[63]), "+f"(d[64]), "+f"(d[65]), "+f"(d[66]), "+f"(d[67]), "+f"(d[68]), "+f"(d[69]), "+f"(d[70]), "+f"(d[71]), "+f"(d[72]), "+f"(d[73]), "+f"(d[74]), "+f"(d[75]), "+f"(d[76]), "+f"(d[77]), "+f"(d[78]), "+f"(d[79]), "+f"(d[80]), "+f"(d[81]), "+f"(d[82]), "+f"(d[83]), "+f"(d[84]), "+f"(d[85]), "+f"(d[86]), "+f"(d[87]), "+f"(d[88]), "+f"(d[89]), "+f"(d[90]), "+f"(d[91]), "+f"(d[92]), "+f"(d[93]), "+f"(d[94]), "+f"(d[95])
    : "r"(a0), "r"(a1), "r"(db), "r"(h1) : "memory");
}
template <int S> __device__ __forceinline__ void wgmma_aug256(float (&d)[S], uint32_t a0, uint32_t a1, uint32_t db, uint32_t h1) {
  asm volatile("{\n.reg .b64 b;\n.reg .b32 z;\nmov.b32 z, 0;\n"
    "mov.b64 b, {%130, %131};\nwgmma.fence.sync.aligned;\n"
    "wgmma.mma_async.sync.aligned.m64n256k16.f32.bf16.bf16 "
    "{%0, %1, %2, %3, %4, %5, %6, %7, %8, %9, %10, %11, %12, %13, %14, %15, %16, %17, %18, %19, %20, %21, %22, %23, %24, %25, %26, %27, %28, %29, %30, %31, %32, %33, %34, %35, %36, %37, %38, %39, %40, %41, %42, %43, %44, %45, %46, %47, %48, %49, %50, %51, %52, %53, %54, %55, %56, %57, %58, %59, %60, %61, %62, %63, %64, %65, %66, %67, %68, %69, %70, %71, %72, %73, %74, %75, %76, %77, %78, %79, %80, %81, %82, %83, %84, %85, %86, %87, %88, %89, %90, %91, %92, %93, %94, %95, %96, %97, %98, %99, %100, %101, %102, %103, %104, %105, %106, %107, %108, %109, %110, %111, %112, %113, %114, %115, %116, %117, %118, %119, %120, %121, %122, %123, %124, %125, %126, %127}, "
    "{%128, %129, z, z}, b, 1, 1, 1, 1;\n"
    "wgmma.commit_group.sync.aligned;\n}"
    : "+f"(d[0]), "+f"(d[1]), "+f"(d[2]), "+f"(d[3]), "+f"(d[4]), "+f"(d[5]), "+f"(d[6]), "+f"(d[7]), "+f"(d[8]), "+f"(d[9]), "+f"(d[10]), "+f"(d[11]), "+f"(d[12]), "+f"(d[13]), "+f"(d[14]), "+f"(d[15]), "+f"(d[16]), "+f"(d[17]), "+f"(d[18]), "+f"(d[19]), "+f"(d[20]), "+f"(d[21]), "+f"(d[22]), "+f"(d[23]), "+f"(d[24]), "+f"(d[25]), "+f"(d[26]), "+f"(d[27]), "+f"(d[28]), "+f"(d[29]), "+f"(d[30]), "+f"(d[31]), "+f"(d[32]), "+f"(d[33]), "+f"(d[34]), "+f"(d[35]), "+f"(d[36]), "+f"(d[37]), "+f"(d[38]), "+f"(d[39]), "+f"(d[40]), "+f"(d[41]), "+f"(d[42]), "+f"(d[43]), "+f"(d[44]), "+f"(d[45]), "+f"(d[46]), "+f"(d[47]), "+f"(d[48]), "+f"(d[49]), "+f"(d[50]), "+f"(d[51]), "+f"(d[52]), "+f"(d[53]), "+f"(d[54]), "+f"(d[55]), "+f"(d[56]), "+f"(d[57]), "+f"(d[58]), "+f"(d[59]), "+f"(d[60]), "+f"(d[61]), "+f"(d[62]), "+f"(d[63]), "+f"(d[64]), "+f"(d[65]), "+f"(d[66]), "+f"(d[67]), "+f"(d[68]), "+f"(d[69]), "+f"(d[70]), "+f"(d[71]), "+f"(d[72]), "+f"(d[73]), "+f"(d[74]), "+f"(d[75]), "+f"(d[76]), "+f"(d[77]), "+f"(d[78]), "+f"(d[79]), "+f"(d[80]), "+f"(d[81]), "+f"(d[82]), "+f"(d[83]), "+f"(d[84]), "+f"(d[85]), "+f"(d[86]), "+f"(d[87]), "+f"(d[88]), "+f"(d[89]), "+f"(d[90]), "+f"(d[91]), "+f"(d[92]), "+f"(d[93]), "+f"(d[94]), "+f"(d[95]), "+f"(d[96]), "+f"(d[97]), "+f"(d[98]), "+f"(d[99]), "+f"(d[100]), "+f"(d[101]), "+f"(d[102]), "+f"(d[103]), "+f"(d[104]), "+f"(d[105]), "+f"(d[106]), "+f"(d[107]), "+f"(d[108]), "+f"(d[109]), "+f"(d[110]), "+f"(d[111]), "+f"(d[112]), "+f"(d[113]), "+f"(d[114]), "+f"(d[115]), "+f"(d[116]), "+f"(d[117]), "+f"(d[118]), "+f"(d[119]), "+f"(d[120]), "+f"(d[121]), "+f"(d[122]), "+f"(d[123]), "+f"(d[124]), "+f"(d[125]), "+f"(d[126]), "+f"(d[127])
    : "r"(a0), "r"(a1), "r"(db), "r"(h1) : "memory");
}

__device__ __forceinline__ uint32_t clock32() { uint32_t c; asm volatile("mov.u32 %0, %%clock;" : "=r"(c)); return c; }
__device__ __forceinline__ void spin_until(uint32_t c) {
  asm volatile("{\n.reg .pred p;\n.reg .s32 t;\nLAB_WAIT:\nmov.u32 t, %%clock;\nsub.s32 t, t, %0;\nsetp.lt.s32 p, t, 0;\n@p bra.uni LAB_WAIT;\n}" ::"r"(c) : "memory");
}
struct Nop { __device__ __forceinline__ void operator()(int) const {} };
template <int V> struct IC { static constexpr int v = V; };
struct Pipe {
  uint32_t db, g8, a8, pa, tph, aend, curB, curA, prevB, prevA, bo, so, sph, h0, h1, one;
  uint2 nx;
  int w; bool l0;
  __device__ __forceinline__ int lane() const { return LSO ? (so >> 5) & 31 : threadIdx.x & 31; }
  __device__ __forceinline__ void adv_a() { a8 += 8; pa += PA1; if (a8 == aend) a8 -= NA * 8; }
  __device__ __forceinline__ uint32_t take() { const uint32_t a = SB + OFF_A + a8 * 1024; adv_a(); return a; }
  __device__ __forceinline__ uint32_t ahead(int d) const { uint32_t ls = a8 + d * 8; if (ls >= aend) ls -= NA * 8; return SB + OFF_A + ls * 1024; }
  __device__ __forceinline__ uint32_t wait_ahead(int d) {
    uint32_t ls = a8 + d * 8;
    if (ls >= aend) ls -= NA * 8;
    mbar_spin31(SB + BAR_FULLA + ls, pa + d * PA1);
    return SB + OFF_A + ls * 1024;
  }
  template <int N, bool FIRST, int S> __device__ __forceinline__ uint2 iss(float (&acc)[S], bool skip) {
    const uint32_t da = DA0 + a8 * 64;
    if (!FIRST) { if (N != 192) db &= ~0x2000u; else if (db == DB0 + 15 * 512) db = DB0; }
    prevB = curB; prevA = curA;
    curB = g8 & 56; curA = a8;
    g8 += G1;
    a8 += skip ? 16 : 8; pa += skip ? 2 * PA1 : PA1;
    if (a8 >= aend) a8 -= NA * 8;
    uint2 ok = make_uint2(0, 0);
    if constexpr (N == 128) {
      if (FIRST) wgmma_first128(acc, da, db, h0, h1, one);
      else ok = wgmma_probe128(acc, da, db, h0, h1, one, SB + BAR_FULLB + (g8 & 56), g8, SB + BAR_FULLA + a8, pa);
    }
    if constexpr (N == 192) {
      if (FIRST) wgmma_first192(acc, da, db, h0, h1, one);
      else ok = wgmma_probe192(acc, da, db, h0, h1, one, SB + BAR_FULLB + (g8 & 56), g8, SB + BAR_FULLA + a8, pa);
    }
    if constexpr (N == 256) { if (FIRST) wgmma_first256(acc, da, db, h0, h1, one); else wgmma_acc256(acc, da, db, h0, h1, one); }
    db += N * 8 - 384;
    return ok;
  }
  __device__ __forceinline__ void ensure(uint2 ok) {
    asm volatile(
        "{\n.reg .pred p, q;\n.reg .b64 s, t;\nmov.b64 s, {%1, %1};\nmov.b64 t, {%3, %3};\nsetp.ne.u32 p, %4, 0;\nsetp.ne.u32 q, %5, 0;\n@!p bra.uni LAB_WAIT;\n@q bra.uni DONE;\n"
        "LAB_WAIT:\nmbarrier.try_wait.shared::cta.b64 p, [%0], s;\nmbarrier.try_wait.shared::cta.b64 q, [%2], t;\n"
        "and.pred p, p, q;\n@!p bra.uni LAB_WAIT;\nDONE:\n}" ::"r"(SB + BAR_FULLB + (g8 & 56)), "r"(g8), "r"(SB + BAR_FULLA + a8), "r"(pa), "r"(ok.x), "r"(ok.y) : "memory");
  }
  template <class Hook> __device__ __forceinline__ void validate(bool check, const CUtensorMap* tm16, int c0, int c1, int wp, int j, Hook hook) {
    const uint32_t rows = SB + OFF_A + a8 * 1024 + wp * 2048, ad = a8 * 1024 + so;
    uint32_t v0 = 0, v1 = 0;
    asm volatile("{\n.reg .pred p;\nsetp.ne.u32 p, %3, 0;\n@p ld.shared.b32 %0, [%2];\n@p ld.shared.b32 %1, [%2 + 1024];\n}" : "+r"(v0), "+r"(v1) : "r"(ad), "r"((uint32_t)check));
    check = true;
    hook();
    while (__any_sync(~0u, check && max(v0, v1) == 0xffffffffu)) {
      const uint32_t bar = SB + BAR_SPEC + (w * 4 + wp) * 8;
      e_load<2048>(rows, tm16, c0 + sched_k(c_sched.v[j][(g8 >> 3) & 511]), c1 + wp * 16, bar);
      mbar_spin(bar, sph);
      sph ^= 1;
      v0 = lds32(ad); v1 = lds32(ad + 1024);
    }
  }
  __device__ __forceinline__ void drain() {
    wg_wait<0>();
    arrive_2(SB + BAR_EMPTYB + curB, SB + BAR_EMPTYA + curA, l0);
    curB = BAR_DUMMY - BAR_EMPTYB; curA = BAR_DUMMY - BAR_EMPTYA;
  }
  __device__ __forceinline__ void signal_server(uint32_t odd) { __syncwarp(); arrive_n(SB + BAR_SRV + w * 16 + odd * 8, l0); }
  __device__ __forceinline__ void signal_loader() { __syncwarp(); arrive_n(SB + BAR_STG + w * 8, l0); }
  template <int N, bool HOLD = false, int S, class Pre = Nop> __device__ __forceinline__ void begin(float (&acc)[S], uint32_t p0, int proft, Pre pre = Pre()) {
    db = DB0 + p0 * 512;
    const uint32_t c1 = HOLD ? clock32() : 0;
    ensure(make_uint2(0, 0));
    if (HOLD) spin_until(c1 + lds32(SB + OFF_HOLD + w * 4));
    pre(0);
    PROF_T(w, proft, 0);
    ensure(iss<N, true>(acc, false));
  }
  template <int N, bool ENSURE = true, int S, class Hook, class Mid = Nop> __device__ __forceinline__ void run(float (&acc)[S], int i0, int i1, uint32_t skips, int pause, Hook hook, int imid = -1, Mid mid = Mid()) {
    int i = i0, ev = imid >= 0 ? imid : (w ? pause : -1);
#pragma unroll 1
    while (true) {
      const uint2 ok = iss<N, false>(acc, (skips >> i) & 1);
      wg_wait<1>();
      arrive_2(SB + BAR_EMPTYB + prevB, SB + BAR_EMPTYA + prevA, l0);
      if (pause >= 0 && i + 1 == i1) { nx = ok; break; }
      if constexpr (ENSURE) { ensure(ok); hook(i); } else hook(i, ok);
      i++;
      if (pause < 0 && i == i1) break;
      if (i == ev) {
        const bool ps = w && i == pause;
        if (ps) drain();
        if (i == imid) mid(i);
        if (ps) mbar_spin(SB + BAR_LEAD, tph);
        ev = pause;
      }
    }
  }
  template <int N, bool V, int S> __device__ __forceinline__ uint2 steps(float (&acc)[S], uint32_t ev, uint32_t chk = 0) {
    asm volatile("mul.f32 %0, %0, %1;" : "+r"(ev) : "r"(one * 0x3f800000u));
    if constexpr (N == 128 && !V) return wgmma_loop128_0(acc, db, g8, a8, pa, curB, curA, h0, h1, one, aend, ev, chk, so);
    if constexpr (N == 128 && V) return wgmma_loop128_1(acc, db, g8, a8, pa, curB, curA, h0, h1, one, aend, ev, chk, so);
    if constexpr (N == 192 && !V) return wgmma_loop192_0(acc, db, g8, a8, pa, curB, curA, h0, h1, one, aend, ev, chk, so);
    if constexpr (N == 192 && V) return wgmma_loop192_2(acc, db, g8, a8, pa, curB, curA, h0, h1, one, aend, ev, chk, so);
    if constexpr (N == 256) return wgmma_loop256_0(acc, db, g8, a8, pa, curB, curA, h0, h1, one, aend, ev, chk, so);
  }
  template <int N, bool AUG, int S> __device__ __forceinline__ void end(float (&acc)[S], int ns, uint32_t pos, uint32_t au0, uint32_t au1, int proft) {
    uint32_t augB = 0;
    if (LEARLY) arrive_n(SB + BAR_LEAD + w * (BAR_DUMMY - BAR_LEAD), l0);
    if constexpr (AUG) {
      if (AGK && N == 192)
        asm volatile("{\n.reg .pred p;\n.reg .b64 s;\nmov.b64 s, {%1, %1};\nsetp.ne.u32 p, %2, 0;\n@p bra.uni DONE;\nLAB_WAIT:\nmbarrier.try_wait.shared::cta.b64 p, [%0], s;\n@!p bra.uni LAB_WAIT;\nDONE:\n}"
                     ::"r"(SB + BAR_FULLB + (g8 & 56)), "r"(g8), "r"(nx.x) : "memory");
      else mbar_spin31(SB + BAR_FULLB + (g8 & 56), g8);
      const uint32_t dc = (((SB + OFF_B) >> 4) | (64u << 16)) + pos * 512;
      if constexpr (N == 192) wgmma_aug192(acc, au0, au1, dc, h1); else wgmma_aug256(acc, au0, au1, dc, h1);
      augB = g8 & 56; g8 += G1;
    }
    if (!LEARLY) arrive_n(SB + BAR_LEAD + w * (BAR_DUMMY - BAR_LEAD), l0);
    tph ^= 1;
    if (ns > 0) wait_ahead(ns - 1);
    wg_wait<0>();
    arrive_2(SB + BAR_EMPTYB + curB, SB + BAR_EMPTYA + curA, l0);
    if (AUG) arrive_n(SB + BAR_EMPTYB + augB, l0);
    PROF_T(w, proft, 1);
  }
};

__device__ __forceinline__ uint32_t box_addr(uint32_t buf, uint32_t bo, int u) { return (buf + bo) ^ (u * 32); }

__device__ __forceinline__ float bf_round(float x) { return __bfloat162float(__float2bfloat16_rn(x)); }
__device__ __forceinline__ void own_rstd(int w, int wp, int lane, float (&rstd)[2]) {
#pragma unroll
  for (int hh = 0; hh < 2; hh++) rstd[hh] = __uint_as_float(lds32(SB + OFF_RSTD + (w * 72 + 8 + wp * 16 + (lane >> 2) + hh * 8) * 4));
}
__device__ __forceinline__ void stats_fetch(int w, int wp, int lane, uint32_t (&au)[2]) {
  const int g = lane >> 2, q4 = lane & 3;
  float rstd[2];
  own_rstd(w, wp, lane, rstd);
#pragma unroll
  for (int hh = 0; hh < 2; hh++) {
    const float m = __uint_as_float(lds32(SB + OFF_MEAN + (w * 64 + wp * 16 + g + hh * 8) * 4));
    const float v = q4 == 3 ? rcp(rstd[hh]) : -m;
    const float v1 = bf_round(v), v2 = bf_round(v - v1);
    const float p = q4 == 1 ? v2 : (q4 == 2 ? v - v1 - v2 : v1);
    au[hh] = pack_bf16(p, q4 == 3 ? v2 : p);
  }
}

__device__ __forceinline__ void halo_fetch(uint32_t slot, int w, const uint4* src, uint32_t bar) {
  asm volatile("{\n.reg .pred p;\nelect.sync _|p, 0xffffffff;\n@p mbarrier.arrive.expect_tx.shared::cta.b64 _, [%4], 2080;\n"
               "@p cp.async.bulk.shared::cluster.global.mbarrier::complete_tx::bytes [%0], [%2], 2048, [%4];\n"
               "@p cp.async.bulk.shared::cluster.global.mbarrier::complete_tx::bytes [%1], [%3], 32, [%4];\n}"
               ::"r"(slot), "r"(SB + OFF_RSTD + w * 288), "l"(src), "l"(src + 128), "r"(bar) : "memory");
}
struct Attn {
  uint32_t lo[24], hi[24], ha[16], hslot;
  float c[8][4], rstd[2];
  float2 rk[3];
  __device__ __forceinline__ void A(const float (&acc)[96], Pipe& M, int w, int wp, int r, uint4* halo_out) {
    const int lane = M.lane();
    M.signal_loader();
    auto cvt = [&](uint32_t& d, int u) { asm volatile("cvt.rn.bf16x2.f32 %0, %1, %2;" : "=r"(d) : "f"(acc[u + 1]), "f"(acc[u])); };
    auto rest = [&] {
#pragma unroll
      for (int nb = 23; nb >= 0; nb--) {
        cvt(lo[nb], 4 * nb);
        if (nb < 8) cvt(hi[nb], 4 * nb + 2);
        if (nb >= 16) lo[nb] = movm(lo[nb]);
      }
    };
#pragma unroll
    for (int nb = 8; nb < 24; nb++) hi[nb] = pack_bf16(acc[4 * nb + 2], acc[4 * nb + 3]);
    hslot = M.ahead(3);
    const uint32_t hbuf = hslot + wp * 2048 + lane * 16;
#pragma unroll
    for (int nb = 16; nb < 24; nb++) hi[nb] = movm(hi[nb]);
    if (TAR) rest();
    if (wp == 3) {
      if (r < 15) {
#pragma unroll
        for (int p = 0; p < 4; p++) halo_out[p * 32 + lane] = make_uint4(hi[8 + 4 * p] ? hi[8 + 4 * p] : 0x8000u, hi[9 + 4 * p], hi[10 + 4 * p], hi[11 + 4 * p]);
        if (!RSV) {
          const uint32_t rh = lds32(SB + OFF_RSTD + (w * 72 + 64 + (lane & 7)) * 4);
          if (lane < 8) reinterpret_cast<uint32_t*>(halo_out + 128)[lane] = rh ? rh : 0x80000000u;
        }
      }
    } else {
#pragma unroll
      for (int p = 0; p < 4; p++)
        asm volatile("st.shared.v4.b32 [%0], {%1,%2,%3,%4};" ::"r"(hbuf + 2048 + p * 512), "r"(hi[8 + 4 * p]), "r"(hi[9 + 4 * p]), "r"(hi[10 + 4 * p]), "r"(hi[11 + 4 * p]) : "memory");
      __syncwarp();
      arrive_n(SB + BAR_HALO + w * 8, M.l0);
    }
    if (!TAR) rest();
  }
  __device__ __forceinline__ void B(int w, int wp, int lane, uint32_t hph) {
    own_rstd(w, wp, lane, rstd);
    mbar_spin(SB + BAR_HALO + w * 8, hph);
#pragma unroll
    for (int p = 0; p < 4; p++)
      asm volatile("ld.shared.v4.b32 {%0,%1,%2,%3}, [%4];" : "=r"(ha[4 * p]), "=r"(ha[4 * p + 1]), "=r"(ha[4 * p + 2]), "=r"(ha[4 * p + 3]) : "r"(hslot + wp * 2048 + lane * 16 + p * 512) : "memory");
#pragma unroll
    for (int u = 0; u < 3; u++) rk[u] = lds64(SB + OFF_RSTD + (w * 72 + wp * 16 + u * 8 + 2 * (lane & 3)) * 4);
  }
  template <class F> __device__ __forceinline__ void C(int wp, int r, int lane, uint32_t zero, F last) {
    const int g = lane >> 2, q = lane & 3;
    const bool nohalo = (wp == 0) && (r == 0);
    const bool up0 = 2 * q > g, up1 = 2 * q + 1 > g;
    const float sc = 0.17677669529663687f * 1.4426950408889634f;
    const float kx0 = up0 ? rk[0].x : rk[1].x, kx1 = up1 ? rk[0].y : rk[1].y;
    const float ky0 = up0 ? rk[1].x : rk[2].x, ky1 = up1 ? rk[1].y : rk[2].y;
    const float fx = rstd[0] * sc, fy = rstd[1] * sc;
    float sm[2][4] = {}, s0[2][4] = {}, s1[2][4] = {};
#pragma unroll
    for (int ks = 0; ks < 2; ks++)
#pragma unroll
      for (int h = 0; h < 2; h++) {
        const int a = 4 * h + 2 * ks;
        mma16(s0[h], lo[a], hi[a], lo[a + 1], hi[a + 1], lo[8 + a], lo[9 + a]);
        mma16(s1[h], lo[a], hi[a], lo[a + 1], hi[a + 1], hi[8 + a], hi[9 + a]);
      }
#pragma unroll
    for (int u = 0; u < 4; u++) { const int a = 4 * (u & 1) + (u & 2); mma16(sm[u & 1], lo[a], hi[a], lo[a + 1], hi[a + 1], ha[a], ha[a + 1]); }
    uint32_t pf[2][4];
    const uint32_t um = (up0 ? 0xffffu : 0u) | (up1 ? 0xffff0000u : 0u);
#pragma unroll
    for (int h = 0; h < 2; h++) {
      if (nohalo) { sm[h][0] = -INFINITY; sm[h][1] = -INFINITY; }
      float x0 = (up0 ? sm[h][0] : s0[h][0]) * (kx0 * fx), x1 = (up1 ? sm[h][1] : s0[h][1]) * (kx1 * fx);
      float y0 = (up0 ? s0[h][2] : s1[h][2]) * (ky0 * fy), y1 = (up1 ? s0[h][3] : s1[h][3]) * (ky1 * fy);
      float mx = fmaxf(x0, x1), my = fmaxf(y0, y1);
      mx = fmaxf(mx, __shfl_xor_sync(~0u, mx, 1)); my = fmaxf(my, __shfl_xor_sync(~0u, my, 1));
      mx = fmaxf(mx, __shfl_xor_sync(~0u, mx, 2)); my = fmaxf(my, __shfl_xor_sync(~0u, my, 2));
      x0 = ex2(x0 - mx); x1 = ex2(x1 - mx); y0 = ex2(y0 - my); y1 = ex2(y1 - my);
      float sx = x0 + x1, sy = y0 + y1;
      x0 *= kx0; x1 *= kx1; y0 *= ky0; y1 *= ky1;
      sx += __shfl_xor_sync(~0u, sx, 1); sy += __shfl_xor_sync(~0u, sy, 1);
      sx += __shfl_xor_sync(~0u, sx, 2); sy += __shfl_xor_sync(~0u, sy, 2);
      sx = rcp(sx); sy = rcp(sy);
      x0 *= sx; x1 *= sx; y0 *= sy; y1 *= sy;
      const uint32_t px = pack_bf16(x0, x1), py = pack_bf16(y0, y1);
      pf[h][0] = px & um; pf[h][1] = px & ~um; pf[h][2] = py & um; pf[h][3] = py & ~um;
    }
#pragma unroll
    for (int u = 0; u < 4; u++) {
#pragma unroll
      for (int e = 0; e < 4; e++) { c[2 * u][e] = 0.f; c[2 * u + 1][e] = 0.f; }
      mma8(c[2 * u], ha[8 + 2 * u], ha[9 + 2 * u], pf[u >> 1][0]);
      mma8(c[2 * u + 1], lo[16 + 2 * u], lo[17 + 2 * u], pf[u >> 1][2]);
    }
#pragma unroll
    for (int u = 0; u < 4; u++) {
      mma8(c[2 * u], lo[16 + 2 * u], lo[17 + 2 * u], pf[u >> 1][1]);
      mma8(c[2 * u + 1], hi[16 + 2 * u], hi[17 + 2 * u], pf[u >> 1][3]);
    }
    uint32_t dep = 0;
    last();
#pragma unroll
    for (int u = 0; u < (EFIRST == 3 ? 0 : 8); u++) dep |= __float_as_uint(c[u][0]);
    asm volatile("bar.sync %0, 256;" ::"r"(3 + (dep & zero)) : "memory");
  }
  __device__ __forceinline__ void E(Pipe& M, bool urgent) {
#pragma unroll
    for (int u = 0; u < 4; u++)
      asm volatile("stmatrix.sync.aligned.m8n8.x4.trans.shared.b16 [%0], {%1, %2, %3, %4};" ::"r"(box_addr(hslot, M.bo, u)),
                   "r"(pack_bf16(c[2 * u][0], c[2 * u][1])), "r"(pack_bf16(c[2 * u + 1][0], c[2 * u + 1][1])),
                   "r"(pack_bf16(c[2 * u][2], c[2 * u][3])), "r"(pack_bf16(c[2 * u + 1][2], c[2 * u + 1][3])) : "memory");
    __syncwarp();
    arrive_n(SB + (urgent ? BAR_STG + M.w * 8 : BAR_SRV + M.w * 16 + 8), M.l0);
  }
};

__device__ __forceinline__ void epi_res(const float (&acc)[64], const float (&pre)[64], float sc0, float sc1, uint32_t (&xr)[32], Pipe& M, int wp) {
  Pipe T = M;
  const uint32_t buf0 = T.take(), buf1 = T.take();
#pragma unroll
  for (int u = 0; u < 8; u++) {
#pragma unroll
    for (int nb = 2 * u; nb < 2 * u + 2; nb++) {
      xr[2 * nb] = pack_bf16(fmaf(acc[4 * nb], sc0, pre[2 * nb]), fmaf(acc[4 * nb + 1], sc0, pre[32 + 2 * nb]));
      xr[2 * nb + 1] = pack_bf16(fmaf(acc[4 * nb + 2], sc1, pre[2 * nb + 1]), fmaf(acc[4 * nb + 3], sc1, pre[33 + 2 * nb]));
    }
    stsm4(box_addr(u < 4 ? buf0 : buf1, M.bo, u & 3), xr[4 * u], xr[4 * u + 1], xr[4 * u + 2], xr[4 * u + 3]);
    if (u == 3) M.signal_loader();
  }
  __syncwarp();
  arrive_n(SB + BAR_STG2 + M.w * 8, M.l0);
  fence_async_smem();
  if (!NWB) wg_bar(M.w);
}
__device__ __forceinline__ void presum(float (&pre)[64], int lane, float usebias) {
  const uint32_t bias = SB + OFF_VEC + (lane & 3) * 8;
#pragma unroll
  for (int nb = 0; nb < 16; nb++) {
    const float2 b = lds64(bias + nb * 32);
#pragma unroll
    for (int u = 2 * nb; u < 2 * nb + 2; u++) {
      const uint32_t v = __float_as_uint(pre[u]);
      pre[32 + u] = fmaf(b.y, usebias, bf_hi(v)); pre[u] = fmaf(b.x, usebias, bf_lo(v));
    }
  }
}
template <int S, int Q> __device__ __forceinline__ void pack_relu(uint32_t (&o)[Q], const float (&acc)[S]) {
#pragma unroll
  for (int u = 0; u < Q; u++) asm("cvt.rn.relu.bf16x2.f32 %0, %1, %2;" : "=r"(o[u]) : "f"(acc[2 * u + 1]), "f"(acc[2 * u]));
}
__device__ __forceinline__ uint32_t sq_bf16x2(uint32_t a) { uint32_t d; asm("mul.rn.bf16x2 %0, %1, %1;" : "=r"(d) : "r"(a)); return d; }
template <int Q> __device__ __forceinline__ void ffn_stage(const uint32_t (&o)[Q], int i, Pipe& M) {
  i -= M.w;
  if (i == 1 || i == 4 || i == 7 || (Q == 64 && i == 10)) {
    const uint32_t buf = M.wait_ahead(2 - M.w);
#pragma unroll
    for (int b = 0; b < Q / 16; b++)
      if (i == 3 * b + 1) {
#pragma unroll
        for (int u = 4 * b; u < 4 * b + 4; u++)
          stsm4(box_addr(buf, M.bo, u & 3), sq_bf16x2(o[4 * u]), sq_bf16x2(o[4 * u + 1]), sq_bf16x2(o[4 * u + 2]), sq_bf16x2(o[4 * u + 3]));
      }
    M.signal_server((i & 1) ^ (Q == 64));
  }
}

__device__ __forceinline__ void wait_flags(const uint8_t* f, uint32_t tag, int lane) {
  const uint32_t t4 = (tag & 0xff) * 0x01010101u;
  const uint32_t* fp = reinterpret_cast<const uint32_t*>(f) + (lane & (FG / 4 - 1));
  while (__any_sync(~0u, __vsub4(ld_relaxed(fp), t4) & 0x80808080u)) {}
  asm volatile("fence.acquire.gpu;\nfence.proxy.async.global;" ::: "memory");
}
__device__ __forceinline__ uint32_t get_epoch() { mbar_spin(SB + BAR_EPOCH, 0); return __shfl_sync(~0u, lds32(SB + OFF_HOLD + 8), 0); }
__device__ __forceinline__ void aloader(const Params& P, const Ptrs& Q, int bid, int r, int j, int lane, int w, uint32_t e, uint32_t epoch) {
  const uint32_t abase = SB + OFF_A + w * NA * 8192, fbase = SB + BAR_FULLA + w * NA * 8, ebase = SB + BAR_EMPTYA + w * NA * 8;
  uint32_t slot = NPRO, ph = 1, nst = 0, hph = 0, npace = 0;
  int t = -1, kind = -1, a0 = 0, a1 = 0;
  const CUtensorMap* tmA = nullptr;
  uint64_t pol = 0;
  uint4* hin = Q.s->halo[0][0] + (r * 16 + j * 2 + w - 16) * 136;
  uint32_t* const pace = Q.s->pace[0] + (bid & -PG) * 4;
  const uint8_t* const flags = Q.s->flags[r / (FG / 8)][w];
  auto adv = [&] { if (++slot == NA) { slot = 0; ph ^= 1; } };
#pragma unroll 1
  for (int g = NPRO; g <= NSTEP; g++) {
    const uint32_t cur = e;
    e = c_sched.v[j][g + 1];
    if (!(cur & E_RARE)) {
      if (cur & E_HAND) { mbar_spin(ebase + slot * 8, ph); e_arrive(fbase + slot * 8, 1); adv(); }
    } else {
      if (cur & F_NEW) {
        t++; kind = kind == 5 ? 0 : kind + 1;
        const bool narrow = kind == 2 || kind == 5;
        static_assert(TM_XIN == 0 && TM_X == 1 && TM_XA == 2 && TM_O == 3 && TM_H == 4, "map order");
        tmA = &P.tm[t < 2 ? 0 : (0x422311 >> (4 * kind)) & 15];
        pol = ((AEF >> t) & 1) ? 0x12F0000000000000ull : 0x1000000000000000ull;
        a0 = narrow ? 0 : w * 1024; a1 = narrow ? r * 128 + w * 64 : r * 64;
      }
      const bool xo = cur & E_XPUB0;
      uint32_t s = slot;
      if (cur & (E_HAND | E_ATTN | E_XPUB0)) {
        if (cur & E_KEEP) e_arrive(ebase + slot * 8, 4);
#pragma unroll 1
        for (int u = xo ? 0 : 1; u < 2; u++) { mbar_wait(ebase + slot * 8, ph); e_arrive(fbase + slot * 8, 1); adv(); }
      }
      uint32_t hold = 0;
      int lag = 0;
      if ((xo && t < 12) || (cur & F_GATH)) {
        uint32_t v;
        uint32_t v1;
        do asm volatile("ld.relaxed.gpu.global.v2.u32 {%0, %1}, [%2];" : "=r"(v), "=r"(v1) : "l"(pace + npace + (lane & (PG - 1)) * 2) : "memory");
        while (__any_sync(~0u, ((v ^ (epoch * 16 + t - 1)) | (v ^ v1)) & 31));
        v += v1;
        npace ^= PG * 2;
        lag = min((int)(v - __shfl_sync(~0u, v, bid & (PG - 1))), 8000) * 27 >> 5;
        hold = __reduce_max_sync(~0u, lag);
        asm volatile("st.shared.b32 [%0], %1;" ::"r"(SB + OFF_HOLD + w * 4), "r"(hold) : "memory");
      }
      if (cur & (E_ATTN | E_XPUB0)) {
        const uint32_t s2 = s == NA - 1 ? 0 : s + 1;
        mbar_wait(SB + BAR_STG + w * 8, nst & 1);
        nst++;
        LT(0);
        const uint32_t c1 = clock32();
        e_store(tmA, a0 + sched_k(cur), a1, abase + s * 8192);
        if (xo) {
          if (!LATE2 || t == 12) {
            mbar_spin(SB + BAR_STG2 + w * 8, ~t & 1);
            e_store(tmA, a0 + sched_k(cur) + 64, a1, abase + s2 * 8192);
          }
          if (t == 12) break;
          if (NPD) {
#pragma unroll 1
            for (int u = 0; u < NPD; u++) {
              const int c = u + (u >= j);
              spin_until(c1 + SDP + __shfl_sync(~0u, lag, Q44 ? c * 4 + (bid & 3) : c * 2 + (bid & 1)));
              e_load(abase + slot * 8192, tmA, a0 + c * 128, a1, fbase + slot * 8, pol);
              adv();
            }
            g += NPD + 1;
            e = c_sched.v[j][g + 1];
          }
          if (LATE2) {
            mbar_spin(SB + BAR_STG2 + w * 8, ~t & 1);
            e_store(tmA, a0 + sched_k(cur) + 64, a1, abase + s2 * 8192);
          }
        } else e_arrive(SB + BAR_OWN + w * 8, 1);
        LT(1);
        spin_until(c1 + hold + (xo ? SDELAY : SDELAYO));
        LT(2);
        LT(5);
      }
      if (cur & E_SIG) {
        e_arrive(SB + BAR_SRV + w * 16, 4);
      }
      if (cur & E_REL) bulk_wait_all();
      if (cur & E_HALO) {
        mbar_spin(SB + BAR_STG + w * 8, nst & 1);
        nst++;
        const uint32_t hs = abase + (slot >= 3 ? slot - 3 : slot + 3) * 8192, ad = hs + lane * 32 + (lane & 4) * 4;
        if (r == 0) {
#pragma unroll
          for (int p = 0; p < 4; p++) sts128(hs + lane * 16 + p * 512, 0, 0, 0, 0);
          asm volatile("st.shared.b32 [%0], %1;" ::"r"(SB + OFF_RSTD + w * 288 + (lane & 7) * 4), "r"(0x3f800000) : "memory");
        } else {
          spin_until(clock32() + HDELAY);
          do {
            halo_fetch(hs, w, hin, SB + BAR_SPEC + 80 + w * 8);
            mbar_spin(SB + BAR_SPEC + 80 + w * 8, hph);
            hph ^= 1;
          } while (__any_sync(~0u, min(min(lds32(ad), lds32(ad + 1024)), lds32(SB + OFF_RSTD + w * 288)) == 0));
        }
        e_arrive(SB + BAR_HALO + w * 8, 1);
      }
      if ((cur & E_REL) && (kind == 1 || kind == 2) && r > 0) {
        uint4* hz = hin + lane;
        hin += 256 * 136;
#pragma unroll
        for (int p = 0; p < 4; p++) hz[p * 32] = make_uint4(0, 0, 0, 0);
        if (lane < 2) hz[128] = make_uint4(0, 0, 0, 0);
      }
      if (cur & E_WAIT) {
        wait_flags(flags + ((cur & E_PART1) ? FG : 0), epoch * 16 + t, lane);
      }
    }
    if (!(cur & (F_AUG | F_NOA))) {
      mbar_wait(ebase + slot * 8, ph);
      e_load(abase + slot * 8192, tmA, a0 + sched_k(cur), a1, fbase + slot * 8, pol);
      adv();
      if ((cur & F_STAMP) && (ST2W || w == 0)) {
        if (!ST2W) mbar_spin(SB + BAR_EMPTYB + ((g - 6) & 7) * 8, ((g - 6) >> 3) & 1);
        uint32_t stamp;
        asm volatile("mov.u32 %0, %%globaltimer_lo;" : "=r"(stamp));
        asm volatile("st.relaxed.gpu.global.u32 [%0], %1;" ::"l"(pace + npace + (ST2W ? (bid & (PG - 1)) * 2 + w : bid & (PG - 1))), "r"((stamp & ~31u) | ((epoch * 16 + t) & 31)) : "memory");
      }
    }
  }
  bulk_wait_all();
}

__device__ __forceinline__ void bloader(const Params& P, const Ptrs& Q, bool aux, int j, int lane, uint32_t e, uint32_t epoch) {
  const uint32_t* const sched = c_sched.v[aux ? 8 : j];
  int kind = -1, c2 = 0, c3 = 0, na = 0;
  const CUtensorMap* tmB = nullptr;
  uint32_t sph = 0, efm = aux ? 0 : BEF * 2;
  uint64_t pol = 0;
#pragma unroll 1
  for (int g = aux ? 8 + (j & 1) : NPRO; g < (aux ? NSTEP_AUX : NSTEP); g += 1 + aux) {
    const uint32_t cur = e;
    e = sched[g + 1 + aux];
    if (cur & F_NEW) {
      kind = kind == 5 ? 0 : kind + ((cur >> 29) & 3);
      static_assert(TM_WQKV == 5 && TM_WO == 6 && TM_W1A == 7 && TM_W1B == 8 && TM_W2 == 9, "map order");
      tmB = &P.tm[(0x978655 >> (4 * kind)) & 15];
      efm >>= 1;
      pol = (efm & 1) ? 0x12F0000000000000ull : 0x1000000000000000ull;
      na = (0x243233 >> (4 * kind)) & 15;
      c2 = ((0x277200 >> (4 * kind)) & 15) * j + (kind == 4 ? 3 : 0);
      c3 = kind <= 1 ? kind * 8 + j : 0;
    }
    const int need = g - (int)((cur >> 5) & 15);
    const uint32_t dst = SB + OFF_B + (cur & 31) * 8192, bar = SB + BAR_FULLB + (g & 7) * 8;
    mbar_wait(SB + BAR_EMPTYB + (need & 7) * 8, (need >> 3) & 1);
    if (!(cur & F_AUG)) {
      asm volatile("{\n.reg .pred p;\nelect.sync _|p, 0xffffffff;\n@p mbarrier.arrive.expect_tx.shared::cta.b64 _, [%2], %7;\n"
                   "@p cp.async.bulk.tensor.4d.shared::cluster.global.mbarrier::complete_tx::bytes.L2::cache_hint [%0], [%1, {%3, %4, %5, %6}], [%2], %8;\n}"
                   ::"r"(dst), "l"(tmB), "r"(bar), "r"(0), "r"(sched_k(cur)), "r"(c2), "r"(c3), "r"(na * 8192), "l"(pol) : "memory");
    } else {
      const bool chk = g < NSTEP / 2;
      const uint32_t b2 = chk ? SB + BAR_AUG : bar, ad = dst + lane * 16 + (lane >> 3) * 4;
      while (true) {
        asm volatile("{\n.reg .pred p;\nelect.sync _|p, 0xffffffff;\n@p mbarrier.arrive.expect_tx.shared::cta.b64 _, [%2], 4096;\n"
                     "@p cp.async.bulk.shared::cluster.global.mbarrier::complete_tx::bytes [%0], [%1], 4096, [%2];\n}"
                     ::"r"(dst), "l"(Q.s->aug[epoch & 1][(kind - (kind >= 3)) * 8 + j]), "r"(b2) : "memory");
        if (!chk) break;
        mbar_spin(b2, sph);
        sph ^= 1;
        uint32_t mn = ~0u;
#pragma unroll
        for (int u = 0; u < 8; u++) mn = min(mn, lds32(ad + u * 512));
        if (!__any_sync(~0u, mn == 0)) { e_arrive(bar, 1); break; }
      }
      __syncwarp();
    }
  }
}

constexpr uint32_t job_slots(int layer) {
  const int pos[10] = {11, 26, 63, 73, 77, 81, 92, 96, 100, 104};
  uint32_t v = 0;
  for (int m = 0; m < 10; m++) v |= (uint32_t)((layer * 148 + pos[m]) % NA) << (3 * m);
  return v;
}
constexpr uint32_t JOB_SLOTS0 = job_slots(0), JOB_SLOTS1 = job_slots(1);
__device__ __forceinline__ void server(const Params& P, const Ptrs& Q, int bid, int r, int j, int lane, uint32_t epoch) {
  if (CPF) spin_until(clock32() + CPF);
  epoch += __shfl_sync(~0u, c_sched.v[j][lane < 18 ? lane * 16 : 0] >> 31, 0);
  {
    const uint2 b = reinterpret_cast<const uint2*>(Q.b2 + j * 128)[lane];
    sts128(SB + OFF_VEC + lane * 16, b.x << 16, b.x & 0xffff0000u, b.y << 16, b.y & 0xffff0000u);
  }
  int hl = 0;
  uint32_t fph = 0, pend = SB + BAR_DUMMY3;
#pragma unroll 1
  for (int n = 0; n < 20; n++) {
    const int layer = n >= 10, m = n - 10 * layer;
    const bool stat = m == 0 || m == 2;
    const uint32_t slot = ((layer ? JOB_SLOTS1 : JOB_SLOTS0) >> (m * 3)) & 7;
    auto fetch = [&](int w) {
      asm volatile("{\n.reg .pred p;\nelect.sync _|p, 0xffffffff;\n@p mbarrier.arrive.expect_tx.shared::cta.b64 _, [%2], 4096;\n"
                   "@p cp.async.bulk.shared::cluster.global.mbarrier::complete_tx::bytes [%0], [%1], 4096, [%2];\n}"
                   ::"r"(SB + OFF_A + (w * NA + slot) * 8192), "l"(&Q.s->stats[hl][r * 32 + w * 16][0][0]), "r"(SB + BAR_SPEC + 64 + w * 8) : "memory");
    };
#pragma unroll 1
    for (int w = 0; w < 2; w++) {
      mbar_spin(SB + BAR_SRV + w * 16 + (n & 1) * 8, (n >> 1) & 1);
      if (stat) fetch(w);
      else {
        e_store(&P.tm[m == 1 ? TM_O : TM_H], m == 1 ? j * 64 : 448 * j + (m - 3) * 64, r * 128 + w * 64, SB + OFF_A + (w * NA + slot) * 8192);
        bulk_wait_read<1>();
        e_arrive(pend, 4);
        pend = SB + BAR_EMPTYA + (w * NA + slot) * 8;
      }
    }
    if (stat) {
#pragma unroll 1
      for (int w = 0; w < 2; w++) {
        const uint32_t src = SB + OFF_A + (w * NA + slot) * 8192 + (lane >> 1) * 256 + ((lane >> 1) & 7) * 32 + (lane & 1) * 16;
        float ms[2], md[2], mq[2], m0[2];
        while (true) {
          mbar_spin(SB + BAR_SPEC + 64 + w * 8, (fph >> w) & 1);
          fph ^= 1u << w;
          uint32_t bad = 0;
          ms[0] = ms[1] = md[0] = md[1] = mq[0] = mq[1] = m0[0] = m0[1] = 0.f;
#pragma unroll 1
          for (int p = 0; p < 8; p += 2) {
            const float4 v2[2] = {lds128(src ^ (p * 32)), lds128(src ^ (p * 32) ^ 32)};
            if (p == 0) { m0[0] = v2[0].x; m0[1] = v2[0].z; }
#pragma unroll
            for (int z = 0; z < 2; z++) {
              const float4 v = v2[z];
              const float a = v.x - m0[0], b = v.z - m0[1];
              bad |= __float_as_uint(v.y) ^ epoch;
              ms[0] += a; md[0] = fmaf(a, a, md[0]); mq[0] += __uint_as_float(__float_as_uint(v.y) & ~63u);
              ms[1] += b; md[1] = fmaf(b, b, md[1]); mq[1] += v.w;
            }
          }
          if (!__any_sync(~0u, bad & 63)) break;
          fetch(w);
          __syncwarp();
        }
        e_arrive(SB + BAR_EMPTYA + (w * NA + slot) * 8, 4);
        const int row = (lane >> 3) * 16 + (lane & 7);
#pragma unroll
        for (int z = 0; z < 2; z++) {
          const float d = ms[z] * 0.125f;
          asm volatile("st.shared.f32 [%0], %1;" ::"r"(SB + OFF_MEAN + (w * 64 + row + z * 8) * 4), "f"(m0[z] + d) : "memory");
          const float rs = rsq(fmaf(mq[z], 1.f / 1024.f, fmaxf(fmaf(md[z], 0.125f, -d * d), 0.f)) + 1e-5f);
          asm volatile("st.shared.f32 [%0], %1;" ::"r"(SB + OFF_RSTD + (w * 72 + 8 + row + z * 8) * 4), "f"(rs) : "memory");
          if (RSV && z && !m && lane >= 24) {
            float* const h = reinterpret_cast<float*>(Q.s->halo[0][0] + 122) + (uint32_t)((hl * 256 + r * 16 + j * 2 + w) * 544 + lane);
            h[0] = h[256 * 544] = rs != 0.f ? rs : -0.f;
          }
        }
        e_arrive(SB + BAR_STAT + w * 8, 8);
      }
    }
    if (stat && n != 12) {
#pragma unroll 1
      for (int u = 0; u < (m ? 2 : 3); u++) {
        const uint32_t pitch = u == 2 ? 448 : 128;
        uint4* p = reinterpret_cast<uint4*>(u == 2 ? Q.s->h : (m ? Q.out : Q.s->x)) + (u == 2 ? 64 + j * 8 : j * 16 + u * 8) + ((r * 128 + (lane >> 3)) * pitch + (lane & 7));
#pragma unroll 1
        for (int k = 0; k < 32 / FUN; k++) {
#pragma unroll
          for (int z = 0; z < FUN; z++) {
            *p = make_uint4(~0u, ~0u, ~0u, ~0u);
            p += 4 * pitch;
            asm volatile("" : "+l"(p));
          }
        }
      }
      __syncwarp();
    }
    if ((0x222 >> m) & 1) {
      bulk_wait_all();
      e_arrive(pend, 4);
      pend = SB + BAR_DUMMY3;
      if (lane < 2) st_release8(&Q.s->flags[r / (FG / 8)][lane][(r & (FG / 8 - 1)) * 8 + j + (m == 9 ? FG : 0)], epoch * 16 + layer * 6 + (m == 1 ? 2 : 5));
      __syncwarp();
    }
    hl += stat;
  }
}

__device__ __forceinline__ void aux_math(const Ptrs& Q, int bid, int jj, int warp, int lane) {
  const int g = lane >> 2, q = lane & 3, c0 = (warp & 3) * 2;
  uint32_t st = warp >> 2, bf[16][4] = {};
  const uint32_t ad0 = SB + ((lane >> 4) * 8 + (lane & 7)) * 128 + (((c0 + ((lane >> 3) & 1)) ^ (lane & 7)) << 4);
#pragma unroll 1
  for (int t = 0; t < 4; t++) {
    float acc[4][4] = {};
    uint32_t bias[8];
#pragma unroll
    for (int a = 0; a < 8; a++) bias[a] = t >= 2 ? reinterpret_cast<const uint32_t*>(Q.b1 + 448 * jj + (t - 2) * 192 + c0 * 8)[(a >> 1) * 32 + (a & 1) * 4 + q] : 0u;
#pragma unroll 1
    for (int i = 0; i < 16; i++, st += 2) {
      const uint32_t ad = ad0 + (c_sched.v[8][st] & 31) * 8192;
      mbar_spin(SB + BAR_FULLB + (st & 7) * 8, (st >> 3) & 1);
#pragma unroll
      for (int u = 0; u < 16; u++)
        asm volatile("{\n.reg .pred p;\nsetp.ne.u32 p, %5, 0;\n@p ldmatrix.sync.aligned.m8n8.x4.trans.shared.b16 {%0,%1,%2,%3}, [%4];\n}"
                     : "+r"(bf[u][0]), "+r"(bf[u][1]), "+r"(bf[u][2]), "+r"(bf[u][3])
                     : "r"(ad + (u & 3) * 8192 + (u >> 2) * 2048), "r"((u & 3) != 3 || t == 3 ? 1 : 0) : "memory");
      __syncwarp();
      e_arrive(SB + BAR_EMPTYB + (st & 7) * 8, 2);
#pragma unroll
      for (int u = 0; u < 16; u++) mma16(acc[u & 3], bf[u][0], bf[u][1], bf[u][2], bf[u][3], 0x3F803F80u, 0x3F803F80u);
    }
    const uint32_t epoch = lds32(SB + OFF_HOLD + 8);
    const uint32_t o = (t * 8 + jj) * 1024 + g * 32 + ((c0 ^ g) << 2) + q + (epoch & 1) * 32768;
    uint32_t *const p0 = Q.s->aug[0][0] + o, *const p1 = Q.s->aug[0][0] + (o ^ 4);
#pragma unroll
    for (int a = 0; a < 8; a++) {
      const float u = acc[a >> 1][(a & 1) * 2];
      uint32_t h = movm(pack_bf16(u, u - bf_round(u)));
      if (g >= 6) h = bias[a];
      ((a & 1) ? p1 : p0)[(a >> 1) * 256] = h ? h : 0x8000u;
    }
    uint4* const z = reinterpret_cast<uint4*>(Q.s->aug[~epoch & 1][t * 8 + jj]) + (threadIdx.x & 127);
    z[0] = z[128] = make_uint4(0, 0, 0, 0);
  }
}

template <bool BYSM> __global__ void __launch_bounds__(NTHREADS, 1) mega_kernel(const __grid_constant__ Ptrs Q, const __grid_constant__ Params P) {
  extern __shared__ __align__(1024) uint8_t smem_raw[];
  constexpr uint32_t sb = SB;
  const uint32_t centry = clock32();
  const int warp = __shfl_sync(~0u, threadIdx.x >> 5, 0), lane = threadIdx.x & 31;
  const int bid = BYSM ? work_id() : blockIdx.x;
  const bool aux = bid >= NMAIN;
  const int r = Q44 ? ((bid >> 5) << 2) | (bid & 3) : ((bid >> 4) << 1) | (bid & 1), j = (aux ? bid * 2 : bid >> (1 + Q44)) & 7;
  PRO(0);
  {
    const uint32_t b = sb + OFF_BAR + warp * 48, cnt = warp < 6 ? 1 : (warp < 10 ? 4 : 8);
    asm volatile("{\n.reg .pred p;\nelect.sync _|p, 0xffffffff;\n@p mbarrier.init.shared::cta.b64 [%0], %1;\n@p mbarrier.init.shared::cta.b64 [%0 + 8], %1;\n"
                 "@p mbarrier.init.shared::cta.b64 [%0 + 16], %1;\n@p mbarrier.init.shared::cta.b64 [%0 + 24], %1;\n"
                 "@p mbarrier.init.shared::cta.b64 [%0 + 32], %1;\n@p mbarrier.init.shared::cta.b64 [%0 + 40], %1;\nfence.mbarrier_init.release.cluster;\n}"
                 ::"r"(b), "r"(cnt) : "memory");
  }
  __syncthreads();
  {
    static_assert(NPRO == 4 && ROUND0 == 0, "prologue stages");
    const int st = ((11 - warp) * (aux ? 32 : 11)) >> 5, op = aux ? (st < 8) * 2 : 11 - warp - 3 * st, sd = aux ? st >> STGX : (op == 2 ? st : st & 2);
    const uint32_t bar0 = sb + OFF_BAR + (op * 6 + st) * 8;
    const int kc = aux ? (st >> 1) * 64 : (st & 2 ? (ROUND1 >> (4 * j)) & 15 : 0) * 128 + (st & 1) * 64;
    spin_until(centry + (sd ? STG0 + sd * STG1 : 0));
    if (op == 2) {
      asm volatile("{\n.reg .pred p;\nelect.sync _|p, 0xffffffff;\n@p mbarrier.arrive.expect_tx.shared::cta.b64 _, [%2], 24576;\n"
                   "@p cp.async.bulk.tensor.4d.shared::cluster.global.mbarrier::complete_tx::bytes [%0], [%1, {%3, %4, %3, %5}], [%2];\n}"
                   ::"r"(sb + OFF_B + (aux ? (st & 1) * 114688 + (st >> 1) * 24576 : (st + 1) * 24576)), "l"(&P.tm[TM_WQKV]), "r"(bar0), "r"(0), "r"(kc), "r"(j + (st & aux)) : "memory");
    } else if (!aux) e_load(sb + OFF_A + (op * 6 + st) * 8192, &P.tm[TM_XIN], op * 1024 + kc, r * 64, bar0);
    PRO(1);
    asm volatile("prefetch.tensormap [%0];" ::"l"(&P.tm[warp]) : "memory");
  }
  if (warp >= 8) {
    asm volatile("setmaxnreg.dec.sync.aligned.u32 24;");
    if (warp == 11) {
      if (smem_u32(smem_raw) != SB) __trap();
      const uint32_t epoch = __shfl_sync(~0u, ld_relaxed(&Q.s->epoch[bid]) + 1, 0);
      Q.s->epoch[bid] = epoch;
      asm volatile("st.shared.b32 [%0], %1;" ::"r"(sb + OFF_HOLD + 8), "r"(epoch) : "memory");
      e_arrive(sb + BAR_EPOCH, 1);
      PRO(2);
      if (!aux) server(P, Q, bid, r, j, lane, epoch);
    } else {
      const uint32_t e = c_sched.v[aux ? 8 : j][aux ? warp : NPRO];
      spin_until(centry + STGL + (e >> 31));
      PRO(2);
      const uint32_t epoch = get_epoch();
      PRO(3);
      if (warp <= 8 + aux) bloader(P, Q, aux, j + warp - 8, lane, e, epoch);
      else if (!aux) aloader(P, Q, bid, r, j, lane, warp - 9, e, epoch);
    }
  } else if (aux) aux_math(Q, bid, j + (warp >> 2), warp, lane);
  else {
    asm volatile("setmaxnreg.inc.sync.aligned.u32 240;");
    const int w = warp >> 2, wp = warp & 3;
    {
      uint32_t xr[32];
#pragma unroll
      for (int u = 0; u < 32; u++) if (NOI) asm volatile("" : "=r"(xr[u])); else xr[u] = 0;
      Pipe M;
      M.db = 0; M.g8 = 0; M.a8 = w * NA * 8; M.pa = 0; M.tph = 0; M.aend = (w + 1) * NA * 8;
      M.h0 = gridDim.y * 0x40000040u; M.h1 = gridDim.z * 0x40000040u; M.one = gridDim.z;
      M.curB = M.curA = M.prevB = M.prevA = M.sph = 0; M.nx = make_uint2(0, 0); M.w = w; M.l0 = lane == 0;
      M.bo = (wp * 16 + (lane & 15)) * 128 + (((lane >> 4) ^ (lane & 7)) << 4);
      M.so = __shfl_sync(~0u, SB + OFF_A + wp * 2048 + lane * 32 + (lane >> 2) * 4, lane);
      M.bo = __shfl_sync(~0u, M.bo, lane);
      auto nop = [](int) {};
      const uint32_t zero = gridDim.y - 1;
      PROF_T(w, 0, 3);
      if (STARTC) spin_until(centry + STARTC);
#pragma unroll 1
      for (int hl = 0; hl < 4; hl++) {
        const int t0 = hl * 3;
        const bool ffn = hl & 1;
        float acc[96], acn[64];
        uint32_t au[2] = {0u, 0u};
        {
          const int d = hl ? 0 : ((OWNP * 2u) >> (4 * j)) & 15;
          auto own = [&](auto h, uint32_t dep = 0) {
#pragma unroll
            for (int u = 4 * h.v; u < 4 * h.v + 4; u++)
              asm volatile("ldmatrix.sync.aligned.m8n8.x4.shared.b16 {%0,%1,%2,%3}, [%4];" : "=r"(xr[4 * u]), "=r"(xr[4 * u + 1]), "=r"(xr[4 * u + 2]), "=r"(xr[4 * u + 3])
                           : "r"(box_addr(sb + OFF_A + M.a8 * 1024, M.bo + dep, u & 3)) : "memory");
          };
          M.begin<192>(acc, ffn ? 12 : 3, t0, [&](int) { if (hl + d == 0) own(IC<0>{}); });
          if (hl + d == 0) own(IC<1>{}, (xr[0] | xr[4] | xr[8] | xr[12]) & zero);
          float ss[2] = {0.f, 0.f}, sq[2] = {0.f, 0.f};
          auto part = [&](auto c0, auto n) {
#pragma unroll
            for (int v = 0; v < 4 * n.v; v++) {
              const int u = c0.v + v / n.v * 4 + v % n.v;
              float a, b;
              asm volatile("shl.b32 %0, %2, 16;\nand.b32 %1, %2, 0xffff0000;" : "=f"(a), "=f"(b) : "r"(xr[u]));
              ss[u & 1] += a + b; sq[u & 1] = fmaf(a, a, fmaf(b, b, sq[u & 1]));
            }
          };
          const uint64_t plan = hl ? PLAN1 : (d ? PLAN0 : PLANZ);
          auto todo = [&](int i) { uint64_t v; asm volatile("shr.u64 %0, %1, %2;" : "=l"(v) : "l"(plan), "r"((i + 1 - d) * 8)); return (uint32_t)v; };
          uint32_t m = todo(1);
          M.run<192, false>(acc, 1, 16, 1u << 10, 16 - (ffn ? LEAD3 : LEAD0), [&](int i, uint2 ok) {
           CT(0);
           if (m & 7) {
             if (m & 1) part(IC<0>{}, IC<2>{});
             if (m & 2) part(IC<2>{}, IC<2>{});
             if (m & 4) part(IC<16>{}, IC<1>{});
           }
           CT(1);
           M.ensure(ok);
           CT(3);
           M.validate(hl != 0, &P.tm[ffn ? TM_XA16 : TM_X16], w * 1024, r * 64, wp, j, [&] {
            if (m & 0xf8) {
              if (m & 128) { if (m & 1) own(IC<1>{}); else own(IC<0>{}); }
              if (m & 8) part(IC<17>{}, IC<1>{});
              if (m & 16) part(IC<18>{}, IC<1>{});
              if (m & 32) part(IC<19>{}, IC<1>{});
              if (m & 64) {
                const uint32_t epoch = lds32(sb + OFF_HOLD + 8);
#pragma unroll
                for (int o = 1; o < 4; o *= 2)
#pragma unroll
                  for (int z = 0; z < 2; z++) { ss[z] += __shfl_xor_sync(~0u, ss[z], o); sq[z] += __shfl_xor_sync(~0u, sq[z], o); }
                const float m0 = ss[0] * (1.f / 128.f), m1 = ss[1] * (1.f / 128.f);
                const int rowpair = r * 64 + w * 32 + wp * 8 + (M.lane() >> 2);
                if ((M.lane() & 3) == 0)
                  st_pkt(&Q.s->stats[hl][rowpair >> 1][j][rowpair & 1], __float_as_uint(m0), (__float_as_uint(fmaxf(fmaf(-ss[0], m0, sq[0]), 0.f)) & ~63u) | (epoch & 63),
                         __float_as_uint(m1), __float_as_uint(fmaxf(fmaf(-ss[1], m1, sq[1]), 0.f)));
              }
            }
            m = todo(i + 1);
            if (i == STATI) { mbar_spin(sb + BAR_STAT + w * 8, hl & 1); stats_fetch(w, wp, M.lane(), au); }
           });
           CT(4);
          });
          M.end<192, true>(acc, ffn ? 0 : 4, 15, au[0], au[1], t0);
          PROF_T(w, t0, 2);
        }
        if (!ffn) {
          Attn T;
#pragma unroll 1
          for (int wave = 0; wave < 2; wave++) {
            AP(9);
            uint4* const hp = Q.s->halo[0][0] + (uint32_t)(((hl + wave) * 256 + r * 16 + j * 2 + w) * 136);
            T.A(acc, M, w, wp, r, hp);
            AP(0);
            if (wave == 0) {
              M.begin<192, PACE2 & 1>(acc, 6, t0 + 1);
              M.run<192>(acc, 1, NH1, 4, -1, nop);
              T.B(w, wp, M.lane(), 0);
              M.drain();
            } else {
              M.begin<128, (PACE2 >> 1) & 1>(acn, 12, t0 + 2);
              M.run<128>(acn, 1, NH2, 4, -1, nop);
              T.B(w, wp, M.lane(), 1);
              M.drain();
#pragma unroll
              for (int z = 0; z < 64; z++) asm volatile("mov.b32 %0, %1;" : "=f"(acc[z]) : "f"(acn[z]));
#pragma unroll
              for (int z = 64; z < 96; z++) acc[z] = 0.f;
            }
            AP(2);
            T.C(wp, r, M.lane(), zero, [&] { if (EFIRST == 3 || (EFIRST == 2 && wave)) T.E(M, wave); });
            AP(3);
            if (wave == 1) break;
            M.run<192>(acc, NH1, 16, 1u << 7, 16 - LEAD1, [&](int i) { if (EFIRST < 3 && i == NH1) T.E(M, false); });
            M.end<192, true>(acc, 4, 10, au[0], au[1], t0 + 1);
            PROF_T(w, t0 + 1, 2);
          }
#pragma unroll
          for (int z = 0; z < 64; z++) asm volatile("mov.b32 %0, %1;" : "=f"(acn[z]) : "f"(acc[z]));
          if (EFIRST == 1) T.E(M, true);
          else if (!EFIRST) {
            M.ensure(M.iss<128, false>(acn, false));
            T.E(M, true);
          }
        } else {
          uint32_t pk[48], pk2[64];
          pack_relu(pk, acc);
          {
            float acc2[128];
            M.begin<256, (PACE2 >> 3) & 1>(acc2, 0, t0 + 1);
            M.run<256>(acc2, 1, 16, 0x248, 16 - LEAD4, [&](int i) { ffn_stage(pk, i, M); });
            M.end<256, true>(acc2, 0, 0, au[0], au[1], t0 + 1);
            pack_relu(pk2, acc2);
            PROF_T(w, t0 + 1, 2);
          }
          M.begin<128, (PACE2 >> 4) & 1>(acn, 2, t0 + 2);
          M.run<128>(acn, 1, 13, 0x1248, -1, [&](int i) { ffn_stage(pk2, i, M); });
        }
        {
          float pre[64], rstd[2] = {0.f, 0.f};
#pragma unroll
          for (int u = 0; u < 32; u++) { pre[u] = __uint_as_float(xr[u]); if (!NOI) pre[32 + u] = 0.f; }
          if (NOI) {
#pragma unroll
            for (int u = 32; u < 64; u += 4) { const float4 v = lds128(sb + OFF_VEC); pre[u] = v.x; pre[u + 1] = v.y; pre[u + 2] = v.z; pre[u + 3] = v.w; }
          }
          const int ks = ffn ? 56 : 16, pause = ks - (ffn ? LEAD5 : LEAD2), vfrom = ffn ? 99 : 7;
          M.run<128>(acn, ffn ? 13 : NH2 + !EFIRST, ks, 0, pause, [&](int i) {
            if (i >= vfrom) {
              if (i == 7) mbar_spin(sb + BAR_OWN + w * 8, hl >> 1);
              M.validate(true, &P.tm[TM_O16], 0, r * 128 + w * 64, wp, j, [] {});
            }
          }, w ? (ffn ? (PRE5 ? PRE5 : pause) : (PRE2 ? PRE2 : pause)) : (ffn ? 20 : IPRE), [&](int) { presum(pre, M.lane(), ffn ? 1.f : 0.f); own_rstd(w, wp, M.lane(), rstd); });
          M.end<128, false>(acn, 2, 0, 0, 0, t0 + 2);
          epi_res(acn, pre, ffn ? rstd[0] * rstd[0] : 1.f, ffn ? rstd[1] * rstd[1] : 1.f, xr, M, wp);
          PROF_T(w, t0 + 2, 2);
        }
      }
    }
  }
}

typedef CUresult (*EncFn)(CUtensorMap*, CUtensorMapDataType, cuuint32_t, void*, const cuuint64_t*, const cuuint64_t*, const cuuint32_t*,
                          const cuuint32_t*, CUtensorMapInterleave, CUtensorMapSwizzle, CUtensorMapL2promotion, CUtensorMapFloatOOBfill);

void enc2(EncFn enc, CUtensorMap* tm, const void* p, uint64_t cols, uint64_t rows, uint32_t boxrows = 64, CUtensorMapL2promotion promo = CU_TENSOR_MAP_L2_PROMOTION_L2_128B) {
  cuuint64_t gd[2] = {cols, rows}, gs[1] = {cols * 2};
  cuuint32_t box[2] = {64, boxrows}, es[2] = {1, 1};
  enc(tm, CU_TENSOR_MAP_DATA_TYPE_BFLOAT16, 2, const_cast<void*>(p), gd, gs, box, es, CU_TENSOR_MAP_INTERLEAVE_NONE, CU_TENSOR_MAP_SWIZZLE_128B,
      promo, CU_TENSOR_MAP_FLOAT_OOB_FILL_NONE);
}
void enc4(EncFn enc, CUtensorMap* tm, const void* p, uint64_t K, uint64_t N, uint64_t d2, uint64_t s2, uint64_t d3, uint64_t s3, uint32_t na) {
  cuuint64_t gd[4] = {64, K, d2, d3}, gs[3] = {N * 2, s2, s3};
  cuuint32_t box[4] = {64, 64, na, 1}, es[4] = {1, 1, 1, 1};
  enc(tm, CU_TENSOR_MAP_DATA_TYPE_BFLOAT16, 4, const_cast<void*>(p), gd, gs, box, es, CU_TENSOR_MAP_INTERLEAVE_NONE, CU_TENSOR_MAP_SWIZZLE_128B,
      WPROMO, CU_TENSOR_MAP_FLOAT_OOB_FILL_NONE);
}

}

extern "C" void kernel_launch(void* const* d_in, const int* in_sizes, int n_in, void* d_out, int out_size) {
  static EncFn enc = nullptr;
  static Scratch* ps = nullptr;
  static void (*kernel)(Ptrs, Params) = mega_kernel<true>;
  if (!enc) {
    cudaDriverEntryPointQueryResult qr;
    cudaGetDriverEntryPoint("cuTensorMapEncodeTiled", (void**)&enc, cudaEnableDefault, &qr);
    int dev = 0, nsm = 0;
    cudaGetDevice(&dev);
    cudaDeviceGetAttribute(&nsm, cudaDevAttrMultiProcessorCount, dev);
    if (nsm != NMAIN + NAUX) kernel = mega_kernel<false>;
    cudaFuncSetAttribute(kernel, cudaFuncAttributeMaxDynamicSharedMemorySize, SMEM_BYTES);
    cudaGetSymbolAddress((void**)&ps, g_s);
  }
  Params P;
  Ptrs Q;
  Q.s = ps;
  void *p_h = ps->h, *p_x = ps->x;
  enc2(enc, &P.tm[TM_XIN], d_in[0], 2048, 1024, 64, XPROMO);
  enc2(enc, &P.tm[TM_X], d_out, 2048, 1024);
  enc2(enc, &P.tm[TM_XA], p_x, 2048, 1024);
  enc2(enc, &P.tm[TM_O], p_h, 3584, 2048);
  enc2(enc, &P.tm[TM_H], p_h, 3584, 2048);
  enc2(enc, &P.tm[TM_X16], d_out, 2048, 1024, 16);
  enc2(enc, &P.tm[TM_XA16], p_x, 2048, 1024, 16);
  enc2(enc, &P.tm[TM_O16], p_h, 3584, 2048, 16);
  enc4(enc, &P.tm[TM_WQKV], d_in[1], 1024, 3072, 3, 2048, 16, 128, 3);
  enc4(enc, &P.tm[TM_WO], d_in[2], 1024, 1024, 16, 128, 1, 128, 2);
  enc4(enc, &P.tm[TM_W1A], d_in[4], 1024, 3584, 56, 128, 1, 128, 4);
  enc4(enc, &P.tm[TM_W1B], d_in[4], 1024, 3584, 56, 128, 1, 128, 3);
  enc4(enc, &P.tm[TM_W2], d_in[6], 3584, 1024, 16, 128, 1, 128, 2);
  Q.out = (__nv_bfloat16*)d_out;
  Q.b1 = (const __nv_bfloat16*)d_in[5];
  Q.b2 = (const __nv_bfloat16*)d_in[7];
  kernel<<<NMAIN + NAUX, NTHREADS, SMEM_BYTES, cudaStreamPerThread>>>(Q, P);
}
```

```cpp
#include <cuda_runtime.h>
#include <cuda_bf16.h>
#include <cuda.h>
#include <stdint.h>

#define LEAD0 2
#define LEAD1 1
#define LEAD2 4
#define LEAD3 2
#define LEAD4 1
#define LEAD5 5
#define WPROMO CU_TENSOR_MAP_L2_PROMOTION_L2_128B
#define PLAN1 0x7f0000ull
#define PLAN2 0x400000003f0000ull
#define P0S 0x640096
#define PAS 0x430ff
#define PLAN0 0x4030020c8180ull
#define PLANZ 0x40300a050000ull
#define LSO 1
#define STATI 13
#define PACE2 0x1a
#define ST2 12
#define STB 3
#define PROBE 4
#define OWNP 0x22221110
#define SIG0 14
#define STGX 2
#define STGM 3
#define NPRO 4
#define XPROMO CU_TENSOR_MAP_L2_PROMOTION_L2_256B
#define IPRE 7
#define FILLT 1
#define EARLYC 1
#define OWNDLY 0
#define EPW 0
#define CPF 5000
#define STG0 800
#define STG1 500
#define STGL (STG0 + 4 * STG1)
#define STGLX 0
#define STARTC 0
#define FUN 4
#define XEF 0
#define BEF 0xff8
#define AEF 0xdb6
#define SEF 0
#define SDELAYO 1000
#define SDELAY 300
#define HDELAY 450
#define Q44 1
#define FG 8
#define NOI 1
#define EFIRST 1
#define STA 1
#define PG (Q44 ? 32 : 16)
#define NH1 6
#define NH2 3
namespace {

constexpr int NMAIN = 128, NAUX = 4, NTHREADS = 384;
constexpr uint32_t OFF_B = 0;
constexpr uint32_t OFF_A = 131072;
constexpr uint32_t OFF_VEC = 229376;
constexpr uint32_t OFF_BAR = 231424;
constexpr uint32_t OFF_RSTD = OFF_VEC + 512, OFF_MEAN = OFF_VEC + 1088, OFF_HOLD = OFF_VEC + 2032;
constexpr uint32_t SMEM_BYTES = OFF_BAR + 960;
constexpr uint32_t BAR_FULLA = OFF_BAR, BAR_FULLB = OFF_BAR + 96, BAR_OWN = OFF_BAR + 160, BAR_EPOCH = OFF_BAR + 176, BAR_AUG = OFF_BAR + 184, BAR_SPEC = OFF_BAR + 192,
                   BAR_EMPTYA = OFF_BAR + 288, BAR_STG = OFF_BAR + 384, BAR_SRV = OFF_BAR + 400, BAR_LEAD = OFF_BAR + 432, BAR_HALO = OFF_BAR + 440, BAR_STG2 = OFF_BAR + 456,
                   BAR_DUMMY3 = OFF_BAR + 472, BAR_EMPTYB = OFF_BAR + 480, BAR_STAT = OFF_BAR + 544, BAR_DUMMY = OFF_BAR + 560;
constexpr int NA = 6;
constexpr uint32_t SB = 1024;
constexpr uint32_t SPIN_LIMIT = 1u << 22;

enum { TM_XIN = 0, TM_X, TM_XA, TM_O, TM_H, TM_WQKV, TM_WO, TM_W1A, TM_W1B, TM_W2, TM_X16, TM_XA16, TM_O16, TM_COUNT };

struct Scratch;
struct Ptrs {
  Scratch* s;
  __nv_bfloat16* out;
  const __nv_bfloat16* b1;
  const __nv_bfloat16* b2;
};
struct Params { CUtensorMap tm[TM_COUNT]; };

constexpr int NSTEP = 280, NSTEP_AUX = 128;
enum : uint32_t { F_STAMP = 1u << 28, F_GATH = 1u << 15, F_NEW = 1u << 16, F_AUG = 1u << 17, F_NOA = 1u << 18, E_HAND = 1u << 19, E_ATTN = 1u << 20, E_XPUB0 = 1u << 21,
                  E_WAIT = 1u << 22, E_REL = 1u << 23, E_KEEP = 1u << 24, E_PART1 = 1u << 25, E_HALO = 1u << 26,
                  E_SIG = 1u << 27, E_RARE = F_NEW | E_KEEP | (0xfu << 20) | (3u << 26) };
constexpr int own_round(int j) { return (OWNP >> (4 * j)) & 15; }
constexpr uint32_t first_order(int j) {
  uint32_t used = 0, v = 0;
  for (int p = 0; p < 8; p++) {
    int c = own_round(j) == p ? j : -1;
    for (int u = 0; u < 8 && c < 0; u++) if (u != j && !((used >> u) & 1) && own_round(u) < p) c = u;
    if (c < 0 && own_round(j ^ 1) == p) c = j ^ 1;
    for (int u = 0; u < 8 && c < 0; u++) { const int x = (u + (j & 6)) & 7; if (x != j && own_round(x) == p) c = x; }
    used |= 1u << c; v |= (uint32_t)c << (4 * p);
  }
  return v;
}
constexpr uint32_t first_round(int p) { uint32_t v = 0; for (int j = 0; j < 8; j++) v |= ((first_order(j) >> (4 * p)) & 15) << (4 * j); return v; }
constexpr uint32_t ROUND0 = first_round(0), ROUND1 = first_round(1);
__host__ __device__ constexpr int pos0(int kind) { return (P0S >> (4 * kind)) & 15; }
__host__ __device__ constexpr int posa(int kind) { return (PAS >> (4 * kind)) & 15; }
struct Sched { uint32_t v[9][NSTEP + 8]; };
constexpr Sched make_sched() {
  Sched T{};
  for (int j = 0; j < 8; j++) {
    int owner[16] = {};
    for (int i = 0; i < 16; i++) owner[i] = -100;
    int p = 0, g = 0;
    for (int t = 0; t < 12; t++) {
      const int kind = t % 6, ks = kind == 5 ? 56 : (kind == 2 ? 16 : 17);
      for (int i = 0; i < ks; i++) {
        const bool augs = ks == 17 && i == 16;
        const int na = (kind == 2 || kind == 5) ? 2 : (augs ? 1 : (kind == 4 ? 4 : 3));
        if (i == 0) p = pos0(kind);
        if (augs) p = posa(kind);
        if (p + na > 16) p = 0;
        int need = g - 8;
        for (int a = p; a < p + na; a++) { if (owner[a] > need) need = owner[a]; owner[a] = g; }
        uint32_t k = i, f = i == (t ? 0 : NPRO) ? F_NEW | (1u << 29) : 0;
        if (augs) { k = 0; f |= F_AUG; }
        else if (kind == 0 || kind == 3) {
          const int o = i - 2;
          if (t == 0) k = ((first_order(j) >> (4 * (i >> 1))) & 15) * 2 + (i & 1);
          else if (i < 2) { k = 2 * j + i; f |= F_NOA | (i == 0 ? E_XPUB0 : 0); }
          else { const int half = o >= 7; int u = o - 7 * half; u += u >= j; k = 2 * u + half; if (i == 6) f |= E_REL; }
          if (i == 11) f |= E_HAND;
          if (i == (t ? 11 : SIG0)) f |= E_SIG;
        } else if (kind == 1 || kind == 4) {
          if (kind == 1) f |= i == 3 ? E_HAND : (i == 8 ? E_HAND | E_KEEP : (i == 5 ? E_HALO : 0));
          if (kind == 1) f |= i == 13 ? E_REL : 0;
          else if (i == 4 || i == 7 || i == 10) f |= E_HAND;
        } else if (kind == 2) {
          f |= i == 0 ? E_WAIT : (i == 3 ? E_HAND : (i == 5 ? E_HALO : 0));
          if (i == 8) { k = 8 + j; f |= E_ATTN | E_KEEP | F_NOA; }
          if (i > 8) k = i - 1 + (i - 9 >= j);
          if (i == 11) f |= E_REL;
        } else {
          k = i < 24 ? (i / 3) * 7 + i % 3 : ((i - 24) / 4) * 7 + 3 + (i - 24) % 4;
          if (i == 4 || i == 7 || i == 10 || i == 13) f |= E_HAND;
          f |= i == 0 ? E_WAIT : (i == 24 ? E_WAIT | E_PART1 : 0);
        }
        if ((kind == 2 || kind == 5) && t < 11 && i == ks - (kind == 2 ? STA : STB)) f |= F_STAMP;
        if (((PACE2 >> kind) & 1) && i == ST2) f |= F_STAMP;
        if (i == 0 && t && ((PACE2 >> ((t - 1) % 6)) & 1)) f |= F_GATH;
        T.v[j][g] = p | ((g - need) << 5) | (k << 9) | f;
        p += na; g++;
      }
    }
    T.v[j][NSTEP] = F_NEW | F_NOA | E_XPUB0 | (2 * j << 9);
  }
  for (int w = 0; w < 2; w++) {
    int owner[14] = {};
    for (int i = 0; i < 14; i++) owner[i] = -100;
    for (int g = w, p = 0; g < NSTEP_AUX; g += 2) {
      const int na = g < 96 ? 3 : 4;
      if (p + na > 14) p = 0;
      int need = g - 8;
      for (int a = p; a < p + na; a++) { if (owner[a] > need) need = owner[a]; owner[a] = g; }
      T.v[8][g] = (p + 14 * w) | ((g - need) << 5) | ((g & 31) >> 1 << 9) | ((g & 30) && g - w != 8 ? 0 : F_NEW | (g - w == 64 ? 2u : 1u) << 29);
      p += na;
    }
  }
  return T;
}
__constant__ Sched c_sched = make_sched();
__device__ __forceinline__ int sched_k(uint32_t e) { return (e >> 3) & 0xfc0; }

struct Scratch {
  __nv_bfloat16 x[2048 * 1024];
  __nv_bfloat16 h[2048 * 3584];
  uint32_t epoch[160];
  uint8_t flags[16][2][64];
  uint32_t pace[8][64];
  uint32_t aug[2][32][1024];
  uint4 stats[4][512][8][2];
  uint4 halo[4][256][136];
};
__device__ __align__(1024) Scratch g_s;
#define PROF_T(w, t, i)
#define PRO(i)
#define LT(i)
#define CT(n)
#define ST(i)
#define AP(i)

__device__ __forceinline__ int work_id() {
  uint32_t smid;
  asm volatile("mov.u32 %0, %%smid;" : "=r"(smid));
  const int t = smid >> 1, u = t - 32, d = (u * 37) >> 8;
  int id = (t & 7) * 16 + (t >> 3) * 2;
  if (t >= 32) id = (1 + u - 7 * d) * 16 + (4 + d) * 2;
  if (t >= 60) id = t < 62 ? t * 2 + 8 : t * 2 - 116;
  return id + (smid & 1);
}

__device__ __forceinline__ uint32_t smem_u32(const void* p) { return (uint32_t)__cvta_generic_to_shared(p); }
__device__ __forceinline__ void mbar_init(uint32_t bar, int cnt) { asm volatile("mbarrier.init.shared::cta.b64 [%0], %1;" ::"r"(bar), "r"(cnt)); }
__device__ __forceinline__ void mbar_expect_tx(uint32_t bar, uint32_t bytes) { asm volatile("mbarrier.arrive.expect_tx.shared::cta.b64 _, [%0], %1;" ::"r"(bar), "r"(bytes) : "memory"); }
__device__ __forceinline__ void mbar_arrive(uint32_t bar, uint32_t cnt) { asm volatile("mbarrier.arrive.shared::cta.b64 _, [%0], %1;" ::"r"(bar), "r"(cnt) : "memory"); }
__device__ __forceinline__ void arrive_n(uint32_t bar, bool) { asm volatile("{\n.reg .pred p;\nelect.sync _|p, 0xffffffff;\n@p mbarrier.arrive.shared::cta.b64 _, [%0];\n}" ::"r"(bar) : "memory"); }
__device__ __forceinline__ void arrive_2(uint32_t b0, uint32_t b1, bool) {
  asm volatile("{\n.reg .pred p;\nelect.sync _|p, 0xffffffff;\n@p mbarrier.arrive.shared::cta.b64 _, [%0];\n@p mbarrier.arrive.shared::cta.b64 _, [%1];\n}" ::"r"(b0), "r"(b1) : "memory");
}
__device__ __forceinline__ void mbar_wait(uint32_t bar, uint32_t parity) {
  asm volatile(
      "{\n.reg .pred p;\n.reg .u32 c;\nmov.u32 c, 0;\n"
      "LAB_WAIT:\nmbarrier.try_wait.parity.shared::cta.b64 p, [%0], %1;\n@p bra.uni DONE;\n"
      "add.u32 c, c, 1;\nsetp.lt.u32 p, c, 4000000;\n@p bra.uni LAB_WAIT;\ntrap;\nDONE:\n}" ::"r"(bar), "r"(parity) : "memory");
}
__device__ __forceinline__ void mbar_spin(uint32_t bar, uint32_t parity) {
  asm volatile("{\n.reg .pred p;\nLAB_WAIT:\nmbarrier.try_wait.parity.shared::cta.b64 p, [%0], %1;\n@!p pmevent 7;\n@!p bra.uni LAB_WAIT;\n}" ::"r"(bar), "r"(parity) : "memory");
}
__device__ __forceinline__ void mbar_spin31(uint32_t bar, uint32_t ph) {
  asm volatile("{\n.reg .pred p;\n.reg .b64 s;\nmov.b64 s, {%1, %1};\nLAB_WAIT:\nmbarrier.try_wait.shared::cta.b64 p, [%0], s;\n@!p pmevent 7;\n@!p bra.uni LAB_WAIT;\n}" ::"r"(bar), "r"(ph) : "memory");
}
__device__ __forceinline__ bool elect_one() {
  uint32_t p;
  asm volatile("{\n.reg .pred P;\nelect.sync _|P, 0xffffffff;\nselp.u32 %0, 1, 0, P;\n}" : "=r"(p));
  return p != 0;
}
__device__ __forceinline__ bool mbar_test(uint32_t bar, uint32_t parity) {
  uint32_t ok;
  asm volatile("{\n.reg .pred p;\nmbarrier.test_wait.parity.shared::cta.b64 p, [%1], %2;\nselp.u32 %0, 1, 0, p;\n}" : "=r"(ok) : "r"(bar), "r"(parity) : "memory");
  return ok != 0;
}
__device__ __forceinline__ void tma_ld2(uint32_t dst, const CUtensorMap* tm, int c0, int c1, uint32_t bar) {
  asm volatile("cp.async.bulk.tensor.2d.shared::cluster.global.mbarrier::complete_tx::bytes [%0], [%1, {%3, %4}], [%2];" ::"r"(dst), "l"(tm), "r"(bar), "r"(c0), "r"(c1) : "memory");
}
__device__ __forceinline__ void tma_ld4(uint32_t dst, const CUtensorMap* tm, int c1, int c2, int c3, uint32_t bar, uint64_t pol = 0x1000000000000000ull) {
  asm volatile("cp.async.bulk.tensor.4d.shared::cluster.global.mbarrier::complete_tx::bytes.L2::cache_hint [%0], [%1, {%3, %4, %5, %6}], [%2], %7;" ::"r"(dst), "l"(tm), "r"(bar), "r"(0), "r"(c1), "r"(c2), "r"(c3), "l"(pol) : "memory");
}
__device__ __forceinline__ void tma_st2(const CUtensorMap* tm, int c0, int c1, uint32_t src) {
  asm volatile("cp.async.bulk.tensor.2d.global.shared::cta.bulk_group [%0, {%2, %3}], [%1];" ::"l"(tm), "r"(src), "r"(c0), "r"(c1) : "memory");
}
__device__ __forceinline__ void bulk_ld(uint32_t dst, const void* src, uint32_t bytes, uint32_t bar) {
  asm volatile("cp.async.bulk.shared::cluster.global.mbarrier::complete_tx::bytes [%0], [%1], %2, [%3];" ::"r"(dst), "l"(src), "r"(bytes), "r"(bar) : "memory");
}
__device__ __forceinline__ void e_arrive(uint32_t bar, uint32_t cnt) {
  if (cnt == 1) asm volatile("{\n.reg .pred p;\nelect.sync _|p, 0xffffffff;\n@p mbarrier.arrive.shared::cta.b64 _, [%0];\n}" ::"r"(bar) : "memory");
  else asm volatile("{\n.reg .pred p;\nelect.sync _|p, 0xffffffff;\n@p mbarrier.arrive.shared::cta.b64 _, [%0], %1;\n}" ::"r"(bar), "r"(cnt) : "memory");
}
template <int BYTES = 8192> __device__ __forceinline__ void e_load(uint32_t dst, const CUtensorMap* tm, int c0, int c1, uint32_t bar, uint64_t pol = 0x1000000000000000ull) {
  asm volatile("{\n.reg .pred p;\nelect.sync _|p, 0xffffffff;\n@p mbarrier.arrive.expect_tx.shared::cta.b64 _, [%2], %5;\n"
               "@p cp.async.bulk.tensor.2d.shared::cluster.global.mbarrier::complete_tx::bytes.L2::cache_hint [%0], [%1, {%3, %4}], [%2], %6;\n}"
               ::"r"(dst), "l"(tm), "r"(bar), "r"(c0), "r"(c1), "n"(BYTES), "l"(pol) : "memory");
}
__device__ __forceinline__ void e_store(const CUtensorMap* tm, int c0, int c1, uint32_t src) {
  asm volatile("{\n.reg .pred p;\nfence.proxy.async.shared::cta;\nelect.sync _|p, 0xffffffff;\n"
               "@p cp.async.bulk.tensor.2d.global.shared::cta.bulk_group [%0, {%2, %3}], [%1];\ncp.async.bulk.commit_group;\n}"
               ::"l"(tm), "r"(src), "r"(c0), "r"(c1) : "memory");
}
__device__ __forceinline__ void bulk_commit() { asm volatile("cp.async.bulk.commit_group;" ::: "memory"); }
template <int N> __device__ __forceinline__ void bulk_wait_read() { asm volatile("cp.async.bulk.wait_group.read %0;" ::"n"(N) : "memory"); }
__device__ __forceinline__ void bulk_wait_all() { asm volatile("cp.async.bulk.wait_group 0;" ::: "memory"); }
__device__ __forceinline__ void fence_async_smem() { asm volatile("fence.proxy.async.shared::cta;" ::: "memory"); }
__device__ __forceinline__ void wg_fence() { asm volatile("wgmma.fence.sync.aligned;" ::: "memory"); }
__device__ __forceinline__ void wg_commit() { asm volatile("wgmma.commit_group.sync.aligned;" ::: "memory"); }
template <int N> __device__ __forceinline__ void wg_wait() { asm volatile("wgmma.wait_group.sync.aligned %0;" ::"n"(N) : "memory"); }
__device__ __forceinline__ void wg_bar(int w) { asm volatile("bar.sync %0, 128;" ::"r"(w + 1) : "memory"); }
__device__ __forceinline__ uint32_t ld_acquire(const uint32_t* p) { uint32_t v; asm volatile("ld.acquire.gpu.global.u32 %0, [%1];" : "=r"(v) : "l"(p) : "memory"); return v; }
__device__ __forceinline__ uint4 ld_relaxed4(const uint32_t* p) {
  uint4 v; asm volatile("ld.relaxed.gpu.global.v4.u32 {%0,%1,%2,%3}, [%4];" : "=r"(v.x), "=r"(v.y), "=r"(v.z), "=r"(v.w) : "l"(p) : "memory"); return v;
}
__device__ __forceinline__ void st_release8(uint8_t* p, uint32_t v) { asm volatile("st.release.gpu.global.u8 [%0], %1;" ::"l"(p), "r"(v) : "memory"); }
__device__ __forceinline__ uint32_t ld_relaxed(const uint32_t* p) { uint32_t v; asm volatile("ld.relaxed.gpu.global.u32 %0, [%1];" : "=r"(v) : "l"(p) : "memory"); return v; }
__device__ __forceinline__ void st_release(uint32_t* p, uint32_t v) { asm volatile("st.release.gpu.global.u32 [%0], %1;" ::"l"(p), "r"(v) : "memory"); }
__device__ __forceinline__ void st_pkt(uint4* p, uint32_t a, uint32_t b, uint32_t c, uint32_t d) {
  asm volatile("{\n.reg .b64 lo, hi;\n.reg .b128 v;\nmov.b64 lo, {%1, %2};\nmov.b64 hi, {%3, %4};\nmov.b128 v, {lo, hi};\nst.relaxed.gpu.global.b128 [%0], v;\n}" ::"l"(p), "r"(a), "r"(b), "r"(c), "r"(d) : "memory");
}
__device__ __forceinline__ uint4 ld_pkt(const uint4* p) {
  uint4 r;
  asm volatile("{\n.reg .b64 lo, hi;\n.reg .b128 v;\nld.relaxed.gpu.global.b128 v, [%4];\nmov.b128 {lo, hi}, v;\nmov.b64 {%0, %1}, lo;\nmov.b64 {%2, %3}, hi;\n}" : "=r"(r.x), "=r"(r.y), "=r"(r.z), "=r"(r.w) : "l"(p) : "memory");
  return r;
}
__device__ __forceinline__ uint32_t pack_bf16(float lo, float hi) { uint32_t d; asm("cvt.rn.bf16x2.f32 %0, %1, %2;" : "=r"(d) : "f"(hi), "f"(lo)); return d; }
__device__ __forceinline__ float ex2(float x) { float y; asm("ex2.approx.ftz.f32 %0, %1;" : "=f"(y) : "f"(x)); return y; }
__device__ __forceinline__ float rsq(float x) { float y; asm("rsqrt.approx.ftz.f32 %0, %1;" : "=f"(y) : "f"(x)); return y; }
__device__ __forceinline__ float rcp(float x) { float y; asm("rcp.approx.ftz.f32 %0, %1;" : "=f"(y) : "f"(x)); return y; }
__device__ __forceinline__ float bf_lo(uint32_t v) { return __uint_as_float(v << 16); }
__device__ __forceinline__ float bf_hi(uint32_t v) { return __uint_as_float(v & 0xffff0000u); }
__device__ __forceinline__ void stsm4(uint32_t addr, uint32_t a, uint32_t b, uint32_t c, uint32_t d) {
  asm volatile("stmatrix.sync.aligned.m8n8.x4.shared.b16 [%0], {%1, %2, %3, %4};" ::"r"(addr), "r"(a), "r"(b), "r"(c), "r"(d) : "memory");
}
__device__ __forceinline__ uint32_t movm(uint32_t a) { uint32_t d; asm volatile("movmatrix.sync.aligned.m8n8.trans.b16 %0, %1;" : "=r"(d) : "r"(a)); return d; }
__device__ __forceinline__ void mma16(float (&c)[4], uint32_t a0, uint32_t a1, uint32_t a2, uint32_t a3, uint32_t b0, uint32_t b1) {
  asm volatile("mma.sync.aligned.m16n8k16.row.col.f32.bf16.bf16.f32 {%0,%1,%2,%3}, {%4,%5,%6,%7}, {%8,%9}, {%0,%1,%2,%3};"
               : "+f"(c[0]), "+f"(c[1]), "+f"(c[2]), "+f"(c[3]) : "r"(a0), "r"(a1), "r"(a2), "r"(a3), "r"(b0), "r"(b1));
}
__device__ __forceinline__ void mma8(float (&c)[4], uint32_t a0, uint32_t a1, uint32_t b0) {
  asm volatile("mma.sync.aligned.m16n8k8.row.col.f32.bf16.bf16.f32 {%0,%1,%2,%3}, {%4,%5}, {%6}, {%0,%1,%2,%3};"
               : "+f"(c[0]), "+f"(c[1]), "+f"(c[2]), "+f"(c[3]) : "r"(a0), "r"(a1), "r"(b0));
}
__device__ __forceinline__ void sts128(uint32_t a, uint32_t x, uint32_t y, uint32_t z, uint32_t w) {
  asm volatile("st.shared.v4.b32 [%0], {%1,%2,%3,%4};" ::"r"(a), "r"(x), "r"(y), "r"(z), "r"(w) : "memory");
}
__device__ __forceinline__ float2 lds64(uint32_t a) { float2 v; asm volatile("ld.shared.v2.f32 {%0,%1}, [%2];" : "=f"(v.x), "=f"(v.y) : "r"(a)); return v; }
__device__ __forceinline__ float4 lds128(uint32_t a) { float4 v; asm volatile("ld.shared.v4.f32 {%0,%1,%2,%3}, [%4];" : "=f"(v.x), "=f"(v.y), "=f"(v.z), "=f"(v.w) : "r"(a)); return v; }
__device__ __forceinline__ uint32_t lds32(uint32_t a) { uint32_t v; asm volatile("ld.shared.b32 %0, [%1];" : "=r"(v) : "r"(a)); return v; }
constexpr uint32_t PA1 = 0x80000000u / NA + 1, G1 = 8 + (1u << 28);
constexpr uint32_t DA0 = ((SB + OFF_A) >> 4) | (1u << 16), DB0 = ((SB + OFF_B) >> 4) | (512u << 16);
template <int S> __device__ __forceinline__ uint2 wgmma_first128(float (&d)[S], uint32_t da, uint32_t& db, uint32_t h0, uint32_t h1, uint32_t one, uint32_t b0, uint32_t p0, uint32_t b1, uint32_t p1) {
  uint2 ok;
  asm volatile("{\n.reg .b64 a, b, s;\n.reg .b32 t, u;\n.reg .pred p, q;\nwgmma.fence.sync.aligned;\n"
    "mov.b32 t, %67;\n"
    "mov.b64 a, {t, %68};\nmov.b64 b, {%66, %69};\n"
    "wgmma.mma_async.sync.aligned.m64n128k16.f32.bf16.bf16 "
    "{%2, %3, %4, %5, %6, %7, %8, %9, %10, %11, %12, %13, %14, %15, %16, %17, %18, %19, %20, %21, %22, %23, %24, %25, %26, %27, %28, %29, %30, %31, %32, %33, %34, %35, %36, %37, %38, %39, %40, %41, %42, %43, %44, %45, %46, %47, %48, %49, %50, %51, %52, %53, %54, %55, %56, %57, %58, %59, %60, %61, %62, %63, %64, %65}, "
    "a, b, 0, 1, 1, 0, 1;\n"
    "mad.lo.u32 t, %70, 2, t;\nmad.lo.u32 %66, %70, 128, %66;\n"
    "mov.b64 a, {t, %68};\nmov.b64 b, {%66, %69};\n"
    "wgmma.mma_async.sync.aligned.m64n128k16.f32.bf16.bf16 "
    "{%2, %3, %4, %5, %6, %7, %8, %9, %10, %11, %12, %13, %14, %15, %16, %17, %18, %19, %20, %21, %22, %23, %24, %25, %26, %27, %28, %29, %30, %31, %32, %33, %34, %35, %36, %37, %38, %39, %40, %41, %42, %43, %44, %45, %46, %47, %48, %49, %50, %51, %52, %53, %54, %55, %56, %57, %58, %59, %60, %61, %62, %63, %64, %65}, "
    "a, b, 1, 1, 1, 0, 1;\n"
    "mad.lo.u32 t, %70, 2, t;\nmad.lo.u32 %66, %70, 128, %66;\n"
    "mov.b64 a, {t, %68};\nmov.b64 b, {%66, %69};\n"
    "wgmma.mma_async.sync.aligned.m64n128k16.f32.bf16.bf16 "
    "{%2, %3, %4, %5, %6, %7, %8, %9, %10, %11, %12, %13, %14, %15, %16, %17, %18, %19, %20, %21, %22, %23, %24, %25, %26, %27, %28, %29, %30, %31, %32, %33, %34, %35, %36, %37, %38, %39, %40, %41, %42, %43, %44, %45, %46, %47, %48, %49, %50, %51, %52, %53, %54, %55, %56, %57, %58, %59, %60, %61, %62, %63, %64, %65}, "
    "a, b, 1, 1, 1, 0, 1;\n"
    "mov.b64 s, {%72, %72};\nmbarrier.test_wait.shared::cta.b64 p, [%71], s;\nmov.b64 s, {%74, %74};\nmbarrier.test_wait.shared::cta.b64 q, [%73], s;\n"
    "mad.lo.u32 t, %70, 2, t;\nmad.lo.u32 %66, %70, 128, %66;\n"
    "mov.b64 a, {t, %68};\nmov.b64 b, {%66, %69};\n"
    "wgmma.mma_async.sync.aligned.m64n128k16.f32.bf16.bf16 "
    "{%2, %3, %4, %5, %6, %7, %8, %9, %10, %11, %12, %13, %14, %15, %16, %17, %18, %19, %20, %21, %22, %23, %24, %25, %26, %27, %28, %29, %30, %31, %32, %33, %34, %35, %36, %37, %38, %39, %40, %41, %42, %43, %44, %45, %46, %47, %48, %49, %50, %51, %52, %53, %54, %55, %56, %57, %58, %59, %60, %61, %62, %63, %64, %65}, "
    "a, b, 1, 1, 1, 0, 1;\n"
    "wgmma.commit_group.sync.aligned;\nselp.u32 %0, 1, 0, p;\nselp.u32 %1, 1, 0, q;\n}"
    : "=r"(ok.x), "=r"(ok.y), "=f"(d[0]), "=f"(d[1]), "=f"(d[2]), "=f"(d[3]), "=f"(d[4]), "=f"(d[5]), "=f"(d[6]), "=f"(d[7]), "=f"(d[8]), "=f"(d[9]), "=f"(d[10]), "=f"(d[11]), "=f"(d[12]), "=f"(d[13]), "=f"(d[14]), "=f"(d[15]), "=f"(d[16]), "=f"(d[17]), "=f"(d[18]), "=f"(d[19]), "=f"(d[20]), "=f"(d[21]), "=f"(d[22]), "=f"(d[23]), "=f"(d[24]), "=f"(d[25]), "=f"(d[26]), "=f"(d[27]), "=f"(d[28]), "=f"(d[29]), "=f"(d[30]), "=f"(d[31]), "=f"(d[32]), "=f"(d[33]), "=f"(d[34]), "=f"(d[35]), "=f"(d[36]), "=f"(d[37]), "=f"(d[38]), "=f"(d[39]), "=f"(d[40]), "=f"(d[41]), "=f"(d[42]), "=f"(d[43]), "=f"(d[44]), "=f"(d[45]), "=f"(d[46]), "=f"(d[47]), "=f"(d[48]), "=f"(d[49]), "=f"(d[50]), "=f"(d[51]), "=f"(d[52]), "=f"(d[53]), "=f"(d[54]), "=f"(d[55]), "=f"(d[56]), "=f"(d[57]), "=f"(d[58]), "=f"(d[59]), "=f"(d[60]), "=f"(d[61]), "=f"(d[62]), "=f"(d[63]), "+r"(db)
    : "r"(da), "r"(h0), "r"(h1), "r"(one), "r"(b0), "r"(p0), "r"(b1), "r"(p1) : "memory");
  return ok;
}
template <int S> __device__ __forceinline__ uint2 wgmma_step128(float (&d)[S], uint32_t da, uint32_t& db, uint32_t h0, uint32_t h1, uint32_t one, uint32_t b0, uint32_t p0, uint32_t b1, uint32_t p1) {
  uint2 ok;
  asm volatile("{\n.reg .b64 a, b, s;\n.reg .b32 t, u;\n.reg .pred p, q;\nwgmma.fence.sync.aligned;\n"
    "mov.b32 t, %67;\n"
    "mov.b64 a, {t, %68};\nmov.b64 b, {%66, %69};\n"
    "wgmma.mma_async.sync.aligned.m64n128k16.f32.bf16.bf16 "
    "{%2, %3, %4, %5, %6, %7, %8, %9, %10, %11, %12, %13, %14, %15, %16, %17, %18, %19, %20, %21, %22, %23, %24, %25, %26, %27, %28, %29, %30, %31, %32, %33, %34, %35, %36, %37, %38, %39, %40, %41, %42, %43, %44, %45, %46, %47, %48, %49, %50, %51, %52, %53, %54, %55, %56, %57, %58, %59, %60, %61, %62, %63, %64, %65}, "
    "a, b, 1, 1, 1, 0, 1;\n"
    "mad.lo.u32 t, %70, 2, t;\nmad.lo.u32 %66, %70, 128, %66;\n"
    "mov.b64 a, {t, %68};\nmov.b64 b, {%66, %69};\n"
    "wgmma.mma_async.sync.aligned.m64n128k16.f32.bf16.bf16 "
    "{%2, %3, %4, %5, %6, %7, %8, %9, %10, %11, %12, %13, %14, %15, %16, %17, %18, %19, %20, %21, %22, %23, %24, %25, %26, %27, %28, %29, %30, %31, %32, %33, %34, %35, %36, %37, %38, %39, %40, %41, %42, %43, %44, %45, %46, %47, %48, %49, %50, %51, %52, %53, %54, %55, %56, %57, %58, %59, %60, %61, %62, %63, %64, %65}, "
    "a, b, 1, 1, 1, 0, 1;\n"
    "mad.lo.u32 t, %70, 2, t;\nmad.lo.u32 %66, %70, 128, %66;\n"
    "mov.b64 a, {t, %68};\nmov.b64 b, {%66, %69};\n"
    "wgmma.mma_async.sync.aligned.m64n128k16.f32.bf16.bf16 "
    "{%2, %3, %4, %5, %6, %7, %8, %9, %10, %11, %12, %13, %14, %15, %16, %17, %18, %19, %20, %21, %22, %23, %24, %25, %26, %27, %28, %29, %30, %31, %32, %33, %34, %35, %36, %37, %38, %39, %40, %41, %42, %43, %44, %45, %46, %47, %48, %49, %50, %51, %52, %53, %54, %55, %56, %57, %58, %59, %60, %61, %62, %63, %64, %65}, "
    "a, b, 1, 1, 1, 0, 1;\n"
    "mov.b64 s, {%72, %72};\nmbarrier.test_wait.shared::cta.b64 p, [%71], s;\nmov.b64 s, {%74, %74};\nmbarrier.test_wait.shared::cta.b64 q, [%73], s;\n"
    "mad.lo.u32 t, %70, 2, t;\nmad.lo.u32 %66, %70, 128, %66;\n"
    "mov.b64 a, {t, %68};\nmov.b64 b, {%66, %69};\n"
    "wgmma.mma_async.sync.aligned.m64n128k16.f32.bf16.bf16 "
    "{%2, %3, %4, %5, %6, %7, %8, %9, %10, %11, %12, %13, %14, %15, %16, %17, %18, %19, %20, %21, %22, %23, %24, %25, %26, %27, %28, %29, %30, %31, %32, %33, %34, %35, %36, %37, %38, %39, %40, %41, %42, %43, %44, %45, %46, %47, %48, %49, %50, %51, %52, %53, %54, %55, %56, %57, %58, %59, %60, %61, %62, %63, %64, %65}, "
    "a, b, 1, 1, 1, 0, 1;\n"
    "wgmma.commit_group.sync.aligned;\nselp.u32 %0, 1, 0, p;\nselp.u32 %1, 1, 0, q;\n}"
    : "=r"(ok.x), "=r"(ok.y), "+f"(d[0]), "+f"(d[1]), "+f"(d[2]), "+f"(d[3]), "+f"(d[4]), "+f"(d[5]), "+f"(d[6]), "+f"(d[7]), "+f"(d[8]), "+f"(d[9]), "+f"(d[10]), "+f"(d[11]), "+f"(d[12]), "+f"(d[13]), "+f"(d[14]), "+f"(d[15]), "+f"(d[16]), "+f"(d[17]), "+f"(d[18]), "+f"(d[19]), "+f"(d[20]), "+f"(d[21]), "+f"(d[22]), "+f"(d[23]), "+f"(d[24]), "+f"(d[25]), "+f"(d[26]), "+f"(d[27]), "+f"(d[28]), "+f"(d[29]), "+f"(d[30]), "+f"(d[31]), "+f"(d[32]), "+f"(d[33]), "+f"(d[34]), "+f"(d[35]), "+f"(d[36]), "+f"(d[37]), "+f"(d[38]), "+f"(d[39]), "+f"(d[40]), "+f"(d[41]), "+f"(d[42]), "+f"(d[43]), "+f"(d[44]), "+f"(d[45]), "+f"(d[46]), "+f"(d[47]), "+f"(d[48]), "+f"(d[49]), "+f"(d[50]), "+f"(d[51]), "+f"(d[52]), "+f"(d[53]), "+f"(d[54]), "+f"(d[55]), "+f"(d[56]), "+f"(d[57]), "+f"(d[58]), "+f"(d[59]), "+f"(d[60]), "+f"(d[61]), "+f"(d[62]), "+f"(d[63]), "+r"(db)
    : "r"(da), "r"(h0), "r"(h1), "r"(one), "r"(b0), "r"(p0), "r"(b1), "r"(p1) : "memory");
  return ok;
}
template <int S> __device__ __forceinline__ uint2 wgmma_first192(float (&d)[S], uint32_t da, uint32_t& db, uint32_t h0, uint32_t h1, uint32_t one, uint32_t b0, uint32_t p0, uint32_t b1, uint32_t p1) {
  uint2 ok;
  asm volatile("{\n.reg .b64 a, b, s;\n.reg .b32 t, u;\n.reg .pred p, q;\nwgmma.fence.sync.aligned;\n"
    "mov.b32 t, %99;\n"
    "mov.b64 a, {t, %100};\nmov.b64 b, {%98, %101};\n"
    "wgmma.mma_async.sync.aligned.m64n192k16.f32.bf16.bf16 "
    "{%2, %3, %4, %5, %6, %7, %8, %9, %10, %11, %12, %13, %14, %15, %16, %17, %18, %19, %20, %21, %22, %23, %24, %25, %26, %27, %28, %29, %30, %31, %32, %33, %34, %35, %36, %37, %38, %39, %40, %41, %42, %43, %44, %45, %46, %47, %48, %49, %50, %51, %52, %53, %54, %55, %56, %57, %58, %59, %60, %61, %62, %63, %64, %65, %66, %67, %68, %69, %70, %71, %72, %73, %74, %75, %76, %77, %78, %79, %80, %81, %82, %83, %84, %85, %86, %87, %88, %89, %90, %91, %92, %93, %94, %95, %96, %97}, "
    "a, b, 0, 1, 1, 0, 1;\n"
    "mad.lo.u32 t, %102, 2, t;\nmad.lo.u32 %98, %102, 128, %98;\n"
    "mov.b64 a, {t, %100};\nmov.b64 b, {%98, %101};\n"
    "wgmma.mma_async.sync.aligned.m64n192k16.f32.bf16.bf16 "
    "{%2, %3, %4, %5, %6, %7, %8, %9, %10, %11, %12, %13, %14, %15, %16, %17, %18, %19, %20, %21, %22, %23, %24, %25, %26, %27, %28, %29, %30, %31, %32, %33, %34, %35, %36, %37, %38, %39, %40, %41, %42, %43, %44, %45, %46, %47, %48, %49, %50, %51, %52, %53, %54, %55, %56, %57, %58, %59, %60, %61, %62, %63, %64, %65, %66, %67, %68, %69, %70, %71, %72, %73, %74, %75, %76, %77, %78, %79, %80, %81, %82, %83, %84, %85, %86, %87, %88, %89, %90, %91, %92, %93, %94, %95, %96, %97}, "
    "a, b, 1, 1, 1, 0, 1;\n"
    "mad.lo.u32 t, %102, 2, t;\nmad.lo.u32 %98, %102, 128, %98;\n"
    "mov.b64 a, {t, %100};\nmov.b64 b, {%98, %101};\n"
    "wgmma.mma_async.sync.aligned.m64n192k16.f32.bf16.bf16 "
    "{%2, %3, %4, %5, %6, %7, %8, %9, %10, %11, %12, %13, %14, %15, %16, %17, %18, %19, %20, %21, %22, %23, %24, %25, %26, %27, %28, %29, %30, %31, %32, %33, %34, %35, %36, %37, %38, %39, %40, %41, %42, %43, %44, %45, %46, %47, %48, %49, %50, %51, %52, %53, %54, %55, %56, %57, %58, %59, %60, %61, %62, %63, %64, %65, %66, %67, %68, %69, %70, %71, %72, %73, %74, %75, %76, %77, %78, %79, %80, %81, %82, %83, %84, %85, %86, %87, %88, %89, %90, %91, %92, %93, %94, %95, %96, %97}, "
    "a, b, 1, 1, 1, 0, 1;\n"
    "mov.b64 s, {%104, %104};\nmbarrier.test_wait.shared::cta.b64 p, [%103], s;\nmov.b64 s, {%106, %106};\nmbarrier.test_wait.shared::cta.b64 q, [%105], s;\n"
    "mad.lo.u32 t, %102, 2, t;\nmad.lo.u32 %98, %102, 128, %98;\n"
    "mov.b64 a, {t, %100};\nmov.b64 b, {%98, %101};\n"
    "wgmma.mma_async.sync.aligned.m64n192k16.f32.bf16.bf16 "
    "{%2, %3, %4, %5, %6, %7, %8, %9, %10, %11, %12, %13, %14, %15, %16, %17, %18, %19, %20, %21, %22, %23, %24, %25, %26, %27, %28, %29, %30, %31, %32, %33, %34, %35, %36, %37, %38, %39, %40, %41, %42, %43, %44, %45, %46, %47, %48, %49, %50, %51, %52, %53, %54, %55, %56, %57, %58, %59, %60, %61, %62, %63, %64, %65, %66, %67, %68, %69, %70, %71, %72, %73, %74, %75, %76, %77, %78, %79, %80, %81, %82, %83, %84, %85, %86, %87, %88, %89, %90, %91, %92, %93, %94, %95, %96, %97}, "
    "a, b, 1, 1, 1, 0, 1;\n"
    "wgmma.commit_group.sync.aligned;\nselp.u32 %0, 1, 0, p;\nselp.u32 %1, 1, 0, q;\n}"
    : "=r"(ok.x), "=r"(ok.y), "=f"(d[0]), "=f"(d[1]), "=f"(d[2]), "=f"(d[3]), "=f"(d[4]), "=f"(d[5]), "=f"(d[6]), "=f"(d[7]), "=f"(d[8]), "=f"(d[9]), "=f"(d[10]), "=f"(d[11]), "=f"(d[12]), "=f"(d[13]), "=f"(d[14]), "=f"(d[15]), "=f"(d[16]), "=f"(d[17]), "=f"(d[18]), "=f"(d[19]), "=f"(d[20]), "=f"(d[21]), "=f"(d[22]), "=f"(d[23]), "=f"(d[24]), "=f"(d[25]), "=f"(d[26]), "=f"(d[27]), "=f"(d[28]), "=f"(d[29]), "=f"(d[30]), "=f"(d[31]), "=f"(d[32]), "=f"(d[33]), "=f"(d[34]), "=f"(d[35]), "=f"(d[36]), "=f"(d[37]), "=f"(d[38]), "=f"(d[39]), "=f"(d[40]), "=f"(d[41]), "=f"(d[42]), "=f"(d[43]), "=f"(d[44]), "=f"(d[45]), "=f"(d[46]), "=f"(d[47]), "=f"(d[48]), "=f"(d[49]), "=f"(d[50]), "=f"(d[51]), "=f"(d[52]), "=f"(d[53]), "=f"(d[54]), "=f"(d[55]), "=f"(d[56]), "=f"(d[57]), "=f"(d[58]), "=f"(d[59]), "=f"(d[60]), "=f"(d[61]), "=f"(d[62]), "=f"(d[63]), "=f"(d[64]), "=f"(d[65]), "=f"(d[66]), "=f"(d[67]), "=f"(d[68]), "=f"(d[69]), "=f"(d[70]), "=f"(d[71]), "=f"(d[72]), "=f"(d[73]), "=f"(d[74]), "=f"(d[75]), "=f"(d[76]), "=f"(d[77]), "=f"(d[78]), "=f"(d[79]), "=f"(d[80]), "=f"(d[81]), "=f"(d[82]), "=f"(d[83]), "=f"(d[84]), "=f"(d[85]), "=f"(d[86]), "=f"(d[87]), "=f"(d[88]), "=f"(d[89]), "=f"(d[90]), "=f"(d[91]), "=f"(d[92]), "=f"(d[93]), "=f"(d[94]), "=f"(d[95]), "+r"(db)
    : "r"(da), "r"(h0), "r"(h1), "r"(one), "r"(b0), "r"(p0), "r"(b1), "r"(p1) : "memory");
  return ok;
}
template <int S> __device__ __forceinline__ uint2 wgmma_step192(float (&d)[S], uint32_t da, uint32_t& db, uint32_t h0, uint32_t h1, uint32_t one, uint32_t b0, uint32_t p0, uint32_t b1, uint32_t p1) {
  uint2 ok;
  asm volatile("{\n.reg .b64 a, b, s;\n.reg .b32 t, u;\n.reg .pred p, q;\nwgmma.fence.sync.aligned;\n"
    "mov.b32 t, %99;\n"
    "mov.b64 a, {t, %100};\nmov.b64 b, {%98, %101};\n"
    "wgmma.mma_async.sync.aligned.m64n192k16.f32.bf16.bf16 "
    "{%2, %3, %4, %5, %6, %7, %8, %9, %10, %11, %12, %13, %14, %15, %16, %17, %18, %19, %20, %21, %22, %23, %24, %25, %26, %27, %28, %29, %30, %31, %32, %33, %34, %35, %36, %37, %38, %39, %40, %41, %42, %43, %44, %45, %46, %47, %48, %49, %50, %51, %52, %53, %54, %55, %56, %57, %58, %59, %60, %61, %62, %63, %64, %65, %66, %67, %68, %69, %70, %71, %72, %73, %74, %75, %76, %77, %78, %79, %80, %81, %82, %83, %84, %85, %86, %87, %88, %89, %90, %91, %92, %93, %94, %95, %96, %97}, "
    "a, b, 1, 1, 1, 0, 1;\n"
    "mad.lo.u32 t, %102, 2, t;\nmad.lo.u32 %98, %102, 128, %98;\n"
    "mov.b64 a, {t, %100};\nmov.b64 b, {%98, %101};\n"
    "wgmma.mma_async.sync.aligned.m64n192k16.f32.bf16.bf16 "
    "{%2, %3, %4, %5, %6, %7, %8, %9, %10, %11, %12, %13, %14, %15, %16, %17, %18, %19, %20, %21, %22, %23, %24, %25, %26, %27, %28, %29, %30, %31, %32, %33, %34, %35, %36, %37, %38, %39, %40, %41, %42, %43, %44, %45, %46, %47, %48, %49, %50, %51, %52, %53, %54, %55, %56, %57, %58, %59, %60, %61, %62, %63, %64, %65, %66, %67, %68, %69, %70, %71, %72, %73, %74, %75, %76, %77, %78, %79, %80, %81, %82, %83, %84, %85, %86, %87, %88, %89, %90, %91, %92, %93, %94, %95, %96, %97}, "
    "a, b, 1, 1, 1, 0, 1;\n"
    "mad.lo.u32 t, %102, 2, t;\nmad.lo.u32 %98, %102, 128, %98;\n"
    "mov.b64 a, {t, %100};\nmov.b64 b, {%98, %101};\n"
    "wgmma.mma_async.sync.aligned.m64n192k16.f32.bf16.bf16 "
    "{%2, %3, %4, %5, %6, %7, %8, %9, %10, %11, %12, %13, %14, %15, %16, %17, %18, %19, %20, %21, %22, %23, %24, %25, %26, %27, %28, %29, %30, %31, %32, %33, %34, %35, %36, %37, %38, %39, %40, %41, %42, %43, %44, %45, %46, %47, %48, %49, %50, %51, %52, %53, %54, %55, %56, %57, %58, %59, %60, %61, %62, %63, %64, %65, %66, %67, %68, %69, %70, %71, %72, %73, %74, %75, %76, %77, %78, %79, %80, %81, %82, %83, %84, %85, %86, %87, %88, %89, %90, %91, %92, %93, %94, %95, %96, %97}, "
    "a, b, 1, 1, 1, 0, 1;\n"
    "mov.b64 s, {%104, %104};\nmbarrier.test_wait.shared::cta.b64 p, [%103], s;\nmov.b64 s, {%106, %106};\nmbarrier.test_wait.shared::cta.b64 q, [%105], s;\n"
    "mad.lo.u32 t, %102, 2, t;\nmad.lo.u32 %98, %102, 128, %98;\n"
    "mov.b64 a, {t, %100};\nmov.b64 b, {%98, %101};\n"
    "wgmma.mma_async.sync.aligned.m64n192k16.f32.bf16.bf16 "
    "{%2, %3, %4, %5, %6, %7, %8, %9, %10, %11, %12, %13, %14, %15, %16, %17, %18, %19, %20, %21, %22, %23, %24, %25, %26, %27, %28, %29, %30, %31, %32, %33, %34, %35, %36, %37, %38, %39, %40, %41, %42, %43, %44, %45, %46, %47, %48, %49, %50, %51, %52, %53, %54, %55, %56, %57, %58, %59, %60, %61, %62, %63, %64, %65, %66, %67, %68, %69, %70, %71, %72, %73, %74, %75, %76, %77, %78, %79, %80, %81, %82, %83, %84, %85, %86, %87, %88, %89, %90, %91, %92, %93, %94, %95, %96, %97}, "
    "a, b, 1, 1, 1, 0, 1;\n"
    "wgmma.commit_group.sync.aligned;\nselp.u32 %0, 1, 0, p;\nselp.u32 %1, 1, 0, q;\n}"
    : "=r"(ok.x), "=r"(ok.y), "+f"(d[0]), "+f"(d[1]), "+f"(d[2]), "+f"(d[3]), "+f"(d[4]), "+f"(d[5]), "+f"(d[6]), "+f"(d[7]), "+f"(d[8]), "+f"(d[9]), "+f"(d[10]), "+f"(d[11]), "+f"(d[12]), "+f"(d[13]), "+f"(d[14]), "+f"(d[15]), "+f"(d[16]), "+f"(d[17]), "+f"(d[18]), "+f"(d[19]), "+f"(d[20]), "+f"(d[21]), "+f"(d[22]), "+f"(d[23]), "+f"(d[24]), "+f"(d[25]), "+f"(d[26]), "+f"(d[27]), "+f"(d[28]), "+f"(d[29]), "+f"(d[30]), "+f"(d[31]), "+f"(d[32]), "+f"(d[33]), "+f"(d[34]), "+f"(d[35]), "+f"(d[36]), "+f"(d[37]), "+f"(d[38]), "+f"(d[39]), "+f"(d[40]), "+f"(d[41]), "+f"(d[42]), "+f"(d[43]), "+f"(d[44]), "+f"(d[45]), "+f"(d[46]), "+f"(d[47]), "+f"(d[48]), "+f"(d[49]), "+f"(d[50]), "+f"(d[51]), "+f"(d[52]), "+f"(d[53]), "+f"(d[54]), "+f"(d[55]), "+f"(d[56]), "+f"(d[57]), "+f"(d[58]), "+f"(d[59]), "+f"(d[60]), "+f"(d[61]), "+f"(d[62]), "+f"(d[63]), "+f"(d[64]), "+f"(d[65]), "+f"(d[66]), "+f"(d[67]), "+f"(d[68]), "+f"(d[69]), "+f"(d[70]), "+f"(d[71]), "+f"(d[72]), "+f"(d[73]), "+f"(d[74]), "+f"(d[75]), "+f"(d[76]), "+f"(d[77]), "+f"(d[78]), "+f"(d[79]), "+f"(d[80]), "+f"(d[81]), "+f"(d[82]), "+f"(d[83]), "+f"(d[84]), "+f"(d[85]), "+f"(d[86]), "+f"(d[87]), "+f"(d[88]), "+f"(d[89]), "+f"(d[90]), "+f"(d[91]), "+f"(d[92]), "+f"(d[93]), "+f"(d[94]), "+f"(d[95]), "+r"(db)
    : "r"(da), "r"(h0), "r"(h1), "r"(one), "r"(b0), "r"(p0), "r"(b1), "r"(p1) : "memory");
  return ok;
}
template <int S> __device__ __forceinline__ uint2 wgmma_first256(float (&d)[S], uint32_t da, uint32_t& db, uint32_t h0, uint32_t h1, uint32_t one, uint32_t b0, uint32_t p0, uint32_t b1, uint32_t p1) {
  uint2 ok;
  asm volatile("{\n.reg .b64 a, b, s;\n.reg .b32 t, u;\n.reg .pred p, q;\nwgmma.fence.sync.aligned;\n"
    "mov.b32 t, %131;\n"
    "mov.b64 a, {t, %132};\nmov.b64 b, {%130, %133};\n"
    "wgmma.mma_async.sync.aligned.m64n256k16.f32.bf16.bf16 "
    "{%2, %3, %4, %5, %6, %7, %8, %9, %10, %11, %12, %13, %14, %15, %16, %17, %18, %19, %20, %21, %22, %23, %24, %25, %26, %27, %28, %29, %30, %31, %32, %33, %34, %35, %36, %37, %38, %39, %40, %41, %42, %43, %44, %45, %46, %47, %48, %49, %50, %51, %52, %53, %54, %55, %56, %57, %58, %59, %60, %61, %62, %63, %64, %65, %66, %67, %68, %69, %70, %71, %72, %73, %74, %75, %76, %77, %78, %79, %80, %81, %82, %83, %84, %85, %86, %87, %88, %89, %90, %91, %92, %93, %94, %95, %96, %97, %98, %99, %100, %101, %102, %103, %104, %105, %106, %107, %108, %109, %110, %111, %112, %113, %114, %115, %116, %117, %118, %119, %120, %121, %122, %123, %124, %125, %126, %127, %128, %129}, "
    "a, b, 0, 1, 1, 0, 1;\n"
    "mad.lo.u32 t, %134, 2, t;\nmad.lo.u32 %130, %134, 128, %130;\n"
    "mov.b64 a, {t, %132};\nmov.b64 b, {%130, %133};\n"
    "wgmma.mma_async.sync.aligned.m64n256k16.f32.bf16.bf16 "
    "{%2, %3, %4, %5, %6, %7, %8, %9, %10, %11, %12, %13, %14, %15, %16, %17, %18, %19, %20, %21, %22, %23, %24, %25, %26, %27, %28, %29, %30, %31, %32, %33, %34, %35, %36, %37, %38, %39, %40, %41, %42, %43, %44, %45, %46, %47, %48, %49, %50, %51, %52, %53, %54, %55, %56, %57, %58, %59, %60, %61, %62, %63, %64, %65, %66, %67, %68, %69, %70, %71, %72, %73, %74, %75, %76, %77, %78, %79, %80, %81, %82, %83, %84, %85, %86, %87, %88, %89, %90, %91, %92, %93, %94, %95, %96, %97, %98, %99, %100, %101, %102, %103, %104, %105, %106, %107, %108, %109, %110, %111, %112, %113, %114, %115, %116, %117, %118, %119, %120, %121, %122, %123, %124, %125, %126, %127, %128, %129}, "
    "a, b, 1, 1, 1, 0, 1;\n"
    "mov.b64 s, {%136, %136};\nmbarrier.test_wait.shared::cta.b64 p, [%135], s;\nmov.b64 s, {%138, %138};\nmbarrier.test_wait.shared::cta.b64 q, [%137], s;\n"
    "mad.lo.u32 t, %134, 2, t;\nmad.lo.u32 %130, %134, 128, %130;\n"
    "mov.b64 a, {t, %132};\nmov.b64 b, {%130, %133};\n"
    "wgmma.mma_async.sync.aligned.m64n256k16.f32.bf16.bf16 "
    "{%2, %3, %4, %5, %6, %7, %8, %9, %10, %11, %12, %13, %14, %15, %16, %17, %18, %19, %20, %21, %22, %23, %24, %25, %26, %27, %28, %29, %30, %31, %32, %33, %34, %35, %36, %37, %38, %39, %40, %41, %42, %43, %44, %45, %46, %47, %48, %49, %50, %51, %52, %53, %54, %55, %56, %57, %58, %59, %60, %61, %62, %63, %64, %65, %66, %67, %68, %69, %70, %71, %72, %73, %74, %75, %76, %77, %78, %79, %80, %81, %82, %83, %84, %85, %86, %87, %88, %89, %90, %91, %92, %93, %94, %95, %96, %97, %98, %99, %100, %101, %102, %103, %104, %105, %106, %107, %108, %109, %110, %111, %112, %113, %114, %115, %116, %117, %118, %119, %120, %121, %122, %123, %124, %125, %126, %127, %128, %129}, "
    "a, b, 1, 1, 1, 0, 1;\n"
    "mad.lo.u32 t, %134, 2, t;\nmad.lo.u32 %130, %134, 128, %130;\n"
    "mov.b64 a, {t, %132};\nmov.b64 b, {%130, %133};\n"
    "wgmma.mma_async.sync.aligned.m64n256k16.f32.bf16.bf16 "
    "{%2, %3, %4, %5, %6, %7, %8, %9, %10, %11, %12, %13, %14, %15, %16, %17, %18, %19, %20, %21, %22, %23, %24, %25, %26, %27, %28, %29, %30, %31, %32, %33, %34, %35, %36, %37, %38, %39, %40, %41, %42, %43, %44, %45, %46, %47, %48, %49, %50, %51, %52, %53, %54, %55, %56, %57, %58, %59, %60, %61, %62, %63, %64, %65, %66, %67, %68, %69, %70, %71, %72, %73, %74, %75, %76, %77, %78, %79, %80, %81, %82, %83, %84, %85, %86, %87, %88, %89, %90, %91, %92, %93, %94, %95, %96, %97, %98, %99, %100, %101, %102, %103, %104, %105, %106, %107, %108, %109, %110, %111, %112, %113, %114, %115, %116, %117, %118, %119, %120, %121, %122, %123, %124, %125, %126, %127, %128, %129}, "
    "a, b, 1, 1, 1, 0, 1;\n"
    "wgmma.commit_group.sync.aligned;\nselp.u32 %0, 1, 0, p;\nselp.u32 %1, 1, 0, q;\n}"
    : "=r"(ok.x), "=r"(ok.y), "=f"(d[0]), "=f"(d[1]), "=f"(d[2]), "=f"(d[3]), "=f"(d[4]), "=f"(d[5]), "=f"(d[6]), "=f"(d[7]), "=f"(d[8]), "=f"(d[9]), "=f"(d[10]), "=f"(d[11]), "=f"(d[12]), "=f"(d[13]), "=f"(d[14]), "=f"(d[15]), "=f"(d[16]), "=f"(d[17]), "=f"(d[18]), "=f"(d[19]), "=f"(d[20]), "=f"(d[21]), "=f"(d[22]), "=f"(d[23]), "=f"(d[24]), "=f"(d[25]), "=f"(d[26]), "=f"(d[27]), "=f"(d[28]), "=f"(d[29]), "=f"(d[30]), "=f"(d[31]), "=f"(d[32]), "=f"(d[33]), "=f"(d[34]), "=f"(d[35]), "=f"(d[36]), "=f"(d[37]), "=f"(d[38]), "=f"(d[39]), "=f"(d[40]), "=f"(d[41]), "=f"(d[42]), "=f"(d[43]), "=f"(d[44]), "=f"(d[45]), "=f"(d[46]), "=f"(d[47]), "=f"(d[48]), "=f"(d[49]), "=f"(d[50]), "=f"(d[51]), "=f"(d[52]), "=f"(d[53]), "=f"(d[54]), "=f"(d[55]), "=f"(d[56]), "=f"(d[57]), "=f"(d[58]), "=f"(d[59]), "=f"(d[60]), "=f"(d[61]), "=f"(d[62]), "=f"(d[63]), "=f"(d[64]), "=f"(d[65]), "=f"(d[66]), "=f"(d[67]), "=f"(d[68]), "=f"(d[69]), "=f"(d[70]), "=f"(d[71]), "=f"(d[72]), "=f"(d[73]), "=f"(d[74]), "=f"(d[75]), "=f"(d[76]), "=f"(d[77]), "=f"(d[78]), "=f"(d[79]), "=f"(d[80]), "=f"(d[81]), "=f"(d[82]), "=f"(d[83]), "=f"(d[84]), "=f"(d[85]), "=f"(d[86]), "=f"(d[87]), "=f"(d[88]), "=f"(d[89]), "=f"(d[90]), "=f"(d[91]), "=f"(d[92]), "=f"(d[93]), "=f"(d[94]), "=f"(d[95]), "=f"(d[96]), "=f"(d[97]), "=f"(d[98]), "=f"(d[99]), "=f"(d[100]), "=f"(d[101]), "=f"(d[102]), "=f"(d[103]), "=f"(d[104]), "=f"(d[105]), "=f"(d[106]), "=f"(d[107]), "=f"(d[108]), "=f"(d[109]), "=f"(d[110]), "=f"(d[111]), "=f"(d[112]), "=f"(d[113]), "=f"(d[114]), "=f"(d[115]), "=f"(d[116]), "=f"(d[117]), "=f"(d[118]), "=f"(d[119]), "=f"(d[120]), "=f"(d[121]), "=f"(d[122]), "=f"(d[123]), "=f"(d[124]), "=f"(d[125]), "=f"(d[126]), "=f"(d[127]), "+r"(db)
    : "r"(da), "r"(h0), "r"(h1), "r"(one), "r"(b0), "r"(p0), "r"(b1), "r"(p1) : "memory");
  return ok;
}
template <int S> __device__ __forceinline__ uint2 wgmma_step256(float (&d)[S], uint32_t da, uint32_t& db, uint32_t h0, uint32_t h1, uint32_t one, uint32_t b0, uint32_t p0, uint32_t b1, uint32_t p1) {
  uint2 ok;
  asm volatile("{\n.reg .b64 a, b, s;\n.reg .b32 t, u;\n.reg .pred p, q;\nwgmma.fence.sync.aligned;\n"
    "mov.b32 t, %131;\n"
    "mov.b64 a, {t, %132};\nmov.b64 b, {%130, %133};\n"
    "wgmma.mma_async.sync.aligned.m64n256k16.f32.bf16.bf16 "
    "{%2, %3, %4, %5, %6, %7, %8, %9, %10, %11, %12, %13, %14, %15, %16, %17, %18, %19, %20, %21, %22, %23, %24, %25, %26, %27, %28, %29, %30, %31, %32, %33, %34, %35, %36, %37, %38, %39, %40, %41, %42, %43, %44, %45, %46, %47, %48, %49, %50, %51, %52, %53, %54, %55, %56, %57, %58, %59, %60, %61, %62, %63, %64, %65, %66, %67, %68, %69, %70, %71, %72, %73, %74, %75, %76, %77, %78, %79, %80, %81, %82, %83, %84, %85, %86, %87, %88, %89, %90, %91, %92, %93, %94, %95, %96, %97, %98, %99, %100, %101, %102, %103, %104, %105, %106, %107, %108, %109, %110, %111, %112, %113, %114, %115, %116, %117, %118, %119, %120, %121, %122, %123, %124, %125, %126, %127, %128, %129}, "
    "a, b, 1, 1, 1, 0, 1;\n"
    "mad.lo.u32 t, %134, 2, t;\nmad.lo.u32 %130, %134, 128, %130;\n"
    "mov.b64 a, {t, %132};\nmov.b64 b, {%130, %133};\n"
    "wgmma.mma_async.sync.aligned.m64n256k16.f32.bf16.bf16 "
    "{%2, %3, %4, %5, %6, %7, %8, %9, %10, %11, %12, %13, %14, %15, %16, %17, %18, %19, %20, %21, %22, %23, %24, %25, %26, %27, %28, %29, %30, %31, %32, %33, %34, %35, %36, %37, %38, %39, %40, %41, %42, %43, %44, %45, %46, %47, %48, %49, %50, %51, %52, %53, %54, %55, %56, %57, %58, %59, %60, %61, %62, %63, %64, %65, %66, %67, %68, %69, %70, %71, %72, %73, %74, %75, %76, %77, %78, %79, %80, %81, %82, %83, %84, %85, %86, %87, %88, %89, %90, %91, %92, %93, %94, %95, %96, %97, %98, %99, %100, %101, %102, %103, %104, %105, %106, %107, %108, %109, %110, %111, %112, %113, %114, %115, %116, %117, %118, %119, %120, %121, %122, %123, %124, %125, %126, %127, %128, %129}, "
    "a, b, 1, 1, 1, 0, 1;\n"
    "mov.b64 s, {%136, %136};\nmbarrier.test_wait.shared::cta.b64 p, [%135], s;\nmov.b64 s, {%138, %138};\nmbarrier.test_wait.shared::cta.b64 q, [%137], s;\n"
    "mad.lo.u32 t, %134, 2, t;\nmad.lo.u32 %130, %134, 128, %130;\n"
    "mov.b64 a, {t, %132};\nmov.b64 b, {%130, %133};\n"
    "wgmma.mma_async.sync.aligned.m64n256k16.f32.bf16.bf16 "
    "{%2, %3, %4, %5, %6, %7, %8, %9, %10, %11, %12, %13, %14, %15, %16, %17, %18, %19, %20, %21, %22, %23, %24, %25, %26, %27, %28, %29, %30, %31, %32, %33, %34, %35, %36, %37, %38, %39, %40, %41, %42, %43, %44, %45, %46, %47, %48, %49, %50, %51, %52, %53, %54, %55, %56, %57, %58, %59, %60, %61, %62, %63, %64, %65, %66, %67, %68, %69, %70, %71, %72, %73, %74, %75, %76, %77, %78, %79, %80, %81, %82, %83, %84, %85, %86, %87, %88, %89, %90, %91, %92, %93, %94, %95, %96, %97, %98, %99, %100, %101, %102, %103, %104, %105, %106, %107, %108, %109, %110, %111, %112, %113, %114, %115, %116, %117, %118, %119, %120, %121, %122, %123, %124, %125, %126, %127, %128, %129}, "
    "a, b, 1, 1, 1, 0, 1;\n"
    "mad.lo.u32 t, %134, 2, t;\nmad.lo.u32 %130, %134, 128, %130;\n"
    "mov.b64 a, {t, %132};\nmov.b64 b, {%130, %133};\n"
    "wgmma.mma_async.sync.aligned.m64n256k16.f32.bf16.bf16 "
    "{%2, %3, %4, %5, %6, %7, %8, %9, %10, %11, %12, %13, %14, %15, %16, %17, %18, %19, %20, %21, %22, %23, %24, %25, %26, %27, %28, %29, %30, %31, %32, %33, %34, %35, %36, %37, %38, %39, %40, %41, %42, %43, %44, %45, %46, %47, %48, %49, %50, %51, %52, %53, %54, %55, %56, %57, %58, %59, %60, %61, %62, %63, %64, %65, %66, %67, %68, %69, %70, %71, %72, %73, %74, %75, %76, %77, %78, %79, %80, %81, %82, %83, %84, %85, %86, %87, %88, %89, %90, %91, %92, %93, %94, %95, %96, %97, %98, %99, %100, %101, %102, %103, %104, %105, %106, %107, %108, %109, %110, %111, %112, %113, %114, %115, %116, %117, %118, %119, %120, %121, %122, %123, %124, %125, %126, %127, %128, %129}, "
    "a, b, 1, 1, 1, 0, 1;\n"
    "wgmma.commit_group.sync.aligned;\nselp.u32 %0, 1, 0, p;\nselp.u32 %1, 1, 0, q;\n}"
    : "=r"(ok.x), "=r"(ok.y), "+f"(d[0]), "+f"(d[1]), "+f"(d[2]), "+f"(d[3]), "+f"(d[4]), "+f"(d[5]), "+f"(d[6]), "+f"(d[7]), "+f"(d[8]), "+f"(d[9]), "+f"(d[10]), "+f"(d[11]), "+f"(d[12]), "+f"(d[13]), "+f"(d[14]), "+f"(d[15]), "+f"(d[16]), "+f"(d[17]), "+f"(d[18]), "+f"(d[19]), "+f"(d[20]), "+f"(d[21]), "+f"(d[22]), "+f"(d[23]), "+f"(d[24]), "+f"(d[25]), "+f"(d[26]), "+f"(d[27]), "+f"(d[28]), "+f"(d[29]), "+f"(d[30]), "+f"(d[31]), "+f"(d[32]), "+f"(d[33]), "+f"(d[34]), "+f"(d[35]), "+f"(d[36]), "+f"(d[37]), "+f"(d[38]), "+f"(d[39]), "+f"(d[40]), "+f"(d[41]), "+f"(d[42]), "+f"(d[43]), "+f"(d[44]), "+f"(d[45]), "+f"(d[46]), "+f"(d[47]), "+f"(d[48]), "+f"(d[49]), "+f"(d[50]), "+f"(d[51]), "+f"(d[52]), "+f"(d[53]), "+f"(d[54]), "+f"(d[55]), "+f"(d[56]), "+f"(d[57]), "+f"(d[58]), "+f"(d[59]), "+f"(d[60]), "+f"(d[61]), "+f"(d[62]), "+f"(d[63]), "+f"(d[64]), "+f"(d[65]), "+f"(d[66]), "+f"(d[67]), "+f"(d[68]), "+f"(d[69]), "+f"(d[70]), "+f"(d[71]), "+f"(d[72]), "+f"(d[73]), "+f"(d[74]), "+f"(d[75]), "+f"(d[76]), "+f"(d[77]), "+f"(d[78]), "+f"(d[79]), "+f"(d[80]), "+f"(d[81]), "+f"(d[82]), "+f"(d[83]), "+f"(d[84]), "+f"(d[85]), "+f"(d[86]), "+f"(d[87]), "+f"(d[88]), "+f"(d[89]), "+f"(d[90]), "+f"(d[91]), "+f"(d[92]), "+f"(d[93]), "+f"(d[94]), "+f"(d[95]), "+f"(d[96]), "+f"(d[97]), "+f"(d[98]), "+f"(d[99]), "+f"(d[100]), "+f"(d[101]), "+f"(d[102]), "+f"(d[103]), "+f"(d[104]), "+f"(d[105]), "+f"(d[106]), "+f"(d[107]), "+f"(d[108]), "+f"(d[109]), "+f"(d[110]), "+f"(d[111]), "+f"(d[112]), "+f"(d[113]), "+f"(d[114]), "+f"(d[115]), "+f"(d[116]), "+f"(d[117]), "+f"(d[118]), "+f"(d[119]), "+f"(d[120]), "+f"(d[121]), "+f"(d[122]), "+f"(d[123]), "+f"(d[124]), "+f"(d[125]), "+f"(d[126]), "+f"(d[127]), "+r"(db)
    : "r"(da), "r"(h0), "r"(h1), "r"(one), "r"(b0), "r"(p0), "r"(b1), "r"(p1) : "memory");
  return ok;
}
template <int S> __device__ __forceinline__ void wgmma_aug192(float (&d)[S], uint32_t a0, uint32_t a1, uint32_t db, uint32_t h1) {
  asm volatile("{\n.reg .b64 b;\n.reg .b32 z;\nmov.b32 z, 0;\n"
    "mov.b64 b, {%98, %99};\nwgmma.fence.sync.aligned;\n"
    "wgmma.mma_async.sync.aligned.m64n192k16.f32.bf16.bf16 "
    "{%0, %1, %2, %3, %4, %5, %6, %7, %8, %9, %10, %11, %12, %13, %14, %15, %16, %17, %18, %19, %20, %21, %22, %23, %24, %25, %26, %27, %28, %29, %30, %31, %32, %33, %34, %35, %36, %37, %38, %39, %40, %41, %42, %43, %44, %45, %46, %47, %48, %49, %50, %51, %52, %53, %54, %55, %56, %57, %58, %59, %60, %61, %62, %63, %64, %65, %66, %67, %68, %69, %70, %71, %72, %73, %74, %75, %76, %77, %78, %79, %80, %81, %82, %83, %84, %85, %86, %87, %88, %89, %90, %91, %92, %93, %94, %95}, "
    "{%96, %97, z, z}, b, 1, 1, 1, 1;\n"
    "wgmma.commit_group.sync.aligned;\n}"
    : "+f"(d[0]), "+f"(d[1]), "+f"(d[2]), "+f"(d[3]), "+f"(d[4]), "+f"(d[5]), "+f"(d[6]), "+f"(d[7]), "+f"(d[8]), "+f"(d[9]), "+f"(d[10]), "+f"(d[11]), "+f"(d[12]), "+f"(d[13]), "+f"(d[14]), "+f"(d[15]), "+f"(d[16]), "+f"(d[17]), "+f"(d[18]), "+f"(d[19]), "+f"(d[20]), "+f"(d[21]), "+f"(d[22]), "+f"(d[23]), "+f"(d[24]), "+f"(d[25]), "+f"(d[26]), "+f"(d[27]), "+f"(d[28]), "+f"(d[29]), "+f"(d[30]), "+f"(d[31]), "+f"(d[32]), "+f"(d[33]), "+f"(d[34]), "+f"(d[35]), "+f"(d[36]), "+f"(d[37]), "+f"(d[38]), "+f"(d[39]), "+f"(d[40]), "+f"(d[41]), "+f"(d[42]), "+f"(d[43]), "+f"(d[44]), "+f"(d[45]), "+f"(d[46]), "+f"(d[47]), "+f"(d[48]), "+f"(d[49]), "+f"(d[50]), "+f"(d[51]), "+f"(d[52]), "+f"(d[53]), "+f"(d[54]), "+f"(d[55]), "+f"(d[56]), "+f"(d[57]), "+f"(d[58]), "+f"(d[59]), "+f"(d[60]), "+f"(d[61]), "+f"(d[62]), "+f"(d[63]), "+f"(d[64]), "+f"(d[65]), "+f"(d[66]), "+f"(d[67]), "+f"(d[68]), "+f"(d[69]), "+f"(d[70]), "+f"(d[71]), "+f"(d[72]), "+f"(d[73]), "+f"(d[74]), "+f"(d[75]), "+f"(d[76]), "+f"(d[77]), "+f"(d[78]), "+f"(d[79]), "+f"(d[80]), "+f"(d[81]), "+f"(d[82]), "+f"(d[83]), "+f"(d[84]), "+f"(d[85]), "+f"(d[86]), "+f"(d[87]), "+f"(d[88]), "+f"(d[89]), "+f"(d[90]), "+f"(d[91]), "+f"(d[92]), "+f"(d[93]), "+f"(d[94]), "+f"(d[95])
    : "r"(a0), "r"(a1), "r"(db), "r"(h1) : "memory");
}
template <int S> __device__ __forceinline__ void wgmma_aug256(float (&d)[S], uint32_t a0, uint32_t a1, uint32_t db, uint32_t h1) {
  asm volatile("{\n.reg .b64 b;\n.reg .b32 z;\nmov.b32 z, 0;\n"
    "mov.b64 b, {%130, %131};\nwgmma.fence.sync.aligned;\n"
    "wgmma.mma_async.sync.aligned.m64n256k16.f32.bf16.bf16 "
    "{%0, %1, %2, %3, %4, %5, %6, %7, %8, %9, %10, %11, %12, %13, %14, %15, %16, %17, %18, %19, %20, %21, %22, %23, %24, %25, %26, %27, %28, %29, %30, %31, %32, %33, %34, %35, %36, %37, %38, %39, %40, %41, %42, %43, %44, %45, %46, %47, %48, %49, %50, %51, %52, %53, %54, %55, %56, %57, %58, %59, %60, %61, %62, %63, %64, %65, %66, %67, %68, %69, %70, %71, %72, %73, %74, %75, %76, %77, %78, %79, %80, %81, %82, %83, %84, %85, %86, %87, %88, %89, %90, %91, %92, %93, %94, %95, %96, %97, %98, %99, %100, %101, %102, %103, %104, %105, %106, %107, %108, %109, %110, %111, %112, %113, %114, %115, %116, %117, %118, %119, %120, %121, %122, %123, %124, %125, %126, %127}, "
    "{%128, %129, z, z}, b, 1, 1, 1, 1;\n"
    "wgmma.commit_group.sync.aligned;\n}"
    : "+f"(d[0]), "+f"(d[1]), "+f"(d[2]), "+f"(d[3]), "+f"(d[4]), "+f"(d[5]), "+f"(d[6]), "+f"(d[7]), "+f"(d[8]), "+f"(d[9]), "+f"(d[10]), "+f"(d[11]), "+f"(d[12]), "+f"(d[13]), "+f"(d[14]), "+f"(d[15]), "+f"(d[16]), "+f"(d[17]), "+f"(d[18]), "+f"(d[19]), "+f"(d[20]), "+f"(d[21]), "+f"(d[22]), "+f"(d[23]), "+f"(d[24]), "+f"(d[25]), "+f"(d[26]), "+f"(d[27]), "+f"(d[28]), "+f"(d[29]), "+f"(d[30]), "+f"(d[31]), "+f"(d[32]), "+f"(d[33]), "+f"(d[34]), "+f"(d[35]), "+f"(d[36]), "+f"(d[37]), "+f"(d[38]), "+f"(d[39]), "+f"(d[40]), "+f"(d[41]), "+f"(d[42]), "+f"(d[43]), "+f"(d[44]), "+f"(d[45]), "+f"(d[46]), "+f"(d[47]), "+f"(d[48]), "+f"(d[49]), "+f"(d[50]), "+f"(d[51]), "+f"(d[52]), "+f"(d[53]), "+f"(d[54]), "+f"(d[55]), "+f"(d[56]), "+f"(d[57]), "+f"(d[58]), "+f"(d[59]), "+f"(d[60]), "+f"(d[61]), "+f"(d[62]), "+f"(d[63]), "+f"(d[64]), "+f"(d[65]), "+f"(d[66]), "+f"(d[67]), "+f"(d[68]), "+f"(d[69]), "+f"(d[70]), "+f"(d[71]), "+f"(d[72]), "+f"(d[73]), "+f"(d[74]), "+f"(d[75]), "+f"(d[76]), "+f"(d[77]), "+f"(d[78]), "+f"(d[79]), "+f"(d[80]), "+f"(d[81]), "+f"(d[82]), "+f"(d[83]), "+f"(d[84]), "+f"(d[85]), "+f"(d[86]), "+f"(d[87]), "+f"(d[88]), "+f"(d[89]), "+f"(d[90]), "+f"(d[91]), "+f"(d[92]), "+f"(d[93]), "+f"(d[94]), "+f"(d[95]), "+f"(d[96]), "+f"(d[97]), "+f"(d[98]), "+f"(d[99]), "+f"(d[100]), "+f"(d[101]), "+f"(d[102]), "+f"(d[103]), "+f"(d[104]), "+f"(d[105]), "+f"(d[106]), "+f"(d[107]), "+f"(d[108]), "+f"(d[109]), "+f"(d[110]), "+f"(d[111]), "+f"(d[112]), "+f"(d[113]), "+f"(d[114]), "+f"(d[115]), "+f"(d[116]), "+f"(d[117]), "+f"(d[118]), "+f"(d[119]), "+f"(d[120]), "+f"(d[121]), "+f"(d[122]), "+f"(d[123]), "+f"(d[124]), "+f"(d[125]), "+f"(d[126]), "+f"(d[127])
    : "r"(a0), "r"(a1), "r"(db), "r"(h1) : "memory");
}

__device__ __forceinline__ uint32_t clock32() { uint32_t c; asm volatile("mov.u32 %0, %%clock;" : "=r"(c)); return c; }
__device__ __forceinline__ void spin_until(uint32_t c) {
  asm volatile("{\n.reg .pred p;\n.reg .s32 t;\nLAB_WAIT:\nmov.u32 t, %%clock;\nsub.s32 t, t, %0;\nsetp.lt.s32 p, t, 0;\n@p bra.uni LAB_WAIT;\n}" ::"r"(c) : "memory");
}
struct Nop { __device__ __forceinline__ void operator()(int) const {} };
template <int V> struct IC { static constexpr int v = V; };
struct Pipe {
  uint32_t db, g8, a8, pa, tph, aend, curB, curA, prevB, prevA, bo, so, sph, h0, h1, one;
  uint2 nx;
  int w; bool l0;
  __device__ __forceinline__ int lane() const { return LSO ? (so >> 5) & 31 : threadIdx.x & 31; }
  __device__ __forceinline__ void adv_a() { a8 += 8; pa += PA1; if (a8 == aend) a8 -= NA * 8; }
  __device__ __forceinline__ uint32_t take() { const uint32_t a = SB + OFF_A + a8 * 1024; adv_a(); return a; }
  __device__ __forceinline__ uint32_t ahead(int d) const { uint32_t ls = a8 + d * 8; if (ls >= aend) ls -= NA * 8; return SB + OFF_A + ls * 1024; }
  __device__ __forceinline__ uint32_t wait_ahead(int d) {
    uint32_t ls = a8 + d * 8;
    if (ls >= aend) ls -= NA * 8;
    mbar_spin31(SB + BAR_FULLA + ls, pa + d * PA1);
    return SB + OFF_A + ls * 1024;
  }
  template <int N, bool FIRST, int S> __device__ __forceinline__ uint2 iss(float (&acc)[S], bool skip) {
    const uint32_t da = DA0 + a8 * 64;
    if (!FIRST) { if (N != 192) db &= ~0x2000u; else if (db == DB0 + 15 * 512) db = DB0; }
    prevB = curB; prevA = curA;
    curB = g8 & 56; curA = a8;
    g8 += G1;
    a8 += skip ? 16 : 8; pa += skip ? 2 * PA1 : PA1;
    if (a8 >= aend) a8 -= NA * 8;
    const uint32_t fb = SB + BAR_FULLB + (g8 & 56), fa = SB + BAR_FULLA + a8;
    uint2 ok;
    if constexpr (N == 128) ok = FIRST ? wgmma_first128(acc, da, db, h0, h1, one, fb, g8, fa, pa) : wgmma_step128(acc, da, db, h0, h1, one, fb, g8, fa, pa);
    if constexpr (N == 192) ok = FIRST ? wgmma_first192(acc, da, db, h0, h1, one, fb, g8, fa, pa) : wgmma_step192(acc, da, db, h0, h1, one, fb, g8, fa, pa);
    if constexpr (N == 256) ok = FIRST ? wgmma_first256(acc, da, db, h0, h1, one, fb, g8, fa, pa) : wgmma_step256(acc, da, db, h0, h1, one, fb, g8, fa, pa);
    db += N * 8 - 384;
    return ok;
  }
  __device__ __forceinline__ void ensure(uint2 ok) {
    asm volatile(
        "{\n.reg .pred p, q;\n.reg .b64 s, t;\nmov.b64 s, {%1, %1};\nmov.b64 t, {%3, %3};\nsetp.ne.u32 p, %4, 0;\nsetp.ne.u32 q, %5, 0;\n@!p bra.uni LAB_WAIT;\n@q bra.uni DONE;\n"
        "LAB_WAIT:\nmbarrier.try_wait.shared::cta.b64 p, [%0], s;\nmbarrier.try_wait.shared::cta.b64 q, [%2], t;\n"
        "and.pred p, p, q;\n@!p bra.uni LAB_WAIT;\nDONE:\n}" ::"r"(SB + BAR_FULLB + (g8 & 56)), "r"(g8), "r"(SB + BAR_FULLA + a8), "r"(pa), "r"(ok.x), "r"(ok.y) : "memory");
  }
  template <class Hook> __device__ __forceinline__ void validate(bool check, const CUtensorMap* tm16, int c0, int c1, int wp, int j, Hook hook) {
    const uint32_t rows = SB + OFF_A + a8 * 1024 + wp * 2048, ad = a8 * 1024 + so;
    uint32_t v0 = 0, v1 = 0;
    asm volatile("{\n.reg .pred p;\nsetp.ne.u32 p, %3, 0;\n@p ld.shared.b32 %0, [%2];\n@p ld.shared.b32 %1, [%2 + 1024];\n}" : "+r"(v0), "+r"(v1) : "r"(ad), "r"((uint32_t)check));
    hook();
    while (__any_sync(~0u, max(v0, v1) == 0xffffffffu)) {
      const uint32_t bar = SB + BAR_SPEC + (w * 4 + wp) * 8;
      e_load<2048>(rows, tm16, c0 + sched_k(c_sched.v[j][(g8 >> 3) & 511]), c1 + wp * 16, bar);
      mbar_spin(bar, sph);
      sph ^= 1;
      v0 = lds32(ad); v1 = lds32(ad + 1024);
    }
  }
  __device__ __forceinline__ void fence() const { asm volatile("{\n.reg .pred p;\nsetp.eq.u32 p, %0, 2;\nLAB:\n@p pmevent 6;\n@p bra.uni LAB;\n}" ::"r"(one) : "memory"); }
  __device__ __forceinline__ void drain() {
    wg_wait<0>();
    arrive_2(SB + BAR_EMPTYB + curB, SB + BAR_EMPTYA + curA, l0);
    curB = BAR_DUMMY - BAR_EMPTYB; curA = BAR_DUMMY - BAR_EMPTYA;
  }
  __device__ __forceinline__ void signal_server(uint32_t odd) { __syncwarp(); arrive_n(SB + BAR_SRV + w * 16 + odd * 8, l0); }
  __device__ __forceinline__ void signal_loader() { __syncwarp(); arrive_n(SB + BAR_STG + w * 8, l0); }
  template <int N, bool HOLD = false, int S, class Pre = Nop> __device__ __forceinline__ void begin(float (&acc)[S], uint32_t p0, int proft, Pre pre = Pre()) {
    db = DB0 + p0 * 512;
    const uint32_t c1 = HOLD ? clock32() : 0;
    ensure(nx);
    if (HOLD) spin_until(c1 + lds32(SB + OFF_HOLD + w * 4));
    pre(0);
    PROF_T(w, proft, 0);
    ensure(iss<N, true>(acc, false));
  }
  template <int N, bool ENSURE = true, int S, class Hook> __device__ __forceinline__ void run(float (&acc)[S], int i0, int i1, uint32_t skips, int pause, Hook hook) {
    int i = i0;
    const int ev = w ? pause : -1;
#pragma unroll 1
    while (true) {
      const uint2 ok = iss<N, false>(acc, (skips >> i) & 1);
      wg_wait<1>();
      arrive_2(SB + BAR_EMPTYB + prevB, SB + BAR_EMPTYA + prevA, l0);
      if (pause >= 0 && i + 1 == i1) { nx = ok; break; }
      if constexpr (ENSURE) { ensure(ok); hook(i); } else hook(i, ok);
      i++;
      if (pause < 0 && i == i1) break;
      if (pause > 0 && i == ev) { drain(); mbar_spin(SB + BAR_LEAD, tph); }
    }
  }
  template <int N, bool AUG, int S> __device__ __forceinline__ void end(float (&acc)[S], int ns, uint32_t pos, uint32_t au0, uint32_t au1, int proft) {
    uint32_t augB = 0;
    arrive_n(SB + BAR_LEAD + w * (BAR_DUMMY - BAR_LEAD), l0);
    if constexpr (AUG) {
      asm volatile("{\n.reg .pred p;\n.reg .b64 s;\nmov.b64 s, {%1, %1};\nsetp.ne.u32 p, %2, 0;\n@p bra.uni DONE;\nLAB_WAIT:\nmbarrier.try_wait.shared::cta.b64 p, [%0], s;\n@!p bra.uni LAB_WAIT;\nDONE:\n}"
                     ::"r"(SB + BAR_FULLB + (g8 & 56)), "r"(g8), "r"(nx.x) : "memory");
      const uint32_t dc = (((SB + OFF_B) >> 4) | (64u << 16)) + pos * 512;
      if constexpr (N == 192) wgmma_aug192(acc, au0, au1, dc, h1); else wgmma_aug256(acc, au0, au1, dc, h1);
      augB = g8 & 56; g8 += G1;
    }
    tph ^= 1;
    if (ns > 0) wait_ahead(ns - 1);
    nx = make_uint2(mbar_test(SB + BAR_FULLB + (g8 & 56), g8 >> 31), AUG ? mbar_test(SB + BAR_FULLA + a8, pa >> 31) : 1);
    wg_wait<0>();
    arrive_2(SB + BAR_EMPTYB + curB, SB + BAR_EMPTYA + curA, l0);
    if (AUG) arrive_n(SB + BAR_EMPTYB + augB, l0);
    PROF_T(w, proft, 1);
  }
};

__device__ __forceinline__ uint32_t box_addr(uint32_t buf, uint32_t bo, int u) { return (buf + bo) ^ (u * 32); }

__device__ __forceinline__ float bf_round(float x) { return __bfloat162float(__float2bfloat16_rn(x)); }
__device__ __forceinline__ void own_rstd(int w, int wp, int lane, float (&rstd)[2]) {
#pragma unroll
  for (int hh = 0; hh < 2; hh++) rstd[hh] = __uint_as_float(lds32(SB + OFF_RSTD + (w * 72 + 8 + wp * 16 + (lane >> 2) + hh * 8) * 4));
}
__device__ __forceinline__ void stats_fetch(int w, int wp, int lane, uint32_t (&au)[2]) {
  const int g = lane >> 2, q4 = lane & 3;
  float rstd[2];
  own_rstd(w, wp, lane, rstd);
#pragma unroll
  for (int hh = 0; hh < 2; hh++) {
    const float m = __uint_as_float(lds32(SB + OFF_MEAN + (w * 64 + wp * 16 + g + hh * 8) * 4));
    const float v = q4 == 3 ? rcp(rstd[hh]) : -m;
    const float v1 = bf_round(v), v2 = bf_round(v - v1);
    const float p = q4 == 1 ? v2 : (q4 == 2 ? v - v1 - v2 : v1);
    au[hh] = pack_bf16(p, q4 == 3 ? v2 : p);
  }
}

__device__ __forceinline__ void halo_fetch(uint32_t slot, int w, const uint4* src, uint32_t bar) {
  asm volatile("{\n.reg .pred p;\nelect.sync _|p, 0xffffffff;\n@p mbarrier.arrive.expect_tx.shared::cta.b64 _, [%4], 2080;\n"
               "@p cp.async.bulk.shared::cluster.global.mbarrier::complete_tx::bytes [%0], [%2], 2048, [%4];\n"
               "@p cp.async.bulk.shared::cluster.global.mbarrier::complete_tx::bytes [%1], [%3], 32, [%4];\n}"
               ::"r"(slot), "r"(SB + OFF_RSTD + w * 288), "l"(src), "l"(src + 128), "r"(bar) : "memory");
}
struct Attn {
  uint32_t lo[24], hi[24], ha[16], hslot;
  float c[8][4], rstd[2];
  float2 rk[3];
  __device__ __forceinline__ void A(const float (&acc)[96], Pipe& M, int w, int wp, int r, uint4* halo_out) {
    const int lane = M.lane();
    M.signal_loader();
    auto cvt = [&](uint32_t& d, int u) { asm volatile("cvt.rn.bf16x2.f32 %0, %1, %2;" : "=r"(d) : "f"(acc[u + 1]), "f"(acc[u])); };
    auto rest = [&] {
#pragma unroll
      for (int nb = 23; nb >= 0; nb--) {
        cvt(lo[nb], 4 * nb);
        if (nb < 8) cvt(hi[nb], 4 * nb + 2);
        if (nb >= 16) lo[nb] = movm(lo[nb]);
      }
    };
#pragma unroll
    for (int nb = 8; nb < 24; nb++) hi[nb] = pack_bf16(acc[4 * nb + 2], acc[4 * nb + 3]);
    hslot = M.ahead(3);
    const uint32_t hbuf = hslot + wp * 2048 + lane * 16;
#pragma unroll
    for (int nb = 16; nb < 24; nb++) hi[nb] = movm(hi[nb]);
    if (wp == 3) {
      if (r < 15) {
#pragma unroll
        for (int p = 0; p < 4; p++) halo_out[p * 32 + lane] = make_uint4(hi[8 + 4 * p] ? hi[8 + 4 * p] : 0x8000u, hi[9 + 4 * p], hi[10 + 4 * p], hi[11 + 4 * p]);
        const uint32_t rh = lds32(SB + OFF_RSTD + (w * 72 + 64 + (lane & 7)) * 4);
        if (lane < 8) reinterpret_cast<uint32_t*>(halo_out + 128)[lane] = rh ? rh : 0x80000000u;
      }
    } else {
#pragma unroll
      for (int p = 0; p < 4; p++)
        asm volatile("st.shared.v4.b32 [%0], {%1,%2,%3,%4};" ::"r"(hbuf + 2048 + p * 512), "r"(hi[8 + 4 * p]), "r"(hi[9 + 4 * p]), "r"(hi[10 + 4 * p]), "r"(hi[11 + 4 * p]) : "memory");
      __syncwarp();
      arrive_n(SB + BAR_HALO + w * 8, M.l0);
    }
    rest();
  }
  __device__ __forceinline__ void B(int w, int wp, int lane, uint32_t hph) {
    own_rstd(w, wp, lane, rstd);
    mbar_spin(SB + BAR_HALO + w * 8, hph);
#pragma unroll
    for (int p = 0; p < 4; p++)
      asm volatile("ld.shared.v4.b32 {%0,%1,%2,%3}, [%4];" : "=r"(ha[4 * p]), "=r"(ha[4 * p + 1]), "=r"(ha[4 * p + 2]), "=r"(ha[4 * p + 3]) : "r"(hslot + wp * 2048 + lane * 16 + p * 512) : "memory");
#pragma unroll
    for (int u = 0; u < 3; u++) rk[u] = lds64(SB + OFF_RSTD + (w * 72 + wp * 16 + u * 8 + 2 * (lane & 3)) * 4);
  }
  template <class F> __device__ __forceinline__ void C(int wp, int r, int lane, uint32_t zero, F last) {
    const int g = lane >> 2, q = lane & 3;
    const bool nohalo = (wp == 0) && (r == 0);
    const bool up0 = 2 * q > g, up1 = 2 * q + 1 > g;
    const float sc = 0.17677669529663687f * 1.4426950408889634f;
    const float kx0 = up0 ? rk[0].x : rk[1].x, kx1 = up1 ? rk[0].y : rk[1].y;
    const float ky0 = up0 ? rk[1].x : rk[2].x, ky1 = up1 ? rk[1].y : rk[2].y;
    const float fx = rstd[0] * sc, fy = rstd[1] * sc;
    float sm[2][4] = {}, s0[2][4] = {}, s1[2][4] = {};
#pragma unroll
    for (int ks = 0; ks < 2; ks++)
#pragma unroll
      for (int h = 0; h < 2; h++) {
        const int a = 4 * h + 2 * ks;
        mma16(s0[h], lo[a], hi[a], lo[a + 1], hi[a + 1], lo[8 + a], lo[9 + a]);
        mma16(s1[h], lo[a], hi[a], lo[a + 1], hi[a + 1], hi[8 + a], hi[9 + a]);
      }
#pragma unroll
    for (int u = 0; u < 4; u++) { const int a = 4 * (u & 1) + (u & 2); mma16(sm[u & 1], lo[a], hi[a], lo[a + 1], hi[a + 1], ha[a], ha[a + 1]); }
    uint32_t pf[2][4];
    const uint32_t um = (up0 ? 0xffffu : 0u) | (up1 ? 0xffff0000u : 0u);
#pragma unroll
    for (int h = 0; h < 2; h++) {
      if (nohalo) { sm[h][0] = -INFINITY; sm[h][1] = -INFINITY; }
      float x0 = (up0 ? sm[h][0] : s0[h][0]) * (kx0 * fx), x1 = (up1 ? sm[h][1] : s0[h][1]) * (kx1 * fx);
      float y0 = (up0 ? s0[h][2] : s1[h][2]) * (ky0 * fy), y1 = (up1 ? s0[h][3] : s1[h][3]) * (ky1 * fy);
      float mx = fmaxf(x0, x1), my = fmaxf(y0, y1);
      mx = fmaxf(mx, __shfl_xor_sync(~0u, mx, 1)); my = fmaxf(my, __shfl_xor_sync(~0u, my, 1));
      mx = fmaxf(mx, __shfl_xor_sync(~0u, mx, 2)); my = fmaxf(my, __shfl_xor_sync(~0u, my, 2));
      x0 = ex2(x0 - mx); x1 = ex2(x1 - mx); y0 = ex2(y0 - my); y1 = ex2(y1 - my);
      float sx = x0 + x1, sy = y0 + y1;
      x0 *= kx0; x1 *= kx1; y0 *= ky0; y1 *= ky1;
      sx += __shfl_xor_sync(~0u, sx, 1); sy += __shfl_xor_sync(~0u, sy, 1);
      sx += __shfl_xor_sync(~0u, sx, 2); sy += __shfl_xor_sync(~0u, sy, 2);
      sx = rcp(sx); sy = rcp(sy);
      x0 *= sx; x1 *= sx; y0 *= sy; y1 *= sy;
      const uint32_t px = pack_bf16(x0, x1), py = pack_bf16(y0, y1);
      pf[h][0] = px & um; pf[h][1] = px & ~um; pf[h][2] = py & um; pf[h][3] = py & ~um;
    }
#pragma unroll
    for (int u = 0; u < 4; u++) {
#pragma unroll
      for (int e = 0; e < 4; e++) { c[2 * u][e] = 0.f; c[2 * u + 1][e] = 0.f; }
      mma8(c[2 * u], ha[8 + 2 * u], ha[9 + 2 * u], pf[u >> 1][0]);
      mma8(c[2 * u + 1], lo[16 + 2 * u], lo[17 + 2 * u], pf[u >> 1][2]);
    }
#pragma unroll
    for (int u = 0; u < 4; u++) {
      mma8(c[2 * u], lo[16 + 2 * u], lo[17 + 2 * u], pf[u >> 1][1]);
      mma8(c[2 * u + 1], hi[16 + 2 * u], hi[17 + 2 * u], pf[u >> 1][3]);
    }
    uint32_t dep = 0;
    last();
#pragma unroll
    for (int u = 0; u < (EFIRST == 3 ? 0 : 8); u++) dep |= __float_as_uint(c[u][0]);
    asm volatile("bar.sync %0, 256;" ::"r"(3 + (dep & zero)) : "memory");
  }
  __device__ __forceinline__ void E(Pipe& M, bool urgent) {
#pragma unroll
    for (int u = 0; u < 4; u++)
      asm volatile("stmatrix.sync.aligned.m8n8.x4.trans.shared.b16 [%0], {%1, %2, %3, %4};" ::"r"(box_addr(hslot, M.bo, u)),
                   "r"(pack_bf16(c[2 * u][0], c[2 * u][1])), "r"(pack_bf16(c[2 * u + 1][0], c[2 * u + 1][1])),
                   "r"(pack_bf16(c[2 * u][2], c[2 * u][3])), "r"(pack_bf16(c[2 * u + 1][2], c[2 * u + 1][3])) : "memory");
    __syncwarp();
    arrive_n(SB + (urgent ? BAR_STG + M.w * 8 : BAR_SRV + M.w * 16 + 8), M.l0);
  }
};

__device__ __forceinline__ void epi_res(const float (&acc)[64], const float (&pre)[64], float sc0, float sc1, uint32_t (&xr)[32], Pipe& M, int wp) {
  Pipe T = M;
  const uint32_t buf0 = T.take(), buf1 = T.take();
#pragma unroll
  for (int u = 0; u < 8; u++) {
#pragma unroll
    for (int nb = 2 * u; nb < 2 * u + 2; nb++) {
      xr[2 * nb] = pack_bf16(fmaf(acc[4 * nb], sc0, pre[2 * nb]), fmaf(acc[4 * nb + 1], sc0, pre[32 + 2 * nb]));
      xr[2 * nb + 1] = pack_bf16(fmaf(acc[4 * nb + 2], sc1, pre[2 * nb + 1]), fmaf(acc[4 * nb + 3], sc1, pre[33 + 2 * nb]));
    }
    stsm4(box_addr(u < 4 ? buf0 : buf1, M.bo, u & 3), xr[4 * u], xr[4 * u + 1], xr[4 * u + 2], xr[4 * u + 3]);
    if (u == 3) { M.signal_loader(); M.fence(); }
  }
  __syncwarp();
  arrive_n(SB + BAR_STG2 + M.w * 8, M.l0);
  fence_async_smem();
  wg_bar(M.w);
}
__device__ __forceinline__ void presum(float (&pre)[64], const uint32_t (&xr)[32], int lane, float usebias) {
  const uint32_t bias = SB + OFF_VEC + (lane & 3) * 8;
#pragma unroll
  for (int nb = 0; nb < 16; nb++) {
    const float2 b = lds64(bias + nb * 32);
#pragma unroll
    for (int u = 2 * nb; u < 2 * nb + 2; u++) {
      pre[32 + u] = fmaf(b.y, usebias, bf_hi(xr[u])); pre[u] = fmaf(b.x, usebias, bf_lo(xr[u]));
      asm volatile("" : "+f"(pre[u]), "+f"(pre[32 + u]));
    }
  }
}
template <int U0, int U1, int S, int Q> __device__ __forceinline__ void pack_relu(uint32_t (&o)[Q], const float (&acc)[S]) {
#pragma unroll
  for (int u = U0; u < U1; u++) asm volatile("cvt.rn.relu.bf16x2.f32 %0, %1, %2;" : "=r"(o[u]) : "f"(acc[2 * u + 1]), "f"(acc[2 * u]));
}
__device__ __forceinline__ uint32_t sq_bf16x2(uint32_t a) { uint32_t d; asm("mul.rn.bf16x2 %0, %1, %1;" : "=r"(d) : "r"(a)); return d; }
template <int Q> __device__ __forceinline__ void ffn_stage(const uint32_t (&o)[Q], int i, Pipe& M) {
  i -= M.w;
  if (i == 1 || i == 4 || i == 7 || (Q == 64 && i == 10)) {
    const uint32_t buf = M.wait_ahead(2 - M.w);
#pragma unroll
    for (int b = 0; b < Q / 16; b++)
      if (i == 3 * b + 1) {
#pragma unroll
        for (int u = 4 * b; u < 4 * b + 4; u++)
          stsm4(box_addr(buf, M.bo, u & 3), sq_bf16x2(o[4 * u]), sq_bf16x2(o[4 * u + 1]), sq_bf16x2(o[4 * u + 2]), sq_bf16x2(o[4 * u + 3]));
      }
    M.signal_server((i & 1) ^ (Q == 64));
  }
}

__device__ __forceinline__ void wait_flags(const uint8_t* f, uint32_t tag, int lane) {
  const uint32_t t4 = (tag & 0xff) * 0x01010101u;
  const uint32_t* fp = reinterpret_cast<const uint32_t*>(f) + (lane & (FG / 4 - 1));
  while (__any_sync(~0u, __vsub4(ld_relaxed(fp), t4) & 0x80808080u)) {}
  asm volatile("fence.acquire.gpu;\nfence.proxy.async.global;" ::: "memory");
}
__device__ __forceinline__ uint32_t get_epoch() { mbar_spin(SB + BAR_EPOCH, 0); return __shfl_sync(~0u, lds32(SB + OFF_HOLD + 8), 0); }
__device__ __forceinline__ void aloader(const Params& P, const Ptrs& Q, int bid, int r, int j, int lane, int w, uint32_t e, uint32_t epoch) {
  const uint32_t abase = SB + OFF_A + w * NA * 8192, fbase = SB + BAR_FULLA + w * NA * 8, ebase = SB + BAR_EMPTYA + w * NA * 8;
  uint32_t slot = NPRO, ph = 1, nst = 0, hph = 0, npace = 0;
  int t = -1, kind = -1, a0 = 0, a1 = 0;
  const CUtensorMap* tmA = nullptr;
  uint64_t pol = 0;
  uint4* hin = Q.s->halo[0][0] + (r * 16 + j * 2 + w - 16) * 136;
  uint32_t* const pace = Q.s->pace[0] + (bid & -PG) * 4;
  const uint8_t* const flags = Q.s->flags[r / (FG / 8)][w];
  auto adv = [&] { if (++slot == NA) { slot = 0; ph ^= 1; } };
#pragma unroll 1
  for (int g = NPRO; g <= NSTEP; g++) {
    const uint32_t cur = e;
    e = c_sched.v[j][g + 1];
    if (!(cur & E_RARE)) {
      if (cur & E_HAND) { mbar_spin(ebase + slot * 8, ph); e_arrive(fbase + slot * 8, 1); adv(); }
    } else {
      if (cur & F_NEW) {
        t++; kind = kind == 5 ? 0 : kind + 1;
        const bool narrow = kind == 2 || kind == 5;
        static_assert(TM_XIN == 0 && TM_X == 1 && TM_XA == 2 && TM_O == 3 && TM_H == 4, "map order");
        tmA = &P.tm[t < 2 ? 0 : (0x422311 >> (4 * kind)) & 15];
        pol = ((AEF >> t) & 1) ? 0x12F0000000000000ull : 0x1000000000000000ull;
        a0 = narrow ? 0 : w * 1024; a1 = narrow ? r * 128 + w * 64 : r * 64;
      }
      const bool xo = cur & E_XPUB0;
      uint32_t s = slot;
      if (cur & (E_HAND | E_ATTN | E_XPUB0)) {
        if (cur & E_KEEP) e_arrive(ebase + slot * 8, 4);
#pragma unroll 1
        for (int u = xo ? 0 : 1; u < 2; u++) { mbar_wait(ebase + slot * 8, ph); e_arrive(fbase + slot * 8, 1); adv(); }
      }
      uint32_t hold = 0;
      int lag = 0;
      if ((xo && t < 12) || (cur & F_GATH)) {
        uint32_t v;
        uint32_t v1;
        do asm volatile("ld.relaxed.gpu.global.v2.u32 {%0, %1}, [%2];" : "=r"(v), "=r"(v1) : "l"(pace + npace + (lane & (PG - 1)) * 2) : "memory");
        while (__any_sync(~0u, ((v ^ (epoch * 16 + t - 1)) | (v ^ v1)) & 31));
        v += v1;
        npace ^= PG * 2;
        lag = min((int)(v - __shfl_sync(~0u, v, bid & (PG - 1))), 8000) * 27 >> 5;
        hold = __reduce_max_sync(~0u, lag);
        asm volatile("st.shared.b32 [%0], %1;" ::"r"(SB + OFF_HOLD + w * 4), "r"(hold) : "memory");
      }
      if (cur & (E_ATTN | E_XPUB0)) {
        const uint32_t s2 = s == NA - 1 ? 0 : s + 1;
        mbar_wait(SB + BAR_STG + w * 8, nst & 1);
        nst++;
        LT(0);
        const uint32_t c1 = clock32();
        e_store(tmA, a0 + sched_k(cur), a1, abase + s * 8192);
        if (xo) {
          mbar_spin(SB + BAR_STG2 + w * 8, ~t & 1);
          e_store(tmA, a0 + sched_k(cur) + 64, a1, abase + s2 * 8192);
          if (t == 12) break;
        } else e_arrive(SB + BAR_OWN + w * 8, 1);
        LT(1);
        spin_until(c1 + hold + (xo ? SDELAY : SDELAYO));
        LT(2);
        LT(5);
      }
      if (cur & E_SIG) {
        e_arrive(SB + BAR_SRV + w * 16, 4);
      }
      if (cur & E_REL) bulk_wait_all();
      if (cur & E_HALO) {
        mbar_spin(SB + BAR_STG + w * 8, nst & 1);
        nst++;
        const uint32_t hs = abase + (slot >= 3 ? slot - 3 : slot + 3) * 8192, ad = hs + lane * 32 + (lane & 4) * 4;
        if (r == 0) {
#pragma unroll
          for (int p = 0; p < 4; p++) sts128(hs + lane * 16 + p * 512, 0, 0, 0, 0);
          asm volatile("st.shared.b32 [%0], %1;" ::"r"(SB + OFF_RSTD + w * 288 + (lane & 7) * 4), "r"(0x3f800000) : "memory");
        } else {
          spin_until(clock32() + HDELAY);
          do {
            halo_fetch(hs, w, hin, SB + BAR_SPEC + 80 + w * 8);
            mbar_spin(SB + BAR_SPEC + 80 + w * 8, hph);
            hph ^= 1;
          } while (__any_sync(~0u, min(min(lds32(ad), lds32(ad + 1024)), lds32(SB + OFF_RSTD + w * 288)) == 0));
        }
        e_arrive(SB + BAR_HALO + w * 8, 1);
      }
      if ((cur & E_REL) && (kind == 1 || kind == 2) && r > 0) {
        uint4* hz = hin + lane;
        hin += 256 * 136;
#pragma unroll
        for (int p = 0; p < 4; p++) hz[p * 32] = make_uint4(0, 0, 0, 0);
        if (lane < 2) hz[128] = make_uint4(0, 0, 0, 0);
      }
      if (cur & E_WAIT) {
        wait_flags(flags + ((cur & E_PART1) ? FG : 0), epoch * 16 + t, lane);
      }
    }
    if (!(cur & (F_AUG | F_NOA))) {
      mbar_wait(ebase + slot * 8, ph);
      e_load(abase + slot * 8192, tmA, a0 + sched_k(cur), a1, fbase + slot * 8, pol);
      adv();
      if (cur & F_STAMP) {
        uint32_t stamp;
        asm volatile("mov.u32 %0, %%globaltimer_lo;" : "=r"(stamp));
        asm volatile("st.relaxed.gpu.global.u32 [%0], %1;" ::"l"(pace + npace + (bid & (PG - 1)) * 2 + w), "r"((stamp & ~31u) | ((epoch * 16 + t) & 31)) : "memory");
      }
    }
  }
  bulk_wait_all();
}

__device__ __forceinline__ void bloader(const Params& P, const Ptrs& Q, bool aux, int j, int lane, uint32_t e, uint32_t epoch) {
  const uint32_t* const sched = c_sched.v[aux ? 8 : j];
  int kind = -1, c2 = 0, c3 = 0, na = 0;
  const CUtensorMap* tmB = nullptr;
  uint32_t sph = 0, efm = aux ? 0 : BEF * 2;
  uint64_t pol = 0;
#pragma unroll 1
  for (int g = aux ? 8 + (j & 1) : NPRO; g < (aux ? NSTEP_AUX : NSTEP); g += 1 + aux) {
    const uint32_t cur = e;
    e = sched[g + 1 + aux];
    if (cur & F_NEW) {
      kind = kind == 5 ? 0 : kind + ((cur >> 29) & 3);
      static_assert(TM_WQKV == 5 && TM_WO == 6 && TM_W1A == 7 && TM_W1B == 8 && TM_W2 == 9, "map order");
      tmB = &P.tm[(0x978655 >> (4 * kind)) & 15];
      efm >>= 1;
      pol = (efm & 1) ? 0x12F0000000000000ull : 0x1000000000000000ull;
      na = (0x243233 >> (4 * kind)) & 15;
      c2 = ((0x277200 >> (4 * kind)) & 15) * j + (kind == 4 ? 3 : 0);
      c3 = kind <= 1 ? kind * 8 + j : 0;
    }
    const int need = g - (int)((cur >> 5) & 15);
    const uint32_t dst = SB + OFF_B + (cur & 31) * 8192, bar = SB + BAR_FULLB + (g & 7) * 8;
    mbar_wait(SB + BAR_EMPTYB + (need & 7) * 8, (need >> 3) & 1);
    if (!(cur & F_AUG)) {
      asm volatile("{\n.reg .pred p;\nelect.sync _|p, 0xffffffff;\n@p mbarrier.arrive.expect_tx.shared::cta.b64 _, [%2], %7;\n"
                   "@p cp.async.bulk.tensor.4d.shared::cluster.global.mbarrier::complete_tx::bytes.L2::cache_hint [%0], [%1, {%3, %4, %5, %6}], [%2], %8;\n}"
                   ::"r"(dst), "l"(tmB), "r"(bar), "r"(0), "r"(sched_k(cur)), "r"(c2), "r"(c3), "r"(na * 8192), "l"(pol) : "memory");
    } else {
      const bool chk = g < NSTEP / 2;
      const uint32_t b2 = chk ? SB + BAR_AUG : bar, ad = dst + lane * 16 + (lane >> 3) * 4;
      while (true) {
        asm volatile("{\n.reg .pred p;\nelect.sync _|p, 0xffffffff;\n@p mbarrier.arrive.expect_tx.shared::cta.b64 _, [%2], 4096;\n"
                     "@p cp.async.bulk.shared::cluster.global.mbarrier::complete_tx::bytes [%0], [%1], 4096, [%2];\n}"
                     ::"r"(dst), "l"(Q.s->aug[epoch & 1][(kind - (kind >= 3)) * 8 + j]), "r"(b2) : "memory");
        if (!chk) break;
        mbar_spin(b2, sph);
        sph ^= 1;
        uint32_t mn = ~0u;
#pragma unroll
        for (int u = 0; u < 8; u++) mn = min(mn, lds32(ad + u * 512));
        if (!__any_sync(~0u, mn == 0)) { e_arrive(bar, 1); break; }
      }
      __syncwarp();
    }
  }
}

constexpr uint32_t job_slots(int layer) {
  const int pos[10] = {11, 26, 63, 73, 77, 81, 92, 96, 100, 104};
  uint32_t v = 0;
  for (int m = 0; m < 10; m++) v |= (uint32_t)((layer * 148 + pos[m]) % NA) << (3 * m);
  return v;
}
constexpr uint32_t JOB_SLOTS0 = job_slots(0), JOB_SLOTS1 = job_slots(1);
__device__ __forceinline__ void server(const Params& P, const Ptrs& Q, int bid, int r, int j, int lane, uint32_t epoch) {
  if (CPF) spin_until(clock32() + CPF);
  epoch += __shfl_sync(~0u, c_sched.v[j][lane < 18 ? lane * 16 : 0] >> 31, 0);
  {
    const uint2 b = reinterpret_cast<const uint2*>(Q.b2 + j * 128)[lane];
    sts128(SB + OFF_VEC + lane * 16, b.x << 16, b.x & 0xffff0000u, b.y << 16, b.y & 0xffff0000u);
  }
  int hl = 0;
  uint32_t fph = 0, pend = SB + BAR_DUMMY3;
#pragma unroll 1
  for (int n = 0; n < 20; n++) {
    const int layer = n >= 10, m = n - 10 * layer;
    const bool stat = m == 0 || m == 2;
    const uint32_t slot = ((layer ? JOB_SLOTS1 : JOB_SLOTS0) >> (m * 3)) & 7;
    auto fetch = [&](int w) {
      asm volatile("{\n.reg .pred p;\nelect.sync _|p, 0xffffffff;\n@p mbarrier.arrive.expect_tx.shared::cta.b64 _, [%2], 4096;\n"
                   "@p cp.async.bulk.shared::cluster.global.mbarrier::complete_tx::bytes [%0], [%1], 4096, [%2];\n}"
                   ::"r"(SB + OFF_A + (w * NA + slot) * 8192), "l"(&Q.s->stats[hl][r * 32 + w * 16][0][0]), "r"(SB + BAR_SPEC + 64 + w * 8) : "memory");
    };
#pragma unroll 1
    for (int w = 0; w < 2; w++) {
      mbar_spin(SB + BAR_SRV + w * 16 + (n & 1) * 8, (n >> 1) & 1);
      if (stat) fetch(w);
      else {
        e_store(&P.tm[m == 1 ? TM_O : TM_H], m == 1 ? j * 64 : 448 * j + (m - 3) * 64, r * 128 + w * 64, SB + OFF_A + (w * NA + slot) * 8192);
        bulk_wait_read<1>();
        e_arrive(pend, 4);
        pend = SB + BAR_EMPTYA + (w * NA + slot) * 8;
      }
    }
    if (stat) {
#pragma unroll 1
      for (int w = 0; w < 2; w++) {
        const uint32_t src = SB + OFF_A + (w * NA + slot) * 8192 + (lane >> 1) * 256 + ((lane >> 1) & 7) * 32 + (lane & 1) * 16;
        float ms[2], md[2], mq[2], m0[2];
        while (true) {
          mbar_spin(SB + BAR_SPEC + 64 + w * 8, (fph >> w) & 1);
          fph ^= 1u << w;
          uint32_t bad = 0;
          ms[0] = ms[1] = md[0] = md[1] = mq[0] = mq[1] = m0[0] = m0[1] = 0.f;
#pragma unroll 1
          for (int p = 0; p < 8; p += 2) {
            const float4 v2[2] = {lds128(src ^ (p * 32)), lds128(src ^ (p * 32) ^ 32)};
            if (p == 0) { m0[0] = v2[0].x; m0[1] = v2[0].z; }
#pragma unroll
            for (int z = 0; z < 2; z++) {
              const float4 v = v2[z];
              const float a = v.x - m0[0], b = v.z - m0[1];
              bad |= __float_as_uint(v.y) ^ epoch;
              ms[0] += a; md[0] = fmaf(a, a, md[0]); mq[0] += __uint_as_float(__float_as_uint(v.y) & ~63u);
              ms[1] += b; md[1] = fmaf(b, b, md[1]); mq[1] += v.w;
            }
          }
          if (!__any_sync(~0u, bad & 63)) break;
          fetch(w);
          __syncwarp();
        }
        e_arrive(SB + BAR_EMPTYA + (w * NA + slot) * 8, 4);
        const int row = (lane >> 3) * 16 + (lane & 7);
#pragma unroll
        for (int z = 0; z < 2; z++) {
          const float d = ms[z] * 0.125f;
          asm volatile("st.shared.f32 [%0], %1;" ::"r"(SB + OFF_MEAN + (w * 64 + row + z * 8) * 4), "f"(m0[z] + d) : "memory");
          const float rs = rsq(fmaf(mq[z], 1.f / 1024.f, fmaxf(fmaf(md[z], 0.125f, -d * d), 0.f)) + 1e-5f);
          asm volatile("st.shared.f32 [%0], %1;" ::"r"(SB + OFF_RSTD + (w * 72 + 8 + row + z * 8) * 4), "f"(rs) : "memory");
        }
        e_arrive(SB + BAR_STAT + w * 8, 8);
      }
    }
    if (stat && n != 12) {
#pragma unroll 1
      for (int u = 0; u < (m ? 2 : 3); u++) {
        const uint32_t pitch = u == 2 ? 448 : 128;
        uint4* p = reinterpret_cast<uint4*>(u == 2 ? Q.s->h : (m ? Q.out : Q.s->x)) + (u == 2 ? 64 + j * 8 : j * 16 + u * 8) + ((r * 128 + (lane >> 3)) * pitch + (lane & 7));
#pragma unroll 1
        for (int k = 0; k < 32 / FUN; k++) {
#pragma unroll
          for (int z = 0; z < FUN; z++) {
            *p = make_uint4(~0u, ~0u, ~0u, ~0u);
            p += 4 * pitch;
            asm volatile("" : "+l"(p));
          }
        }
      }
      __syncwarp();
    }
    if ((0x222 >> m) & 1) {
      bulk_wait_all();
      e_arrive(pend, 4);
      pend = SB + BAR_DUMMY3;
      if (lane < 2) st_release8(&Q.s->flags[r / (FG / 8)][lane][(r & (FG / 8 - 1)) * 8 + j + (m == 9 ? FG : 0)], epoch * 16 + layer * 6 + (m == 1 ? 2 : 5));
      __syncwarp();
    }
    hl += stat;
  }
}

__device__ __forceinline__ void aux_math(const Ptrs& Q, int bid, int jj, int warp, int lane) {
  const int g = lane >> 2, q = lane & 3, c0 = (warp & 3) * 2;
  uint32_t st = warp >> 2, bf[16][4] = {};
  const uint32_t ad0 = SB + ((lane >> 4) * 8 + (lane & 7)) * 128 + (((c0 + ((lane >> 3) & 1)) ^ (lane & 7)) << 4);
#pragma unroll 1
  for (int t = 0; t < 4; t++) {
    float acc[4][4] = {};
    uint32_t bias[8];
#pragma unroll
    for (int a = 0; a < 8; a++) bias[a] = t >= 2 ? reinterpret_cast<const uint32_t*>(Q.b1 + 448 * jj + (t - 2) * 192 + c0 * 8)[(a >> 1) * 32 + (a & 1) * 4 + q] : 0u;
#pragma unroll 1
    for (int i = 0; i < 16; i++, st += 2) {
      const uint32_t ad = ad0 + (c_sched.v[8][st] & 31) * 8192;
      mbar_spin(SB + BAR_FULLB + (st & 7) * 8, (st >> 3) & 1);
#pragma unroll
      for (int u = 0; u < 16; u++)
        asm volatile("{\n.reg .pred p;\nsetp.ne.u32 p, %5, 0;\n@p ldmatrix.sync.aligned.m8n8.x4.trans.shared.b16 {%0,%1,%2,%3}, [%4];\n}"
                     : "+r"(bf[u][0]), "+r"(bf[u][1]), "+r"(bf[u][2]), "+r"(bf[u][3])
                     : "r"(ad + (u & 3) * 8192 + (u >> 2) * 2048), "r"((u & 3) != 3 || t == 3 ? 1 : 0) : "memory");
      __syncwarp();
      e_arrive(SB + BAR_EMPTYB + (st & 7) * 8, 2);
#pragma unroll
      for (int u = 0; u < 16; u++) mma16(acc[u & 3], bf[u][0], bf[u][1], bf[u][2], bf[u][3], 0x3F803F80u, 0x3F803F80u);
    }
    const uint32_t epoch = lds32(SB + OFF_HOLD + 8);
    const uint32_t o = (t * 8 + jj) * 1024 + g * 32 + ((c0 ^ g) << 2) + q + (epoch & 1) * 32768;
    uint32_t *const p0 = Q.s->aug[0][0] + o, *const p1 = Q.s->aug[0][0] + (o ^ 4);
#pragma unroll
    for (int a = 0; a < 8; a++) {
      const float u = acc[a >> 1][(a & 1) * 2];
      uint32_t h = movm(pack_bf16(u, u - bf_round(u)));
      if (g >= 6) h = bias[a];
      ((a & 1) ? p1 : p0)[(a >> 1) * 256] = h ? h : 0x8000u;
    }
    uint4* const z = reinterpret_cast<uint4*>(Q.s->aug[~epoch & 1][t * 8 + jj]) + (threadIdx.x & 127);
    z[0] = z[128] = make_uint4(0, 0, 0, 0);
  }
}

template <bool BYSM> __global__ void __launch_bounds__(NTHREADS, 1) mega_kernel(const __grid_constant__ Ptrs Q, const __grid_constant__ Params P) {
  extern __shared__ __align__(1024) uint8_t smem_raw[];
  constexpr uint32_t sb = SB;
  const uint32_t centry = clock32();
  const int warp = __shfl_sync(~0u, threadIdx.x >> 5, 0), lane = threadIdx.x & 31;
  const int bid = BYSM ? work_id() : blockIdx.x;
  const bool aux = bid >= NMAIN;
  const int r = Q44 ? ((bid >> 5) << 2) | (bid & 3) : ((bid >> 4) << 1) | (bid & 1), j = (aux ? bid * 2 : bid >> (1 + Q44)) & 7;
  PRO(0);
  {
    const uint32_t b = sb + OFF_BAR + warp * 48, cnt = warp < 6 ? 1 : (warp < 10 ? 4 : 8);
    asm volatile("{\n.reg .pred p;\nelect.sync _|p, 0xffffffff;\n@p mbarrier.init.shared::cta.b64 [%0], %1;\n@p mbarrier.init.shared::cta.b64 [%0 + 8], %1;\n"
                 "@p mbarrier.init.shared::cta.b64 [%0 + 16], %1;\n@p mbarrier.init.shared::cta.b64 [%0 + 24], %1;\n"
                 "@p mbarrier.init.shared::cta.b64 [%0 + 32], %1;\n@p mbarrier.init.shared::cta.b64 [%0 + 40], %1;\nfence.mbarrier_init.release.cluster;\n}"
                 ::"r"(b), "r"(cnt) : "memory");
  }
  __syncthreads();
  {
    static_assert(NPRO == 4 && ROUND0 == 0, "prologue stages");
    const int st = ((11 - warp) * (aux ? 32 : 11)) >> 5, op = aux ? (st < 8) * 2 : 11 - warp - 3 * st, sd = aux ? st >> STGX : (op == 2 ? st : st & 2);
    const uint32_t bar0 = sb + OFF_BAR + (op * 6 + st) * 8;
    const int kc = aux ? (st >> 1) * 64 : (st & 2 ? (ROUND1 >> (4 * j)) & 15 : 0) * 128 + (st & 1) * 64;
    spin_until(centry + (sd ? STG0 + sd * STG1 : 0));
    if (op == 2) {
      asm volatile("{\n.reg .pred p;\nelect.sync _|p, 0xffffffff;\n@p mbarrier.arrive.expect_tx.shared::cta.b64 _, [%2], 24576;\n"
                   "@p cp.async.bulk.tensor.4d.shared::cluster.global.mbarrier::complete_tx::bytes [%0], [%1, {%3, %4, %3, %5}], [%2];\n}"
                   ::"r"(sb + OFF_B + (aux ? (st & 1) * 114688 + (st >> 1) * 24576 : (st + pos0(0) / 3 - (st + pos0(0) / 3 >= 5 ? 5 : 0)) * 24576)), "l"(&P.tm[TM_WQKV]), "r"(bar0), "r"(0), "r"(kc), "r"(j + (st & aux)) : "memory");
    } else if (!aux) e_load(sb + OFF_A + (op * 6 + st) * 8192, &P.tm[TM_XIN], op * 1024 + kc, r * 64, bar0);
    PRO(1);
    asm volatile("prefetch.tensormap [%0];" ::"l"(&P.tm[warp]) : "memory");
  }
  if (warp >= 8) {
    asm volatile("setmaxnreg.dec.sync.aligned.u32 24;");
    if (warp == 11) {
      if (smem_u32(smem_raw) != SB) __trap();
      const uint32_t epoch = __shfl_sync(~0u, ld_relaxed(&Q.s->epoch[bid]) + 1, 0);
      Q.s->epoch[bid] = epoch;
      asm volatile("st.shared.b32 [%0], %1;" ::"r"(sb + OFF_HOLD + 8), "r"(epoch) : "memory");
      e_arrive(sb + BAR_EPOCH, 1);
      PRO(2);
      if (!aux) server(P, Q, bid, r, j, lane, epoch);
    } else {
      const uint32_t e = c_sched.v[aux ? 8 : j][aux ? warp : NPRO];
      spin_until(centry + STGL + (e >> 31));
      PRO(2);
      const uint32_t epoch = get_epoch();
      PRO(3);
      if (warp <= 8 + aux) bloader(P, Q, aux, j + warp - 8, lane, e, epoch);
      else if (!aux) aloader(P, Q, bid, r, j, lane, warp - 9, e, epoch);
    }
  } else if (aux) aux_math(Q, bid, j + (warp >> 2), warp, lane);
  else {
    asm volatile("setmaxnreg.inc.sync.aligned.u32 240;");
    const int w = warp >> 2, wp = warp & 3;
    {
      uint32_t xr[32];
#pragma unroll
      for (int u = 0; u < 32; u++) if (NOI) asm volatile("" : "=r"(xr[u])); else xr[u] = 0;
      Pipe M;
      M.db = 0; M.g8 = 0; M.a8 = w * NA * 8; M.pa = 0; M.tph = 0; M.aend = (w + 1) * NA * 8;
      M.h0 = gridDim.y * 0x40000040u; M.h1 = gridDim.z * 0x40000040u; M.one = gridDim.z;
      M.curB = M.curA = M.prevB = M.prevA = M.sph = 0; M.nx = make_uint2(0, 0); M.w = w; M.l0 = lane == 0;
      M.bo = (wp * 16 + (lane & 15)) * 128 + (((lane >> 4) ^ (lane & 7)) << 4);
      M.so = __shfl_sync(~0u, SB + OFF_A + wp * 2048 + lane * 32 + (lane >> 2) * 4, lane);
      M.bo = __shfl_sync(~0u, M.bo, lane);
      auto nop = [](int) {};
      const uint32_t zero = gridDim.y - 1;
      PROF_T(w, 0, 3);
      if (STARTC) spin_until(centry + STARTC);
#pragma unroll 1
      for (int hl = 0; hl < 4; hl++) {
        const int t0 = hl * 3;
        const bool ffn = hl & 1;
        float acc[96], acn[64];
        uint32_t au[2] = {0u, 0u};
        {
          const int d = hl ? 0 : ((OWNP * 2u) >> (4 * j)) & 15;
          auto own = [&](auto h, uint32_t dep = 0) {
#pragma unroll
            for (int u = 4 * h.v; u < 4 * h.v + 4; u++)
              asm volatile("ldmatrix.sync.aligned.m8n8.x4.shared.b16 {%0,%1,%2,%3}, [%4];" : "=r"(xr[4 * u]), "=r"(xr[4 * u + 1]), "=r"(xr[4 * u + 2]), "=r"(xr[4 * u + 3])
                           : "r"(box_addr(sb + OFF_A + M.a8 * 1024, M.bo + dep, u & 3)) : "memory");
          };
          M.begin<192>(acc, ffn ? pos0(3) : pos0(0), t0, [&](int) { if (hl + d == 0) own(IC<0>{}); });
          if (hl + d == 0) own(IC<1>{}, (xr[0] | xr[4] | xr[8] | xr[12]) & zero);
          float ss[2] = {0.f, 0.f}, sq[2] = {0.f, 0.f};
          auto part = [&](auto c0, auto n) {
#pragma unroll
            for (int v = 0; v < 4 * n.v; v++) {
              const int u = c0.v + v / n.v * 4 + v % n.v;
              float a, b;
              asm volatile("shl.b32 %0, %2, 16;\nand.b32 %1, %2, 0xffff0000;" : "=f"(a), "=f"(b) : "r"(xr[u]));
              ss[u & 1] += a + b; sq[u & 1] = fmaf(a, a, fmaf(b, b, sq[u & 1]));
            }
          };
          const uint64_t plan = hl ? (ffn ? PLAN1 : PLAN2) : (d ? PLAN0 : PLANZ);
          auto todo = [&](int i) { uint64_t v; asm volatile("shr.u64 %0, %1, %2;" : "=l"(v) : "l"(plan), "r"((i + 1 - d) * 8)); return (uint32_t)v; };
          uint32_t m = todo(1);
          M.run<192, false>(acc, 1, 16, 1u << 10, 16 - (ffn ? LEAD3 : LEAD0), [&](int i, uint2 ok) {
           CT(0);
           if (m & 127) {
             if (m & 1) part(IC<0>{}, IC<2>{});
             if (m & 2) part(IC<2>{}, IC<2>{});
             if (m & 4) part(IC<16>{}, IC<1>{});
             if (m & 8) part(IC<17>{}, IC<1>{});
             if (m & 16) part(IC<18>{}, IC<1>{});
             if (m & 32) part(IC<19>{}, IC<1>{});
             if (m & 64) {
               const uint32_t epoch = lds32(sb + OFF_HOLD + 8);
#pragma unroll
               for (int o = 1; o < 4; o *= 2)
#pragma unroll
                 for (int z = 0; z < 2; z++) { ss[z] += __shfl_xor_sync(~0u, ss[z], o); sq[z] += __shfl_xor_sync(~0u, sq[z], o); }
               const float m0 = ss[0] * (1.f / 128.f), m1 = ss[1] * (1.f / 128.f);
               const int rowpair = r * 64 + w * 32 + wp * 8 + (M.lane() >> 2);
               if ((M.lane() & 3) == 0)
                 st_pkt(&Q.s->stats[hl][rowpair >> 1][j][rowpair & 1], __float_as_uint(m0), (__float_as_uint(fmaxf(fmaf(-ss[0], m0, sq[0]), 0.f)) & ~63u) | (epoch & 63),
                        __float_as_uint(m1), __float_as_uint(fmaxf(fmaf(-ss[1], m1, sq[1]), 0.f)));
             }
           }
           CT(1);
           M.ensure(ok);
           CT(3);
           M.validate(hl != 0, &P.tm[ffn ? TM_XA16 : TM_X16], w * 1024, r * 64, wp, j, [&] {
            if (m & 128) { if (m & 1) own(IC<1>{}); else own(IC<0>{}); }
            m = todo(i + 1);
            if (i == STATI) { mbar_spin(sb + BAR_STAT + w * 8, hl & 1); stats_fetch(w, wp, M.lane(), au); }
           });
           CT(4);
          });
          M.end<192, true>(acc, ffn ? 0 : 4, ffn ? posa(3) : posa(0), au[0], au[1], t0);
          PROF_T(w, t0, 2);
        }
        if (!ffn) {
          Attn T;
#pragma unroll 1
          for (int wave = 0; wave < 2; wave++) {
            AP(9);
            uint4* const hp = Q.s->halo[0][0] + (uint32_t)(((hl + wave) * 256 + r * 16 + j * 2 + w) * 136);
            T.A(acc, M, w, wp, r, hp);
            AP(0);
            if (wave == 0) {
              M.begin<192, PACE2 & 1>(acc, pos0(1), t0 + 1);
              M.run<192>(acc, 1, NH1, 4, -1, nop);
              T.B(w, wp, M.lane(), 0);
              M.drain();
            } else {
              M.begin<128, (PACE2 >> 1) & 1>(acn, pos0(2), t0 + 2);
              M.run<128>(acn, 1, NH2, 4, -1, nop);
              T.B(w, wp, M.lane(), 1);
              M.drain();
#pragma unroll
              for (int z = 0; z < 64; z++) asm volatile("mov.b32 %0, %1;" : "=f"(acc[z]) : "f"(acn[z]));
            }
            AP(2);
            T.C(wp, r, M.lane(), zero, [&] { if (EFIRST == 3 || (EFIRST == 2 && wave)) T.E(M, wave); });
            AP(3);
            if (wave == 1) break;
            M.run<192>(acc, NH1, 16, 1u << 7, 16 - LEAD1, [&](int i) { if (EFIRST < 3 && i == NH1) T.E(M, false); });
            M.end<192, true>(acc, 4, posa(1), au[0], au[1], t0 + 1);
            PROF_T(w, t0 + 1, 2);
          }
#pragma unroll
          for (int z = 0; z < 64; z++) asm volatile("mov.b32 %0, %1;" : "=f"(acn[z]) : "f"(acc[z]));
          if (EFIRST == 1) T.E(M, true);
          else if (!EFIRST) {
            M.ensure(M.iss<128, false>(acn, false));
            T.E(M, true);
          }
        } else {
          uint32_t pk[48], pk2[64];
          pack_relu<0, 48>(pk, acc);
          {
            float acc2[128];
            M.begin<256, (PACE2 >> 3) & 1>(acc2, pos0(4), t0 + 1);
            M.run<256>(acc2, 1, 16, 0x248, 16 - LEAD4, [&](int i) { ffn_stage(pk, i, M); });
            M.end<256, true>(acc2, 0, posa(4), au[0], au[1], t0 + 1);
            pack_relu<0, 64>(pk2, acc2);
            PROF_T(w, t0 + 1, 2);
          }
          M.begin<128, (PACE2 >> 4) & 1>(acn, pos0(5), t0 + 2);
          M.run<128>(acn, 1, 13, 0x1248, -1, [&](int i) { ffn_stage(pk2, i, M); });
        }
        {
          const int ks = ffn ? 56 : 16, pause = ks - (ffn ? LEAD5 : LEAD2), vfrom = ffn ? 99 : 7;
          const int imid = w ? pause : (ffn ? 20 : IPRE);
          auto check = [&](int i) {
            if (i >= vfrom) {
              if (i == 7) mbar_spin(sb + BAR_OWN + w * 8, hl >> 1);
              M.validate(true, &P.tm[TM_O16], 0, r * 128 + w * 64, wp, j, [] {});
            }
          };
          M.run<128>(acn, ffn ? 13 : NH2 + !EFIRST, imid, 0, -1, check);
          if (w) M.drain();
          float pre[64], rstd[2];
          presum(pre, xr, M.lane(), ffn ? 1.f : 0.f);
          own_rstd(w, wp, M.lane(), rstd);
          if (w) mbar_spin(SB + BAR_LEAD, M.tph);
          M.run<128>(acn, imid, ks, 0, 0, check);
          M.end<128, false>(acn, 2, 0, 0, 0, t0 + 2);
          epi_res(acn, pre, ffn ? rstd[0] * rstd[0] : 1.f, ffn ? rstd[1] * rstd[1] : 1.f, xr, M, wp);
          PROF_T(w, t0 + 2, 2);
        }
      }
    }
  }
}

typedef CUresult (*EncFn)(CUtensorMap*, CUtensorMapDataType, cuuint32_t, void*, const cuuint64_t*, const cuuint64_t*, const cuuint32_t*,
                          const cuuint32_t*, CUtensorMapInterleave, CUtensorMapSwizzle, CUtensorMapL2promotion, CUtensorMapFloatOOBfill);

void enc2(EncFn enc, CUtensorMap* tm, const void* p, uint64_t cols, uint64_t rows, uint32_t boxrows = 64, CUtensorMapL2promotion promo = CU_TENSOR_MAP_L2_PROMOTION_L2_128B) {
  cuuint64_t gd[2] = {cols, rows}, gs[1] = {cols * 2};
  cuuint32_t box[2] = {64, boxrows}, es[2] = {1, 1};
  enc(tm, CU_TENSOR_MAP_DATA_TYPE_BFLOAT16, 2, const_cast<void*>(p), gd, gs, box, es, CU_TENSOR_MAP_INTERLEAVE_NONE, CU_TENSOR_MAP_SWIZZLE_128B,
      promo, CU_TENSOR_MAP_FLOAT_OOB_FILL_NONE);
}
void enc4(EncFn enc, CUtensorMap* tm, const void* p, uint64_t K, uint64_t N, uint64_t d2, uint64_t s2, uint64_t d3, uint64_t s3, uint32_t na) {
  cuuint64_t gd[4] = {64, K, d2, d3}, gs[3] = {N * 2, s2, s3};
  cuuint32_t box[4] = {64, 64, na, 1}, es[4] = {1, 1, 1, 1};
  enc(tm, CU_TENSOR_MAP_DATA_TYPE_BFLOAT16, 4, const_cast<void*>(p), gd, gs, box, es, CU_TENSOR_MAP_INTERLEAVE_NONE, CU_TENSOR_MAP_SWIZZLE_128B,
      WPROMO, CU_TENSOR_MAP_FLOAT_OOB_FILL_NONE);
}

}

extern "C" void kernel_launch(void* const* d_in, const int* in_sizes, int n_in, void* d_out, int out_size) {
  static EncFn enc = nullptr;
  static Scratch* ps = nullptr;
  static void (*kernel)(Ptrs, Params) = mega_kernel<true>;
  if (!enc) {
    cudaDriverEntryPointQueryResult qr;
    cudaGetDriverEntryPoint("cuTensorMapEncodeTiled", (void**)&enc, cudaEnableDefault, &qr);
    int dev = 0, nsm = 0;
    cudaGetDevice(&dev);
    cudaDeviceGetAttribute(&nsm, cudaDevAttrMultiProcessorCount, dev);
    if (nsm != NMAIN + NAUX) kernel = mega_kernel<false>;
    cudaFuncSetAttribute(kernel, cudaFuncAttributeMaxDynamicSharedMemorySize, SMEM_BYTES);
    cudaGetSymbolAddress((void**)&ps, g_s);
  }
  Params P;
  Ptrs Q;
  Q.s = ps;
  void *p_h = ps->h, *p_x = ps->x;
  enc2(enc, &P.tm[TM_XIN], d_in[0], 2048, 1024, 64, XPROMO);
  enc2(enc, &P.tm[TM_X], d_out, 2048, 1024);
  enc2(enc, &P.tm[TM_XA], p_x, 2048, 1024);
  enc2(enc, &P.tm[TM_O], p_h, 3584, 2048);
  enc2(enc, &P.tm[TM_H], p_h, 3584, 2048);
  enc2(enc, &P.tm[TM_X16], d_out, 2048, 1024, 16);
  enc2(enc, &P.tm[TM_XA16], p_x, 2048, 1024, 16);
  enc2(enc, &P.tm[TM_O16], p_h, 3584, 2048, 16);
  enc4(enc, &P.tm[TM_WQKV], d_in[1], 1024, 3072, 3, 2048, 16, 128, 3);
  enc4(enc, &P.tm[TM_WO], d_in[2], 1024, 1024, 16, 128, 1, 128, 2);
  enc4(enc, &P.tm[TM_W1A], d_in[4], 1024, 3584, 56, 128, 1, 128, 4);
  enc4(enc, &P.tm[TM_W1B], d_in[4], 1024, 3584, 56, 128, 1, 128, 3);
  enc4(enc, &P.tm[TM_W2], d_in[6], 3584, 1024, 16, 128, 1, 128, 2);
  Q.out = (__nv_bfloat16*)d_out;
  Q.b1 = (const __nv_bfloat16*)d_in[5];
  Q.b2 = (const __nv_bfloat16*)d_in[7];
  kernel<<<NMAIN + NAUX, NTHREADS, SMEM_BYTES, cudaStreamPerThread>>>(Q, P);
}
```

```cpp
#include <cuda_runtime.h>
#include <cuda_bf16.h>
#include <cuda.h>
#include <stdint.h>

#define LEAD0 2
#define LEAD1 1
#define LEAD2 4
#define LEAD3 2
#define LEAD4 1
#define LEAD5 5
#define WPROMO CU_TENSOR_MAP_L2_PROMOTION_L2_128B
#define PLAN1 0x7f0000ull
#define PLAN2 0x400000003f0000ull
#define P0S 0x640096
#define PAS 0x430ff
#define PLAN0 0x4030020c8180ull
#define PLAN6 0x7c8380ull
#define PLANZ 0x40300a050000ull
#define LAGM 27
#define APROMO CU_TENSOR_MAP_L2_PROMOTION_L2_128B
#define LSO 1
#define STATI 13
#define PACE2 0x1a
#define ST2 12
#define STB 3
#define PROBE 4
#define XO 0
#define FORD 0x01234567, 0x01234567, 0x01234567, 0x01234567, 0x04567123, 0x04567123, 0x04567123, 0x04765123
#define SIG0 14
#define STGX 2
#define STGM 3
#define NPRO 4
#define XPROMO CU_TENSOR_MAP_L2_PROMOTION_L2_256B
#define IPRE 7
#define FILLT 1
#define EARLYC 1
#define OWNDLY 0
#define EPW 0
#define CPF 5000
#define STG0 800
#define STG1 400
#define STGL (STG0 + 4 * STG1)
#define STGLW 0
#define STGLX 0
#define STARTC 0
#define FUN 4
#define XEF 0
#define BEF 0xff8
#define AEF 0xdb6
#define SEF 0
#define SDELAYO 1000
#define SDELAY 300
#define HDELAY 450
#define Q44 1
#define FG 8
#define NOI 1
#define EFIRST 1
#define STA 1
#define PG (Q44 ? 32 : 16)
#define NH1 6
#define NH2 3
namespace {

constexpr int NMAIN = 128, NAUX = 4, NTHREADS = 384;
constexpr uint32_t OFF_B = 0;
constexpr uint32_t OFF_A = 131072;
constexpr uint32_t OFF_VEC = 229376;
constexpr uint32_t OFF_BAR = 231424;
constexpr uint32_t OFF_RSTD = OFF_VEC + 512, OFF_MEAN = OFF_VEC + 1088, OFF_HOLD = OFF_VEC + 2032;
constexpr uint32_t SMEM_BYTES = OFF_BAR + 960;
constexpr uint32_t BAR_FULLA = OFF_BAR, BAR_FULLB = OFF_BAR + 96, BAR_OWN = OFF_BAR + 160, BAR_EPOCH = OFF_BAR + 176, BAR_AUG = OFF_BAR + 184, BAR_SPEC = OFF_BAR + 192,
                   BAR_EMPTYA = OFF_BAR + 288, BAR_STG = OFF_BAR + 384, BAR_SRV = OFF_BAR + 400, BAR_LEAD = OFF_BAR + 432, BAR_HALO = OFF_BAR + 440, BAR_STG2 = OFF_BAR + 456,
                   BAR_DUMMY3 = OFF_BAR + 472, BAR_EMPTYB = OFF_BAR + 480, BAR_STAT = OFF_BAR + 544, BAR_DUMMY = OFF_BAR + 560;
constexpr int NA = 6;
constexpr uint32_t SB = 1024;
constexpr uint32_t SPIN_LIMIT = 1u << 22;

enum { TM_XIN = 0, TM_X, TM_XA, TM_O, TM_H, TM_WQKV, TM_WO, TM_W1A, TM_W1B, TM_W2, TM_X16, TM_XA16, TM_O16, TM_COUNT };

struct Scratch;
struct Ptrs {
  Scratch* s;
  __nv_bfloat16* out;
  const __nv_bfloat16* b1;
  const __nv_bfloat16* b2;
};
struct Params { CUtensorMap tm[TM_COUNT]; };

constexpr int NSTEP = 280, NSTEP_AUX = 128;
enum : uint32_t { F_STAMP = 1u << 28, F_GATH = 1u << 15, F_NEW = 1u << 16, F_AUG = 1u << 17, F_NOA = 1u << 18, E_HAND = 1u << 19, E_ATTN = 1u << 20, E_XPUB0 = 1u << 21,
                  E_WAIT = 1u << 22, E_REL = 1u << 23, E_KEEP = 1u << 24, E_PART1 = 1u << 25, E_HALO = 1u << 26,
                  E_SIG = 1u << 27, E_RARE = F_NEW | E_KEEP | (0xfu << 20) | (3u << 26) };
constexpr uint32_t first_order(int j) {
  constexpr uint32_t t[8] = {FORD};
  uint32_t v = 0;
  for (int p = 0; p < 8; p++) v |= ((t[j] >> (28 - 4 * p)) & 15) << (4 * p);
  return v;
}
constexpr uint32_t own_rounds() { uint32_t v = 0; for (int j = 0; j < 8; j++) for (int p = 0; p < 8; p++) if (((first_order(j) >> (4 * p)) & 15) == j) v |= p << (4 * j); return v; }
constexpr uint32_t OWNP = own_rounds();
constexpr uint32_t first_round(int p) { uint32_t v = 0; for (int j = 0; j < 8; j++) v |= ((first_order(j) >> (4 * p)) & 15) << (4 * j); return v; }
constexpr uint32_t ROUND0 = first_round(0), ROUND1 = first_round(1);
__host__ __device__ constexpr int pos0(int kind) { return (P0S >> (4 * kind)) & 15; }
__host__ __device__ constexpr int posa(int kind) { return (PAS >> (4 * kind)) & 15; }
struct Sched { uint32_t v[9][NSTEP + 8]; };
constexpr Sched make_sched() {
  Sched T{};
  for (int j = 0; j < 8; j++) {
    int owner[16] = {};
    for (int i = 0; i < 16; i++) owner[i] = -100;
    int p = 0, g = 0;
    for (int t = 0; t < 12; t++) {
      const int kind = t % 6, ks = kind == 5 ? 56 : (kind == 2 ? 16 : 17);
      for (int i = 0; i < ks; i++) {
        const bool augs = ks == 17 && i == 16;
        const int na = (kind == 2 || kind == 5) ? 2 : (augs ? 1 : (kind == 4 ? 4 : 3));
        if (i == 0) p = pos0(kind);
        if (augs) p = posa(kind);
        if (p + na > 16) p = 0;
        int need = g - 8;
        for (int a = p; a < p + na; a++) { if (owner[a] > need) need = owner[a]; owner[a] = g; }
        uint32_t k = i, f = i == (t ? 0 : NPRO) ? F_NEW | (1u << 29) : 0;
        if (augs) { k = 0; f |= F_AUG; }
        else if (kind == 0 || kind == 3) {
          const int o = i - 2;
          if (t == 0) k = ((first_order(j) >> (4 * (i >> 1))) & 15) * 2 + (i & 1);
          else if (i < 2) { k = 2 * j + i; f |= F_NOA | (i == 0 ? E_XPUB0 : 0); }
          else { const int half = o >= 7; int u = o - 7 * half; { const int b = (XO & 3) == 0 ? 0 : ((XO & 3) == 1 ? (j & 4) ^ 4 : j & 4); u += u >= (j ^ b); u ^= b; } k = 2 * u + half; if (i == 6) f |= E_REL; }
          if (i == 11) f |= E_HAND;
          if (i == (t ? 11 : SIG0)) f |= E_SIG;
        } else if (kind == 1 || kind == 4) {
          if (kind == 1) f |= i == 3 ? E_HAND : (i == 8 ? E_HAND | E_KEEP : (i == 5 ? E_HALO : 0));
          if (kind == 1) f |= i == 13 ? E_REL : 0;
          else if (i == 4 || i == 7 || i == 10) f |= E_HAND;
        } else if (kind == 2) {
          f |= i == 0 ? E_WAIT : (i == 3 ? E_HAND : (i == 5 ? E_HALO : 0));
          if (i == 8) { k = 8 + j; f |= E_ATTN | E_KEEP | F_NOA; }
          if (i > 8) { const int b = (XO >> 2) == 0 ? 0 : ((XO >> 2) == 1 ? (j & 4) ^ 4 : j & 4); k = 8 + ((i - 9 + (i - 9 >= (j ^ b))) ^ b); }
          if (i == 11) f |= E_REL;
        } else {
          k = i < 24 ? (i / 3) * 7 + i % 3 : ((i - 24) / 4) * 7 + 3 + (i - 24) % 4;
          if (i == 4 || i == 7 || i == 10 || i == 13) f |= E_HAND;
          f |= i == 0 ? E_WAIT : (i == 24 ? E_WAIT | E_PART1 : 0);
        }
        if ((kind == 2 || kind == 5) && t < 11 && i == ks - (kind == 2 ? STA : STB)) f |= F_STAMP;
        if (((PACE2 >> kind) & 1) && i == ST2) f |= F_STAMP;
        if (i == 0 && t && ((PACE2 >> ((t - 1) % 6)) & 1)) f |= F_GATH;
        T.v[j][g] = p | ((g - need) << 5) | (k << 9) | f;
        p += na; g++;
      }
    }
    T.v[j][NSTEP] = F_NEW | F_NOA | E_XPUB0 | (2 * j << 9);
  }
  for (int w = 0; w < 2; w++) {
    int owner[14] = {};
    for (int i = 0; i < 14; i++) owner[i] = -100;
    for (int g = w, p = 0; g < NSTEP_AUX; g += 2) {
      const int na = g < 96 ? 3 : 4;
      if (p + na > 14) p = 0;
      int need = g - 8;
      for (int a = p; a < p + na; a++) { if (owner[a] > need) need = owner[a]; owner[a] = g; }
      T.v[8][g] = (p + 14 * w) | ((g - need) << 5) | ((g & 31) >> 1 << 9) | ((g & 30) && g - w != 8 ? 0 : F_NEW | (g - w == 64 ? 2u : 1u) << 29);
      p += na;
    }
  }
  return T;
}
__constant__ Sched c_sched = make_sched();
__device__ __forceinline__ int sched_k(uint32_t e) { return (e >> 3) & 0xfc0; }

struct Scratch {
  __nv_bfloat16 x[2048 * 1024];
  __nv_bfloat16 h[2048 * 3584];
  uint32_t epoch[160];
  uint8_t flags[16][2][64];
  uint32_t pace[8][64];
  uint32_t aug[2][32][1024];
  uint4 stats[4][512][8][2];
  uint4 halo[4][256][136];
};
__device__ __align__(1024) Scratch g_s;
#define PROF_T(w, t, i)
#define PRO(i)
#define LT(i)
#define CT(n)
#define ST(i)
#define AP(i)

__device__ __forceinline__ int work_id() {
  uint32_t smid;
  asm volatile("mov.u32 %0, %%smid;" : "=r"(smid));
  const int t = smid >> 1, u = t - 32, d = (u * 37) >> 8;
  int id = (t & 7) * 16 + (t >> 3) * 2;
  if (t >= 32) id = (1 + u - 7 * d) * 16 + (4 + d) * 2;
  if (t >= 60) id = t < 62 ? t * 2 + 8 : t * 2 - 116;
  return id + (smid & 1);
}

__device__ __forceinline__ uint32_t smem_u32(const void* p) { return (uint32_t)__cvta_generic_to_shared(p); }
__device__ __forceinline__ void mbar_init(uint32_t bar, int cnt) { asm volatile("mbarrier.init.shared::cta.b64 [%0], %1;" ::"r"(bar), "r"(cnt)); }
__device__ __forceinline__ void mbar_expect_tx(uint32_t bar, uint32_t bytes) { asm volatile("mbarrier.arrive.expect_tx.shared::cta.b64 _, [%0], %1;" ::"r"(bar), "r"(bytes) : "memory"); }
__device__ __forceinline__ void mbar_arrive(uint32_t bar, uint32_t cnt) { asm volatile("mbarrier.arrive.shared::cta.b64 _, [%0], %1;" ::"r"(bar), "r"(cnt) : "memory"); }
__device__ __forceinline__ void arrive_n(uint32_t bar, bool) { asm volatile("{\n.reg .pred p;\nelect.sync _|p, 0xffffffff;\n@p mbarrier.arrive.shared::cta.b64 _, [%0];\n}" ::"r"(bar) : "memory"); }
__device__ __forceinline__ void arrive_2(uint32_t b0, uint32_t b1, bool) {
  asm volatile("{\n.reg .pred p;\nelect.sync _|p, 0xffffffff;\n@p mbarrier.arrive.shared::cta.b64 _, [%0];\n@p mbarrier.arrive.shared::cta.b64 _, [%1];\n}" ::"r"(b0), "r"(b1) : "memory");
}
__device__ __forceinline__ void mbar_wait(uint32_t bar, uint32_t parity) {
  asm volatile(
      "{\n.reg .pred p;\n.reg .u32 c;\nmov.u32 c, 0;\n"
      "LAB_WAIT:\nmbarrier.try_wait.parity.shared::cta.b64 p, [%0], %1;\n@p bra.uni DONE;\n"
      "add.u32 c, c, 1;\nsetp.lt.u32 p, c, 4000000;\n@p bra.uni LAB_WAIT;\ntrap;\nDONE:\n}" ::"r"(bar), "r"(parity) : "memory");
}
__device__ __forceinline__ void mbar_spin(uint32_t bar, uint32_t parity) {
  asm volatile("{\n.reg .pred p;\nLAB_WAIT:\nmbarrier.try_wait.parity.shared::cta.b64 p, [%0], %1;\n@!p pmevent 7;\n@!p bra.uni LAB_WAIT;\n}" ::"r"(bar), "r"(parity) : "memory");
}
__device__ __forceinline__ void mbar_spin31(uint32_t bar, uint32_t ph) {
  asm volatile("{\n.reg .pred p;\n.reg .b64 s;\nmov.b64 s, {%1, %1};\nLAB_WAIT:\nmbarrier.try_wait.shared::cta.b64 p, [%0], s;\n@!p pmevent 7;\n@!p bra.uni LAB_WAIT;\n}" ::"r"(bar), "r"(ph) : "memory");
}
__device__ __forceinline__ bool elect_one() {
  uint32_t p;
  asm volatile("{\n.reg .pred P;\nelect.sync _|P, 0xffffffff;\nselp.u32 %0, 1, 0, P;\n}" : "=r"(p));
  return p != 0;
}
__device__ __forceinline__ bool mbar_test(uint32_t bar, uint32_t parity) {
  uint32_t ok;
  asm volatile("{\n.reg .pred p;\nmbarrier.test_wait.parity.shared::cta.b64 p, [%1], %2;\nselp.u32 %0, 1, 0, p;\n}" : "=r"(ok) : "r"(bar), "r"(parity) : "memory");
  return ok != 0;
}
__device__ __forceinline__ void tma_ld2(uint32_t dst, const CUtensorMap* tm, int c0, int c1, uint32_t bar) {
  asm volatile("cp.async.bulk.tensor.2d.shared::cluster.global.mbarrier::complete_tx::bytes [%0], [%1, {%3, %4}], [%2];" ::"r"(dst), "l"(tm), "r"(bar), "r"(c0), "r"(c1) : "memory");
}
__device__ __forceinline__ void tma_ld4(uint32_t dst, const CUtensorMap* tm, int c1, int c2, int c3, uint32_t bar, uint64_t pol = 0x1000000000000000ull) {
  asm volatile("cp.async.bulk.tensor.4d.shared::cluster.global.mbarrier::complete_tx::bytes.L2::cache_hint [%0], [%1, {%3, %4, %5, %6}], [%2], %7;" ::"r"(dst), "l"(tm), "r"(bar), "r"(0), "r"(c1), "r"(c2), "r"(c3), "l"(pol) : "memory");
}
__device__ __forceinline__ void tma_st2(const CUtensorMap* tm, int c0, int c1, uint32_t src) {
  asm volatile("cp.async.bulk.tensor.2d.global.shared::cta.bulk_group [%0, {%2, %3}], [%1];" ::"l"(tm), "r"(src), "r"(c0), "r"(c1) : "memory");
}
__device__ __forceinline__ void bulk_ld(uint32_t dst, const void* src, uint32_t bytes, uint32_t bar) {
  asm volatile("cp.async.bulk.shared::cluster.global.mbarrier::complete_tx::bytes [%0], [%1], %2, [%3];" ::"r"(dst), "l"(src), "r"(bytes), "r"(bar) : "memory");
}
__device__ __forceinline__ void e_arrive(uint32_t bar, uint32_t cnt) {
  if (cnt == 1) asm volatile("{\n.reg .pred p;\nelect.sync _|p, 0xffffffff;\n@p mbarrier.arrive.shared::cta.b64 _, [%0];\n}" ::"r"(bar) : "memory");
  else asm volatile("{\n.reg .pred p;\nelect.sync _|p, 0xffffffff;\n@p mbarrier.arrive.shared::cta.b64 _, [%0], %1;\n}" ::"r"(bar), "r"(cnt) : "memory");
}
template <int BYTES = 8192> __device__ __forceinline__ void e_load(uint32_t dst, const CUtensorMap* tm, int c0, int c1, uint32_t bar, uint64_t pol = 0x1000000000000000ull) {
  asm volatile("{\n.reg .pred p;\nelect.sync _|p, 0xffffffff;\n@p mbarrier.arrive.expect_tx.shared::cta.b64 _, [%2], %5;\n"
               "@p cp.async.bulk.tensor.2d.shared::cluster.global.mbarrier::complete_tx::bytes.L2::cache_hint [%0], [%1, {%3, %4}], [%2], %6;\n}"
               ::"r"(dst), "l"(tm), "r"(bar), "r"(c0), "r"(c1), "n"(BYTES), "l"(pol) : "memory");
}
__device__ __forceinline__ void e_store(const CUtensorMap* tm, int c0, int c1, uint32_t src) {
  asm volatile("{\n.reg .pred p;\nfence.proxy.async.shared::cta;\nelect.sync _|p, 0xffffffff;\n"
               "@p cp.async.bulk.tensor.2d.global.shared::cta.bulk_group [%0, {%2, %3}], [%1];\ncp.async.bulk.commit_group;\n}"
               ::"l"(tm), "r"(src), "r"(c0), "r"(c1) : "memory");
}
__device__ __forceinline__ void bulk_commit() { asm volatile("cp.async.bulk.commit_group;" ::: "memory"); }
template <int N> __device__ __forceinline__ void bulk_wait_read() { asm volatile("cp.async.bulk.wait_group.read %0;" ::"n"(N) : "memory"); }
__device__ __forceinline__ void bulk_wait_all() { asm volatile("cp.async.bulk.wait_group 0;" ::: "memory"); }
__device__ __forceinline__ void fence_async_smem() { asm volatile("fence.proxy.async.shared::cta;" ::: "memory"); }
__device__ __forceinline__ void wg_fence() { asm volatile("wgmma.fence.sync.aligned;" ::: "memory"); }
__device__ __forceinline__ void wg_commit() { asm volatile("wgmma.commit_group.sync.aligned;" ::: "memory"); }
template <int N> __device__ __forceinline__ void wg_wait() { asm volatile("wgmma.wait_group.sync.aligned %0;" ::"n"(N) : "memory"); }
__device__ __forceinline__ void wg_bar(int w) { asm volatile("bar.sync %0, 128;" ::"r"(w + 1) : "memory"); }
__device__ __forceinline__ uint32_t ld_acquire(const uint32_t* p) { uint32_t v; asm volatile("ld.acquire.gpu.global.u32 %0, [%1];" : "=r"(v) : "l"(p) : "memory"); return v; }
__device__ __forceinline__ uint4 ld_relaxed4(const uint32_t* p) {
  uint4 v; asm volatile("ld.relaxed.gpu.global.v4.u32 {%0,%1,%2,%3}, [%4];" : "=r"(v.x), "=r"(v.y), "=r"(v.z), "=r"(v.w) : "l"(p) : "memory"); return v;
}
__device__ __forceinline__ void st_release8(uint8_t* p, uint32_t v) { asm volatile("st.release.gpu.global.u8 [%0], %1;" ::"l"(p), "r"(v) : "memory"); }
__device__ __forceinline__ uint32_t ld_relaxed(const uint32_t* p) { uint32_t v; asm volatile("ld.relaxed.gpu.global.u32 %0, [%1];" : "=r"(v) : "l"(p) : "memory"); return v; }
__device__ __forceinline__ void st_release(uint32_t* p, uint32_t v) { asm volatile("st.release.gpu.global.u32 [%0], %1;" ::"l"(p), "r"(v) : "memory"); }
__device__ __forceinline__ void st_pkt(uint4* p, uint32_t a, uint32_t b, uint32_t c, uint32_t d) {
  asm volatile("{\n.reg .b64 lo, hi;\n.reg .b128 v;\nmov.b64 lo, {%1, %2};\nmov.b64 hi, {%3, %4};\nmov.b128 v, {lo, hi};\nst.relaxed.gpu.global.b128 [%0], v;\n}" ::"l"(p), "r"(a), "r"(b), "r"(c), "r"(d) : "memory");
}
__device__ __forceinline__ uint4 ld_pkt(const uint4* p) {
  uint4 r;
  asm volatile("{\n.reg .b64 lo, hi;\n.reg .b128 v;\nld.relaxed.gpu.global.b128 v, [%4];\nmov.b128 {lo, hi}, v;\nmov.b64 {%0, %1}, lo;\nmov.b64 {%2, %3}, hi;\n}" : "=r"(r.x), "=r"(r.y), "=r"(r.z), "=r"(r.w) : "l"(p) : "memory");
  return r;
}
__device__ __forceinline__ uint32_t pack_bf16(float lo, float hi) { uint32_t d; asm("cvt.rn.bf16x2.f32 %0, %1, %2;" : "=r"(d) : "f"(hi), "f"(lo)); return d; }
__device__ __forceinline__ float ex2(float x) { float y; asm("ex2.approx.ftz.f32 %0, %1;" : "=f"(y) : "f"(x)); return y; }
__device__ __forceinline__ float rsq(float x) { float y; asm("rsqrt.approx.ftz.f32 %0, %1;" : "=f"(y) : "f"(x)); return y; }
__device__ __forceinline__ float rcp(float x) { float y; asm("rcp.approx.ftz.f32 %0, %1;" : "=f"(y) : "f"(x)); return y; }
__device__ __forceinline__ float bf_lo(uint32_t v) { return __uint_as_float(v << 16); }
__device__ __forceinline__ float bf_hi(uint32_t v) { return __uint_as_float(v & 0xffff0000u); }
__device__ __forceinline__ void stsm4(uint32_t addr, uint32_t a, uint32_t b, uint32_t c, uint32_t d) {
  asm volatile("stmatrix.sync.aligned.m8n8.x4.shared.b16 [%0], {%1, %2, %3, %4};" ::"r"(addr), "r"(a), "r"(b), "r"(c), "r"(d) : "memory");
}
__device__ __forceinline__ uint32_t movm(uint32_t a) { uint32_t d; asm volatile("movmatrix.sync.aligned.m8n8.trans.b16 %0, %1;" : "=r"(d) : "r"(a)); return d; }
__device__ __forceinline__ void mma16(float (&c)[4], uint32_t a0, uint32_t a1, uint32_t a2, uint32_t a3, uint32_t b0, uint32_t b1) {
  asm volatile("mma.sync.aligned.m16n8k16.row.col.f32.bf16.bf16.f32 {%0,%1,%2,%3}, {%4,%5,%6,%7}, {%8,%9}, {%0,%1,%2,%3};"
               : "+f"(c[0]), "+f"(c[1]), "+f"(c[2]), "+f"(c[3]) : "r"(a0), "r"(a1), "r"(a2), "r"(a3), "r"(b0), "r"(b1));
}
__device__ __forceinline__ void mma8(float (&c)[4], uint32_t a0, uint32_t a1, uint32_t b0) {
  asm volatile("mma.sync.aligned.m16n8k8.row.col.f32.bf16.bf16.f32 {%0,%1,%2,%3}, {%4,%5}, {%6}, {%0,%1,%2,%3};"
               : "+f"(c[0]), "+f"(c[1]), "+f"(c[2]), "+f"(c[3]) : "r"(a0), "r"(a1), "r"(b0));
}
__device__ __forceinline__ void sts128(uint32_t a, uint32_t x, uint32_t y, uint32_t z, uint32_t w) {
  asm volatile("st.shared.v4.b32 [%0], {%1,%2,%3,%4};" ::"r"(a), "r"(x), "r"(y), "r"(z), "r"(w) : "memory");
}
__device__ __forceinline__ float2 lds64(uint32_t a) { float2 v; asm volatile("ld.shared.v2.f32 {%0,%1}, [%2];" : "=f"(v.x), "=f"(v.y) : "r"(a)); return v; }
__device__ __forceinline__ float4 lds128(uint32_t a) { float4 v; asm volatile("ld.shared.v4.f32 {%0,%1,%2,%3}, [%4];" : "=f"(v.x), "=f"(v.y), "=f"(v.z), "=f"(v.w) : "r"(a)); return v; }
__device__ __forceinline__ uint32_t lds32(uint32_t a) { uint32_t v; asm volatile("ld.shared.b32 %0, [%1];" : "=r"(v) : "r"(a)); return v; }
constexpr uint32_t PA1 = 0x80000000u / NA + 1, G1 = 8 + (1u << 28);
constexpr uint32_t DA0 = ((SB + OFF_A) >> 4) | (1u << 16), DB0 = ((SB + OFF_B) >> 4) | (512u << 16);
template <int S> __device__ __forceinline__ uint2 wgmma_first128(float (&d)[S], uint32_t da, uint32_t& db, uint32_t h0, uint32_t h1, uint32_t one, uint32_t b0, uint32_t p0, uint32_t b1, uint32_t p1) {
  uint2 ok;
  asm volatile("{\n.reg .b64 a, b, s;\n.reg .b32 t, u;\n.reg .pred p, q;\nwgmma.fence.sync.aligned;\n"
    "mov.b32 t, %67;\n"
    "mov.b64 a, {t, %68};\nmov.b64 b, {%66, %69};\n"
    "wgmma.mma_async.sync.aligned.m64n128k16.f32.bf16.bf16 "
    "{%2, %3, %4, %5, %6, %7, %8, %9, %10, %11, %12, %13, %14, %15, %16, %17, %18, %19, %20, %21, %22, %23, %24, %25, %26, %27, %28, %29, %30, %31, %32, %33, %34, %35, %36, %37, %38, %39, %40, %41, %42, %43, %44, %45, %46, %47, %48, %49, %50, %51, %52, %53, %54, %55, %56, %57, %58, %59, %60, %61, %62, %63, %64, %65}, "
    "a, b, 0, 1, 1, 0, 1;\n"
    "mad.lo.u32 t, %70, 2, t;\nmad.lo.u32 %66, %70, 128, %66;\n"
    "mov.b64 a, {t, %68};\nmov.b64 b, {%66, %69};\n"
    "wgmma.mma_async.sync.aligned.m64n128k16.f32.bf16.bf16 "
    "{%2, %3, %4, %5, %6, %7, %8, %9, %10, %11, %12, %13, %14, %15, %16, %17, %18, %19, %20, %21, %22, %23, %24, %25, %26, %27, %28, %29, %30, %31, %32, %33, %34, %35, %36, %37, %38, %39, %40, %41, %42, %43, %44, %45, %46, %47, %48, %49, %50, %51, %52, %53, %54, %55, %56, %57, %58, %59, %60, %61, %62, %63, %64, %65}, "
    "a, b, 1, 1, 1, 0, 1;\n"
    "mad.lo.u32 t, %70, 2, t;\nmad.lo.u32 %66, %70, 128, %66;\n"
    "mov.b64 a, {t, %68};\nmov.b64 b, {%66, %69};\n"
    "wgmma.mma_async.sync.aligned.m64n128k16.f32.bf16.bf16 "
    "{%2, %3, %4, %5, %6, %7, %8, %9, %10, %11, %12, %13, %14, %15, %16, %17, %18, %19, %20, %21, %22, %23, %24, %25, %26, %27, %28, %29, %30, %31, %32, %33, %34, %35, %36, %37, %38, %39, %40, %41, %42, %43, %44, %45, %46, %47, %48, %49, %50, %51, %52, %53, %54, %55, %56, %57, %58, %59, %60, %61, %62, %63, %64, %65}, "
    "a, b, 1, 1, 1, 0, 1;\n"
    "mov.b64 s, {%72, %72};\nmbarrier.test_wait.shared::cta.b64 p, [%71], s;\nmov.b64 s, {%74, %74};\nmbarrier.test_wait.shared::cta.b64 q, [%73], s;\n"
    "mad.lo.u32 t, %70, 2, t;\nmad.lo.u32 %66, %70, 128, %66;\n"
    "mov.b64 a, {t, %68};\nmov.b64 b, {%66, %69};\n"
    "wgmma.mma_async.sync.aligned.m64n128k16.f32.bf16.bf16 "
    "{%2, %3, %4, %5, %6, %7, %8, %9, %10, %11, %12, %13, %14, %15, %16, %17, %18, %19, %20, %21, %22, %23, %24, %25, %26, %27, %28, %29, %30, %31, %32, %33, %34, %35, %36, %37, %38, %39, %40, %41, %42, %43, %44, %45, %46, %47, %48, %49, %50, %51, %52, %53, %54, %55, %56, %57, %58, %59, %60, %61, %62, %63, %64, %65}, "
    "a, b, 1, 1, 1, 0, 1;\n"
    "wgmma.commit_group.sync.aligned;\nselp.u32 %0, 1, 0, p;\nselp.u32 %1, 1, 0, q;\n}"
    : "=r"(ok.x), "=r"(ok.y), "=f"(d[0]), "=f"(d[1]), "=f"(d[2]), "=f"(d[3]), "=f"(d[4]), "=f"(d[5]), "=f"(d[6]), "=f"(d[7]), "=f"(d[8]), "=f"(d[9]), "=f"(d[10]), "=f"(d[11]), "=f"(d[12]), "=f"(d[13]), "=f"(d[14]), "=f"(d[15]), "=f"(d[16]), "=f"(d[17]), "=f"(d[18]), "=f"(d[19]), "=f"(d[20]), "=f"(d[21]), "=f"(d[22]), "=f"(d[23]), "=f"(d[24]), "=f"(d[25]), "=f"(d[26]), "=f"(d[27]), "=f"(d[28]), "=f"(d[29]), "=f"(d[30]), "=f"(d[31]), "=f"(d[32]), "=f"(d[33]), "=f"(d[34]), "=f"(d[35]), "=f"(d[36]), "=f"(d[37]), "=f"(d[38]), "=f"(d[39]), "=f"(d[40]), "=f"(d[41]), "=f"(d[42]), "=f"(d[43]), "=f"(d[44]), "=f"(d[45]), "=f"(d[46]), "=f"(d[47]), "=f"(d[48]), "=f"(d[49]), "=f"(d[50]), "=f"(d[51]), "=f"(d[52]), "=f"(d[53]), "=f"(d[54]), "=f"(d[55]), "=f"(d[56]), "=f"(d[57]), "=f"(d[58]), "=f"(d[59]), "=f"(d[60]), "=f"(d[61]), "=f"(d[62]), "=f"(d[63]), "+r"(db)
    : "r"(da), "r"(h0), "r"(h1), "r"(one), "r"(b0), "r"(p0), "r"(b1), "r"(p1) : "memory");
  return ok;
}
template <int S> __device__ __forceinline__ uint2 wgmma_step128(float (&d)[S], uint32_t da, uint32_t& db, uint32_t h0, uint32_t h1, uint32_t one, uint32_t b0, uint32_t p0, uint32_t b1, uint32_t p1) {
  uint2 ok;
  asm volatile("{\n.reg .b64 a, b, s;\n.reg .b32 t, u;\n.reg .pred p, q;\nwgmma.fence.sync.aligned;\n"
    "mov.b32 t, %67;\n"
    "mov.b64 a, {t, %68};\nmov.b64 b, {%66, %69};\n"
    "wgmma.mma_async.sync.aligned.m64n128k16.f32.bf16.bf16 "
    "{%2, %3, %4, %5, %6, %7, %8, %9, %10, %11, %12, %13, %14, %15, %16, %17, %18, %19, %20, %21, %22, %23, %24, %25, %26, %27, %28, %29, %30, %31, %32, %33, %34, %35, %36, %37, %38, %39, %40, %41, %42, %43, %44, %45, %46, %47, %48, %49, %50, %51, %52, %53, %54, %55, %56, %57, %58, %59, %60, %61, %62, %63, %64, %65}, "
    "a, b, 1, 1, 1, 0, 1;\n"
    "mad.lo.u32 t, %70, 2, t;\nmad.lo.u32 %66, %70, 128, %66;\n"
    "mov.b64 a, {t, %68};\nmov.b64 b, {%66, %69};\n"
    "wgmma.mma_async.sync.aligned.m64n128k16.f32.bf16.bf16 "
    "{%2, %3, %4, %5, %6, %7, %8, %9, %10, %11, %12, %13, %14, %15, %16, %17, %18, %19, %20, %21, %22, %23, %24, %25, %26, %27, %28, %29, %30, %31, %32, %33, %34, %35, %36, %37, %38, %39, %40, %41, %42, %43, %44, %45, %46, %47, %48, %49, %50, %51, %52, %53, %54, %55, %56, %57, %58, %59, %60, %61, %62, %63, %64, %65}, "
    "a, b, 1, 1, 1, 0, 1;\n"
    "mad.lo.u32 t, %70, 2, t;\nmad.lo.u32 %66, %70, 128, %66;\n"
    "mov.b64 a, {t, %68};\nmov.b64 b, {%66, %69};\n"
    "wgmma.mma_async.sync.aligned.m64n128k16.f32.bf16.bf16 "
    "{%2, %3, %4, %5, %6, %7, %8, %9, %10, %11, %12, %13, %14, %15, %16, %17, %18, %19, %20, %21, %22, %23, %24, %25, %26, %27, %28, %29, %30, %31, %32, %33, %34, %35, %36, %37, %38, %39, %40, %41, %42, %43, %44, %45, %46, %47, %48, %49, %50, %51, %52, %53, %54, %55, %56, %57, %58, %59, %60, %61, %62, %63, %64, %65}, "
    "a, b, 1, 1, 1, 0, 1;\n"
    "mov.b64 s, {%72, %72};\nmbarrier.test_wait.shared::cta.b64 p, [%71], s;\nmov.b64 s, {%74, %74};\nmbarrier.test_wait.shared::cta.b64 q, [%73], s;\n"
    "mad.lo.u32 t, %70, 2, t;\nmad.lo.u32 %66, %70, 128, %66;\n"
    "mov.b64 a, {t, %68};\nmov.b64 b, {%66, %69};\n"
    "wgmma.mma_async.sync.aligned.m64n128k16.f32.bf16.bf16 "
    "{%2, %3, %4, %5, %6, %7, %8, %9, %10, %11, %12, %13, %14, %15, %16, %17, %18, %19, %20, %21, %22, %23, %24, %25, %26, %27, %28, %29, %30, %31, %32, %33, %34, %35, %36, %37, %38, %39, %40, %41, %42, %43, %44, %45, %46, %47, %48, %49, %50, %51, %52, %53, %54, %55, %56, %57, %58, %59, %60, %61, %62, %63, %64, %65}, "
    "a, b, 1, 1, 1, 0, 1;\n"
    "wgmma.commit_group.sync.aligned;\nselp.u32 %0, 1, 0, p;\nselp.u32 %1, 1, 0, q;\n}"
    : "=r"(ok.x), "=r"(ok.y), "+f"(d[0]), "+f"(d[1]), "+f"(d[2]), "+f"(d[3]), "+f"(d[4]), "+f"(d[5]), "+f"(d[6]), "+f"(d[7]), "+f"(d[8]), "+f"(d[9]), "+f"(d[10]), "+f"(d[11]), "+f"(d[12]), "+f"(d[13]), "+f"(d[14]), "+f"(d[15]), "+f"(d[16]), "+f"(d[17]), "+f"(d[18]), "+f"(d[19]), "+f"(d[20]), "+f"(d[21]), "+f"(d[22]), "+f"(d[23]), "+f"(d[24]), "+f"(d[25]), "+f"(d[26]), "+f"(d[27]), "+f"(d[28]), "+f"(d[29]), "+f"(d[30]), "+f"(d[31]), "+f"(d[32]), "+f"(d[33]), "+f"(d[34]), "+f"(d[35]), "+f"(d[36]), "+f"(d[37]), "+f"(d[38]), "+f"(d[39]), "+f"(d[40]), "+f"(d[41]), "+f"(d[42]), "+f"(d[43]), "+f"(d[44]), "+f"(d[45]), "+f"(d[46]), "+f"(d[47]), "+f"(d[48]), "+f"(d[49]), "+f"(d[50]), "+f"(d[51]), "+f"(d[52]), "+f"(d[53]), "+f"(d[54]), "+f"(d[55]), "+f"(d[56]), "+f"(d[57]), "+f"(d[58]), "+f"(d[59]), "+f"(d[60]), "+f"(d[61]), "+f"(d[62]), "+f"(d[63]), "+r"(db)
    : "r"(da), "r"(h0), "r"(h1), "r"(one), "r"(b0), "r"(p0), "r"(b1), "r"(p1) : "memory");
  return ok;
}
template <int S> __device__ __forceinline__ uint2 wgmma_first192(float (&d)[S], uint32_t da, uint32_t& db, uint32_t h0, uint32_t h1, uint32_t one, uint32_t b0, uint32_t p0, uint32_t b1, uint32_t p1) {
  uint2 ok;
  asm volatile("{\n.reg .b64 a, b, s;\n.reg .b32 t, u;\n.reg .pred p, q;\nwgmma.fence.sync.aligned;\n"
    "mov.b32 t, %99;\n"
    "mov.b64 a, {t, %100};\nmov.b64 b, {%98, %101};\n"
    "wgmma.mma_async.sync.aligned.m64n192k16.f32.bf16.bf16 "
    "{%2, %3, %4, %5, %6, %7, %8, %9, %10, %11, %12, %13, %14, %15, %16, %17, %18, %19, %20, %21, %22, %23, %24, %25, %26, %27, %28, %29, %30, %31, %32, %33, %34, %35, %36, %37, %38, %39, %40, %41, %42, %43, %44, %45, %46, %47, %48, %49, %50, %51, %52, %53, %54, %55, %56, %57, %58, %59, %60, %61, %62, %63, %64, %65, %66, %67, %68, %69, %70, %71, %72, %73, %74, %75, %76, %77, %78, %79, %80, %81, %82, %83, %84, %85, %86, %87, %88, %89, %90, %91, %92, %93, %94, %95, %96, %97}, "
    "a, b, 0, 1, 1, 0, 1;\n"
    "mad.lo.u32 t, %102, 2, t;\nmad.lo.u32 %98, %102, 128, %98;\n"
    "mov.b64 a, {t, %100};\nmov.b64 b, {%98, %101};\n"
    "wgmma.mma_async.sync.aligned.m64n192k16.f32.bf16.bf16 "
    "{%2, %3, %4, %5, %6, %7, %8, %9, %10, %11, %12, %13, %14, %15, %16, %17, %18, %19, %20, %21, %22, %23, %24, %25, %26, %27, %28, %29, %30, %31, %32, %33, %34, %35, %36, %37, %38, %39, %40, %41, %42, %43, %44, %45, %46, %47, %48, %49, %50, %51, %52, %53, %54, %55, %56, %57, %58, %59, %60, %61, %62, %63, %64, %65, %66, %67, %68, %69, %70, %71, %72, %73, %74, %75, %76, %77, %78, %79, %80, %81, %82, %83, %84, %85, %86, %87, %88, %89, %90, %91, %92, %93, %94, %95, %96, %97}, "
    "a, b, 1, 1, 1, 0, 1;\n"
    "mad.lo.u32 t, %102, 2, t;\nmad.lo.u32 %98, %102, 128, %98;\n"
    "mov.b64 a, {t, %100};\nmov.b64 b, {%98, %101};\n"
    "wgmma.mma_async.sync.aligned.m64n192k16.f32.bf16.bf16 "
    "{%2, %3, %4, %5, %6, %7, %8, %9, %10, %11, %12, %13, %14, %15, %16, %17, %18, %19, %20, %21, %22, %23, %24, %25, %26, %27, %28, %29, %30, %31, %32, %33, %34, %35, %36, %37, %38, %39, %40, %41, %42, %43, %44, %45, %46, %47, %48, %49, %50, %51, %52, %53, %54, %55, %56, %57, %58, %59, %60, %61, %62, %63, %64, %65, %66, %67, %68, %69, %70, %71, %72, %73, %74, %75, %76, %77, %78, %79, %80, %81, %82, %83, %84, %85, %86, %87, %88, %89, %90, %91, %92, %93, %94, %95, %96, %97}, "
    "a, b, 1, 1, 1, 0, 1;\n"
    "mov.b64 s, {%104, %104};\nmbarrier.test_wait.shared::cta.b64 p, [%103], s;\nmov.b64 s, {%106, %106};\nmbarrier.test_wait.shared::cta.b64 q, [%105], s;\n"
    "mad.lo.u32 t, %102, 2, t;\nmad.lo.u32 %98, %102, 128, %98;\n"
    "mov.b64 a, {t, %100};\nmov.b64 b, {%98, %101};\n"
    "wgmma.mma_async.sync.aligned.m64n192k16.f32.bf16.bf16 "
    "{%2, %3, %4, %5, %6, %7, %8, %9, %10, %11, %12, %13, %14, %15, %16, %17, %18, %19, %20, %21, %22, %23, %24, %25, %26, %27, %28, %29, %30, %31, %32, %33, %34, %35, %36, %37, %38, %39, %40, %41, %42, %43, %44, %45, %46, %47, %48, %49, %50, %51, %52, %53, %54, %55, %56, %57, %58, %59, %60, %61, %62, %63, %64, %65, %66, %67, %68, %69, %70, %71, %72, %73, %74, %75, %76, %77, %78, %79, %80, %81, %82, %83, %84, %85, %86, %87, %88, %89, %90, %91, %92, %93, %94, %95, %96, %97}, "
    "a, b, 1, 1, 1, 0, 1;\n"
    "wgmma.commit_group.sync.aligned;\nselp.u32 %0, 1, 0, p;\nselp.u32 %1, 1, 0, q;\n}"
    : "=r"(ok.x), "=r"(ok.y), "=f"(d[0]), "=f"(d[1]), "=f"(d[2]), "=f"(d[3]), "=f"(d[4]), "=f"(d[5]), "=f"(d[6]), "=f"(d[7]), "=f"(d[8]), "=f"(d[9]), "=f"(d[10]), "=f"(d[11]), "=f"(d[12]), "=f"(d[13]), "=f"(d[14]), "=f"(d[15]), "=f"(d[16]), "=f"(d[17]), "=f"(d[18]), "=f"(d[19]), "=f"(d[20]), "=f"(d[21]), "=f"(d[22]), "=f"(d[23]), "=f"(d[24]), "=f"(d[25]), "=f"(d[26]), "=f"(d[27]), "=f"(d[28]), "=f"(d[29]), "=f"(d[30]), "=f"(d[31]), "=f"(d[32]), "=f"(d[33]), "=f"(d[34]), "=f"(d[35]), "=f"(d[36]), "=f"(d[37]), "=f"(d[38]), "=f"(d[39]), "=f"(d[40]), "=f"(d[41]), "=f"(d[42]), "=f"(d[43]), "=f"(d[44]), "=f"(d[45]), "=f"(d[46]), "=f"(d[47]), "=f"(d[48]), "=f"(d[49]), "=f"(d[50]), "=f"(d[51]), "=f"(d[52]), "=f"(d[53]), "=f"(d[54]), "=f"(d[55]), "=f"(d[56]), "=f"(d[57]), "=f"(d[58]), "=f"(d[59]), "=f"(d[60]), "=f"(d[61]), "=f"(d[62]), "=f"(d[63]), "=f"(d[64]), "=f"(d[65]), "=f"(d[66]), "=f"(d[67]), "=f"(d[68]), "=f"(d[69]), "=f"(d[70]), "=f"(d[71]), "=f"(d[72]), "=f"(d[73]), "=f"(d[74]), "=f"(d[75]), "=f"(d[76]), "=f"(d[77]), "=f"(d[78]), "=f"(d[79]), "=f"(d[80]), "=f"(d[81]), "=f"(d[82]), "=f"(d[83]), "=f"(d[84]), "=f"(d[85]), "=f"(d[86]), "=f"(d[87]), "=f"(d[88]), "=f"(d[89]), "=f"(d[90]), "=f"(d[91]), "=f"(d[92]), "=f"(d[93]), "=f"(d[94]), "=f"(d[95]), "+r"(db)
    : "r"(da), "r"(h0), "r"(h1), "r"(one), "r"(b0), "r"(p0), "r"(b1), "r"(p1) : "memory");
  return ok;
}
template <int S> __device__ __forceinline__ uint2 wgmma_step192(float (&d)[S], uint32_t da, uint32_t& db, uint32_t h0, uint32_t h1, uint32_t one, uint32_t b0, uint32_t p0, uint32_t b1, uint32_t p1) {
  uint2 ok;
  asm volatile("{\n.reg .b64 a, b, s;\n.reg .b32 t, u;\n.reg .pred p, q;\nwgmma.fence.sync.aligned;\n"
    "mov.b32 t, %99;\n"
    "mov.b64 a, {t, %100};\nmov.b64 b, {%98, %101};\n"
    "wgmma.mma_async.sync.aligned.m64n192k16.f32.bf16.bf16 "
    "{%2, %3, %4, %5, %6, %7, %8, %9, %10, %11, %12, %13, %14, %15, %16, %17, %18, %19, %20, %21, %22, %23, %24, %25, %26, %27, %28, %29, %30, %31, %32, %33, %34, %35, %36, %37, %38, %39, %40, %41, %42, %43, %44, %45, %46, %47, %48, %49, %50, %51, %52, %53, %54, %55, %56, %57, %58, %59, %60, %61, %62, %63, %64, %65, %66, %67, %68, %69, %70, %71, %72, %73, %74, %75, %76, %77, %78, %79, %80, %81, %82, %83, %84, %85, %86, %87, %88, %89, %90, %91, %92, %93, %94, %95, %96, %97}, "
    "a, b, 1, 1, 1, 0, 1;\n"
    "mad.lo.u32 t, %102, 2, t;\nmad.lo.u32 %98, %102, 128, %98;\n"
    "mov.b64 a, {t, %100};\nmov.b64 b, {%98, %101};\n"
    "wgmma.mma_async.sync.aligned.m64n192k16.f32.bf16.bf16 "
    "{%2, %3, %4, %5, %6, %7, %8, %9, %10, %11, %12, %13, %14, %15, %16, %17, %18, %19, %20, %21, %22, %23, %24, %25, %26, %27, %28, %29, %30, %31, %32, %33, %34, %35, %36, %37, %38, %39, %40, %41, %42, %43, %44, %45, %46, %47, %48, %49, %50, %51, %52, %53, %54, %55, %56, %57, %58, %59, %60, %61, %62, %63, %64, %65, %66, %67, %68, %69, %70, %71, %72, %73, %74, %75, %76, %77, %78, %79, %80, %81, %82, %83, %84, %85, %86, %87, %88, %89, %90, %91, %92, %93, %94, %95, %96, %97}, "
    "a, b, 1, 1, 1, 0, 1;\n"
    "mad.lo.u32 t, %102, 2, t;\nmad.lo.u32 %98, %102, 128, %98;\n"
    "mov.b64 a, {t, %100};\nmov.b64 b, {%98, %101};\n"
    "wgmma.mma_async.sync.aligned.m64n192k16.f32.bf16.bf16 "
    "{%2, %3, %4, %5, %6, %7, %8, %9, %10, %11, %12, %13, %14, %15, %16, %17, %18, %19, %20, %21, %22, %23, %24, %25, %26, %27, %28, %29, %30, %31, %32, %33, %34, %35, %36, %37, %38, %39, %40, %41, %42, %43, %44, %45, %46, %47, %48, %49, %50, %51, %52, %53, %54, %55, %56, %57, %58, %59, %60, %61, %62, %63, %64, %65, %66, %67, %68, %69, %70, %71, %72, %73, %74, %75, %76, %77, %78, %79, %80, %81, %82, %83, %84, %85, %86, %87, %88, %89, %90, %91, %92, %93, %94, %95, %96, %97}, "
    "a, b, 1, 1, 1, 0, 1;\n"
    "mov.b64 s, {%104, %104};\nmbarrier.test_wait.shared::cta.b64 p, [%103], s;\nmov.b64 s, {%106, %106};\nmbarrier.test_wait.shared::cta.b64 q, [%105], s;\n"
    "mad.lo.u32 t, %102, 2, t;\nmad.lo.u32 %98, %102, 128, %98;\n"
    "mov.b64 a, {t, %100};\nmov.b64 b, {%98, %101};\n"
    "wgmma.mma_async.sync.aligned.m64n192k16.f32.bf16.bf16 "
    "{%2, %3, %4, %5, %6, %7, %8, %9, %10, %11, %12, %13, %14, %15, %16, %17, %18, %19, %20, %21, %22, %23, %24, %25, %26, %27, %28, %29, %30, %31, %32, %33, %34, %35, %36, %37, %38, %39, %40, %41, %42, %43, %44, %45, %46, %47, %48, %49, %50, %51, %52, %53, %54, %55, %56, %57, %58, %59, %60, %61, %62, %63, %64, %65, %66, %67, %68, %69, %70, %71, %72, %73, %74, %75, %76, %77, %78, %79, %80, %81, %82, %83, %84, %85, %86, %87, %88, %89, %90, %91, %92, %93, %94, %95, %96, %97}, "
    "a, b, 1, 1, 1, 0, 1;\n"
    "wgmma.commit_group.sync.aligned;\nselp.u32 %0, 1, 0, p;\nselp.u32 %1, 1, 0, q;\n}"
    : "=r"(ok.x), "=r"(ok.y), "+f"(d[0]), "+f"(d[1]), "+f"(d[2]), "+f"(d[3]), "+f"(d[4]), "+f"(d[5]), "+f"(d[6]), "+f"(d[7]), "+f"(d[8]), "+f"(d[9]), "+f"(d[10]), "+f"(d[11]), "+f"(d[12]), "+f"(d[13]), "+f"(d[14]), "+f"(d[15]), "+f"(d[16]), "+f"(d[17]), "+f"(d[18]), "+f"(d[19]), "+f"(d[20]), "+f"(d[21]), "+f"(d[22]), "+f"(d[23]), "+f"(d[24]), "+f"(d[25]), "+f"(d[26]), "+f"(d[27]), "+f"(d[28]), "+f"(d[29]), "+f"(d[30]), "+f"(d[31]), "+f"(d[32]), "+f"(d[33]), "+f"(d[34]), "+f"(d[35]), "+f"(d[36]), "+f"(d[37]), "+f"(d[38]), "+f"(d[39]), "+f"(d[40]), "+f"(d[41]), "+f"(d[42]), "+f"(d[43]), "+f"(d[44]), "+f"(d[45]), "+f"(d[46]), "+f"(d[47]), "+f"(d[48]), "+f"(d[49]), "+f"(d[50]), "+f"(d[51]), "+f"(d[52]), "+f"(d[53]), "+f"(d[54]), "+f"(d[55]), "+f"(d[56]), "+f"(d[57]), "+f"(d[58]), "+f"(d[59]), "+f"(d[60]), "+f"(d[61]), "+f"(d[62]), "+f"(d[63]), "+f"(d[64]), "+f"(d[65]), "+f"(d[66]), "+f"(d[67]), "+f"(d[68]), "+f"(d[69]), "+f"(d[70]), "+f"(d[71]), "+f"(d[72]), "+f"(d[73]), "+f"(d[74]), "+f"(d[75]), "+f"(d[76]), "+f"(d[77]), "+f"(d[78]), "+f"(d[79]), "+f"(d[80]), "+f"(d[81]), "+f"(d[82]), "+f"(d[83]), "+f"(d[84]), "+f"(d[85]), "+f"(d[86]), "+f"(d[87]), "+f"(d[88]), "+f"(d[89]), "+f"(d[90]), "+f"(d[91]), "+f"(d[92]), "+f"(d[93]), "+f"(d[94]), "+f"(d[95]), "+r"(db)
    : "r"(da), "r"(h0), "r"(h1), "r"(one), "r"(b0), "r"(p0), "r"(b1), "r"(p1) : "memory");
  return ok;
}
template <int S> __device__ __forceinline__ uint2 wgmma_first256(float (&d)[S], uint32_t da, uint32_t& db, uint32_t h0, uint32_t h1, uint32_t one, uint32_t b0, uint32_t p0, uint32_t b1, uint32_t p1) {
  uint2 ok;
  asm volatile("{\n.reg .b64 a, b, s;\n.reg .b32 t, u;\n.reg .pred p, q;\nwgmma.fence.sync.aligned;\n"
    "mov.b32 t, %131;\n"
    "mov.b64 a, {t, %132};\nmov.b64 b, {%130, %133};\n"
    "wgmma.mma_async.sync.aligned.m64n256k16.f32.bf16.bf16 "
    "{%2, %3, %4, %5, %6, %7, %8, %9, %10, %11, %12, %13, %14, %15, %16, %17, %18, %19, %20, %21, %22, %23, %24, %25, %26, %27, %28, %29, %30, %31, %32, %33, %34, %35, %36, %37, %38, %39, %40, %41, %42, %43, %44, %45, %46, %47, %48, %49, %50, %51, %52, %53, %54, %55, %56, %57, %58, %59, %60, %61, %62, %63, %64, %65, %66, %67, %68, %69, %70, %71, %72, %73, %74, %75, %76, %77, %78, %79, %80, %81, %82, %83, %84, %85, %86, %87, %88, %89, %90, %91, %92, %93, %94, %95, %96, %97, %98, %99, %100, %101, %102, %103, %104, %105, %106, %107, %108, %109, %110, %111, %112, %113, %114, %115, %116, %117, %118, %119, %120, %121, %122, %123, %124, %125, %126, %127, %128, %129}, "
    "a, b, 0, 1, 1, 0, 1;\n"
    "mad.lo.u32 t, %134, 2, t;\nmad.lo.u32 %130, %134, 128, %130;\n"
    "mov.b64 a, {t, %132};\nmov.b64 b, {%130, %133};\n"
    "wgmma.mma_async.sync.aligned.m64n256k16.f32.bf16.bf16 "
    "{%2, %3, %4, %5, %6, %7, %8, %9, %10, %11, %12, %13, %14, %15, %16, %17, %18, %19, %20, %21, %22, %23, %24, %25, %26, %27, %28, %29, %30, %31, %32, %33, %34, %35, %36, %37, %38, %39, %40, %41, %42, %43, %44, %45, %46, %47, %48, %49, %50, %51, %52, %53, %54, %55, %56, %57, %58, %59, %60, %61, %62, %63, %64, %65, %66, %67, %68, %69, %70, %71, %72, %73, %74, %75, %76, %77, %78, %79, %80, %81, %82, %83, %84, %85, %86, %87, %88, %89, %90, %91, %92, %93, %94, %95, %96, %97, %98, %99, %100, %101, %102, %103, %104, %105, %106, %107, %108, %109, %110, %111, %112, %113, %114, %115, %116, %117, %118, %119, %120, %121, %122, %123, %124, %125, %126, %127, %128, %129}, "
    "a, b, 1, 1, 1, 0, 1;\n"
    "mov.b64 s, {%136, %136};\nmbarrier.test_wait.shared::cta.b64 p, [%135], s;\nmov.b64 s, {%138, %138};\nmbarrier.test_wait.shared::cta.b64 q, [%137], s;\n"
    "mad.lo.u32 t, %134, 2, t;\nmad.lo.u32 %130, %134, 128, %130;\n"
    "mov.b64 a, {t, %132};\nmov.b64 b, {%130, %133};\n"
    "wgmma.mma_async.sync.aligned.m64n256k16.f32.bf16.bf16 "
    "{%2, %3, %4, %5, %6, %7, %8, %9, %10, %11, %12, %13, %14, %15, %16, %17, %18, %19, %20, %21, %22, %23, %24, %25, %26, %27, %28, %29, %30, %31, %32, %33, %34, %35, %36, %37, %38, %39, %40, %41, %42, %43, %44, %45, %46, %47, %48, %49, %50, %51, %52, %53, %54, %55, %56, %57, %58, %59, %60, %61, %62, %63, %64, %65, %66, %67, %68, %69, %70, %71, %72, %73, %74, %75, %76, %77, %78, %79, %80, %81, %82, %83, %84, %85, %86, %87, %88, %89, %90, %91, %92, %93, %94, %95, %96, %97, %98, %99, %100, %101, %102, %103, %104, %105, %106, %107, %108, %109, %110, %111, %112, %113, %114, %115, %116, %117, %118, %119, %120, %121, %122, %123, %124, %125, %126, %127, %128, %129}, "
    "a, b, 1, 1, 1, 0, 1;\n"
    "mad.lo.u32 t, %134, 2, t;\nmad.lo.u32 %130, %134, 128, %130;\n"
    "mov.b64 a, {t, %132};\nmov.b64 b, {%130, %133};\n"
    "wgmma.mma_async.sync.aligned.m64n256k16.f32.bf16.bf16 "
    "{%2, %3, %4, %5, %6, %7, %8, %9, %10, %11, %12, %13, %14, %15, %16, %17, %18, %19, %20, %21, %22, %23, %24, %25, %26, %27, %28, %29, %30, %31, %32, %33, %34, %35, %36, %37, %38, %39, %40, %41, %42, %43, %44, %45, %46, %47, %48, %49, %50, %51, %52, %53, %54, %55, %56, %57, %58, %59, %60, %61, %62, %63, %64, %65, %66, %67, %68, %69, %70, %71, %72, %73, %74, %75, %76, %77, %78, %79, %80, %81, %82, %83, %84, %85, %86, %87, %88, %89, %90, %91, %92, %93, %94, %95, %96, %97, %98, %99, %100, %101, %102, %103, %104, %105, %106, %107, %108, %109, %110, %111, %112, %113, %114, %115, %116, %117, %118, %119, %120, %121, %122, %123, %124, %125, %126, %127, %128, %129}, "
    "a, b, 1, 1, 1, 0, 1;\n"
    "wgmma.commit_group.sync.aligned;\nselp.u32 %0, 1, 0, p;\nselp.u32 %1, 1, 0, q;\n}"
    : "=r"(ok.x), "=r"(ok.y), "=f"(d[0]), "=f"(d[1]), "=f"(d[2]), "=f"(d[3]), "=f"(d[4]), "=f"(d[5]), "=f"(d[6]), "=f"(d[7]), "=f"(d[8]), "=f"(d[9]), "=f"(d[10]), "=f"(d[11]), "=f"(d[12]), "=f"(d[13]), "=f"(d[14]), "=f"(d[15]), "=f"(d[16]), "=f"(d[17]), "=f"(d[18]), "=f"(d[19]), "=f"(d[20]), "=f"(d[21]), "=f"(d[22]), "=f"(d[23]), "=f"(d[24]), "=f"(d[25]), "=f"(d[26]), "=f"(d[27]), "=f"(d[28]), "=f"(d[29]), "=f"(d[30]), "=f"(d[31]), "=f"(d[32]), "=f"(d[33]), "=f"(d[34]), "=f"(d[35]), "=f"(d[36]), "=f"(d[37]), "=f"(d[38]), "=f"(d[39]), "=f"(d[40]), "=f"(d[41]), "=f"(d[42]), "=f"(d[43]), "=f"(d[44]), "=f"(d[45]), "=f"(d[46]), "=f"(d[47]), "=f"(d[48]), "=f"(d[49]), "=f"(d[50]), "=f"(d[51]), "=f"(d[52]), "=f"(d[53]), "=f"(d[54]), "=f"(d[55]), "=f"(d[56]), "=f"(d[57]), "=f"(d[58]), "=f"(d[59]), "=f"(d[60]), "=f"(d[61]), "=f"(d[62]), "=f"(d[63]), "=f"(d[64]), "=f"(d[65]), "=f"(d[66]), "=f"(d[67]), "=f"(d[68]), "=f"(d[69]), "=f"(d[70]), "=f"(d[71]), "=f"(d[72]), "=f"(d[73]), "=f"(d[74]), "=f"(d[75]), "=f"(d[76]), "=f"(d[77]), "=f"(d[78]), "=f"(d[79]), "=f"(d[80]), "=f"(d[81]), "=f"(d[82]), "=f"(d[83]), "=f"(d[84]), "=f"(d[85]), "=f"(d[86]), "=f"(d[87]), "=f"(d[88]), "=f"(d[89]), "=f"(d[90]), "=f"(d[91]), "=f"(d[92]), "=f"(d[93]), "=f"(d[94]), "=f"(d[95]), "=f"(d[96]), "=f"(d[97]), "=f"(d[98]), "=f"(d[99]), "=f"(d[100]), "=f"(d[101]), "=f"(d[102]), "=f"(d[103]), "=f"(d[104]), "=f"(d[105]), "=f"(d[106]), "=f"(d[107]), "=f"(d[108]), "=f"(d[109]), "=f"(d[110]), "=f"(d[111]), "=f"(d[112]), "=f"(d[113]), "=f"(d[114]), "=f"(d[115]), "=f"(d[116]), "=f"(d[117]), "=f"(d[118]), "=f"(d[119]), "=f"(d[120]), "=f"(d[121]), "=f"(d[122]), "=f"(d[123]), "=f"(d[124]), "=f"(d[125]), "=f"(d[126]), "=f"(d[127]), "+r"(db)
    : "r"(da), "r"(h0), "r"(h1), "r"(one), "r"(b0), "r"(p0), "r"(b1), "r"(p1) : "memory");
  return ok;
}
template <int S> __device__ __forceinline__ uint2 wgmma_step256(float (&d)[S], uint32_t da, uint32_t& db, uint32_t h0, uint32_t h1, uint32_t one, uint32_t b0, uint32_t p0, uint32_t b1, uint32_t p1) {
  uint2 ok;
  asm volatile("{\n.reg .b64 a, b, s;\n.reg .b32 t, u;\n.reg .pred p, q;\nwgmma.fence.sync.aligned;\n"
    "mov.b32 t, %131;\n"
    "mov.b64 a, {t, %132};\nmov.b64 b, {%130, %133};\n"
    "wgmma.mma_async.sync.aligned.m64n256k16.f32.bf16.bf16 "
    "{%2, %3, %4, %5, %6, %7, %8, %9, %10, %11, %12, %13, %14, %15, %16, %17, %18, %19, %20, %21, %22, %23, %24, %25, %26, %27, %28, %29, %30, %31, %32, %33, %34, %35, %36, %37, %38, %39, %40, %41, %42, %43, %44, %45, %46, %47, %48, %49, %50, %51, %52, %53, %54, %55, %56, %57, %58, %59, %60, %61, %62, %63, %64, %65, %66, %67, %68, %69, %70, %71, %72, %73, %74, %75, %76, %77, %78, %79, %80, %81, %82, %83, %84, %85, %86, %87, %88, %89, %90, %91, %92, %93, %94, %95, %96, %97, %98, %99, %100, %101, %102, %103, %104, %105, %106, %107, %108, %109, %110, %111, %112, %113, %114, %115, %116, %117, %118, %119, %120, %121, %122, %123, %124, %125, %126, %127, %128, %129}, "
    "a, b, 1, 1, 1, 0, 1;\n"
    "mad.lo.u32 t, %134, 2, t;\nmad.lo.u32 %130, %134, 128, %130;\n"
    "mov.b64 a, {t, %132};\nmov.b64 b, {%130, %133};\n"
    "wgmma.mma_async.sync.aligned.m64n256k16.f32.bf16.bf16 "
    "{%2, %3, %4, %5, %6, %7, %8, %9, %10, %11, %12, %13, %14, %15, %16, %17, %18, %19, %20, %21, %22, %23, %24, %25, %26, %27, %28, %29, %30, %31, %32, %33, %34, %35, %36, %37, %38, %39, %40, %41, %42, %43, %44, %45, %46, %47, %48, %49, %50, %51, %52, %53, %54, %55, %56, %57, %58, %59, %60, %61, %62, %63, %64, %65, %66, %67, %68, %69, %70, %71, %72, %73, %74, %75, %76, %77, %78, %79, %80, %81, %82, %83, %84, %85, %86, %87, %88, %89, %90, %91, %92, %93, %94, %95, %96, %97, %98, %99, %100, %101, %102, %103, %104, %105, %106, %107, %108, %109, %110, %111, %112, %113, %114, %115, %116, %117, %118, %119, %120, %121, %122, %123, %124, %125, %126, %127, %128, %129}, "
    "a, b, 1, 1, 1, 0, 1;\n"
    "mov.b64 s, {%136, %136};\nmbarrier.test_wait.shared::cta.b64 p, [%135], s;\nmov.b64 s, {%138, %138};\nmbarrier.test_wait.shared::cta.b64 q, [%137], s;\n"
    "mad.lo.u32 t, %134, 2, t;\nmad.lo.u32 %130, %134, 128, %130;\n"
    "mov.b64 a, {t, %132};\nmov.b64 b, {%130, %133};\n"
    "wgmma.mma_async.sync.aligned.m64n256k16.f32.bf16.bf16 "
    "{%2, %3, %4, %5, %6, %7, %8, %9, %10, %11, %12, %13, %14, %15, %16, %17, %18, %19, %20, %21, %22, %23, %24, %25, %26, %27, %28, %29, %30, %31, %32, %33, %34, %35, %36, %37, %38, %39, %40, %41, %42, %43, %44, %45, %46, %47, %48, %49, %50, %51, %52, %53, %54, %55, %56, %57, %58, %59, %60, %61, %62, %63, %64, %65, %66, %67, %68, %69, %70, %71, %72, %73, %74, %75, %76, %77, %78, %79, %80, %81, %82, %83, %84, %85, %86, %87, %88, %89, %90, %91, %92, %93, %94, %95, %96, %97, %98, %99, %100, %101, %102, %103, %104, %105, %106, %107, %108, %109, %110, %111, %112, %113, %114, %115, %116, %117, %118, %119, %120, %121, %122, %123, %124, %125, %126, %127, %128, %129}, "
    "a, b, 1, 1, 1, 0, 1;\n"
    "mad.lo.u32 t, %134, 2, t;\nmad.lo.u32 %130, %134, 128, %130;\n"
    "mov.b64 a, {t, %132};\nmov.b64 b, {%130, %133};\n"
    "wgmma.mma_async.sync.aligned.m64n256k16.f32.bf16.bf16 "
    "{%2, %3, %4, %5, %6, %7, %8, %9, %10, %11, %12, %13, %14, %15, %16, %17, %18, %19, %20, %21, %22, %23, %24, %25, %26, %27, %28, %29, %30, %31, %32, %33, %34, %35, %36, %37, %38, %39, %40, %41, %42, %43, %44, %45, %46, %47, %48, %49, %50, %51, %52, %53, %54, %55, %56, %57, %58, %59, %60, %61, %62, %63, %64, %65, %66, %67, %68, %69, %70, %71, %72, %73, %74, %75, %76, %77, %78, %79, %80, %81, %82, %83, %84, %85, %86, %87, %88, %89, %90, %91, %92, %93, %94, %95, %96, %97, %98, %99, %100, %101, %102, %103, %104, %105, %106, %107, %108, %109, %110, %111, %112, %113, %114, %115, %116, %117, %118, %119, %120, %121, %122, %123, %124, %125, %126, %127, %128, %129}, "
    "a, b, 1, 1, 1, 0, 1;\n"
    "wgmma.commit_group.sync.aligned;\nselp.u32 %0, 1, 0, p;\nselp.u32 %1, 1, 0, q;\n}"
    : "=r"(ok.x), "=r"(ok.y), "+f"(d[0]), "+f"(d[1]), "+f"(d[2]), "+f"(d[3]), "+f"(d[4]), "+f"(d[5]), "+f"(d[6]), "+f"(d[7]), "+f"(d[8]), "+f"(d[9]), "+f"(d[10]), "+f"(d[11]), "+f"(d[12]), "+f"(d[13]), "+f"(d[14]), "+f"(d[15]), "+f"(d[16]), "+f"(d[17]), "+f"(d[18]), "+f"(d[19]), "+f"(d[20]), "+f"(d[21]), "+f"(d[22]), "+f"(d[23]), "+f"(d[24]), "+f"(d[25]), "+f"(d[26]), "+f"(d[27]), "+f"(d[28]), "+f"(d[29]), "+f"(d[30]), "+f"(d[31]), "+f"(d[32]), "+f"(d[33]), "+f"(d[34]), "+f"(d[35]), "+f"(d[36]), "+f"(d[37]), "+f"(d[38]), "+f"(d[39]), "+f"(d[40]), "+f"(d[41]), "+f"(d[42]), "+f"(d[43]), "+f"(d[44]), "+f"(d[45]), "+f"(d[46]), "+f"(d[47]), "+f"(d[48]), "+f"(d[49]), "+f"(d[50]), "+f"(d[51]), "+f"(d[52]), "+f"(d[53]), "+f"(d[54]), "+f"(d[55]), "+f"(d[56]), "+f"(d[57]), "+f"(d[58]), "+f"(d[59]), "+f"(d[60]), "+f"(d[61]), "+f"(d[62]), "+f"(d[63]), "+f"(d[64]), "+f"(d[65]), "+f"(d[66]), "+f"(d[67]), "+f"(d[68]), "+f"(d[69]), "+f"(d[70]), "+f"(d[71]), "+f"(d[72]), "+f"(d[73]), "+f"(d[74]), "+f"(d[75]), "+f"(d[76]), "+f"(d[77]), "+f"(d[78]), "+f"(d[79]), "+f"(d[80]), "+f"(d[81]), "+f"(d[82]), "+f"(d[83]), "+f"(d[84]), "+f"(d[85]), "+f"(d[86]), "+f"(d[87]), "+f"(d[88]), "+f"(d[89]), "+f"(d[90]), "+f"(d[91]), "+f"(d[92]), "+f"(d[93]), "+f"(d[94]), "+f"(d[95]), "+f"(d[96]), "+f"(d[97]), "+f"(d[98]), "+f"(d[99]), "+f"(d[100]), "+f"(d[101]), "+f"(d[102]), "+f"(d[103]), "+f"(d[104]), "+f"(d[105]), "+f"(d[106]), "+f"(d[107]), "+f"(d[108]), "+f"(d[109]), "+f"(d[110]), "+f"(d[111]), "+f"(d[112]), "+f"(d[113]), "+f"(d[114]), "+f"(d[115]), "+f"(d[116]), "+f"(d[117]), "+f"(d[118]), "+f"(d[119]), "+f"(d[120]), "+f"(d[121]), "+f"(d[122]), "+f"(d[123]), "+f"(d[124]), "+f"(d[125]), "+f"(d[126]), "+f"(d[127]), "+r"(db)
    : "r"(da), "r"(h0), "r"(h1), "r"(one), "r"(b0), "r"(p0), "r"(b1), "r"(p1) : "memory");
  return ok;
}
template <int S> __device__ __forceinline__ void wgmma_aug192(float (&d)[S], uint32_t a0, uint32_t a1, uint32_t db, uint32_t h1) {
  asm volatile("{\n.reg .b64 b;\n.reg .b32 z;\nmov.b32 z, 0;\n"
    "mov.b64 b, {%98, %99};\nwgmma.fence.sync.aligned;\n"
    "wgmma.mma_async.sync.aligned.m64n192k16.f32.bf16.bf16 "
    "{%0, %1, %2, %3, %4, %5, %6, %7, %8, %9, %10, %11, %12, %13, %14, %15, %16, %17, %18, %19, %20, %21, %22, %23, %24, %25, %26, %27, %28, %29, %30, %31, %32, %33, %34, %35, %36, %37, %38, %39, %40, %41, %42, %43, %44, %45, %46, %47, %48, %49, %50, %51, %52, %53, %54, %55, %56, %57, %58, %59, %60, %61, %62, %63, %64, %65, %66, %67, %68, %69, %70, %71, %72, %73, %74, %75, %76, %77, %78, %79, %80, %81, %82, %83, %84, %85, %86, %87, %88, %89, %90, %91, %92, %93, %94, %95}, "
    "{%96, %97, z, z}, b, 1, 1, 1, 1;\n"
    "wgmma.commit_group.sync.aligned;\n}"
    : "+f"(d[0]), "+f"(d[1]), "+f"(d[2]), "+f"(d[3]), "+f"(d[4]), "+f"(d[5]), "+f"(d[6]), "+f"(d[7]), "+f"(d[8]), "+f"(d[9]), "+f"(d[10]), "+f"(d[11]), "+f"(d[12]), "+f"(d[13]), "+f"(d[14]), "+f"(d[15]), "+f"(d[16]), "+f"(d[17]), "+f"(d[18]), "+f"(d[19]), "+f"(d[20]), "+f"(d[21]), "+f"(d[22]), "+f"(d[23]), "+f"(d[24]), "+f"(d[25]), "+f"(d[26]), "+f"(d[27]), "+f"(d[28]), "+f"(d[29]), "+f"(d[30]), "+f"(d[31]), "+f"(d[32]), "+f"(d[33]), "+f"(d[34]), "+f"(d[35]), "+f"(d[36]), "+f"(d[37]), "+f"(d[38]), "+f"(d[39]), "+f"(d[40]), "+f"(d[41]), "+f"(d[42]), "+f"(d[43]), "+f"(d[44]), "+f"(d[45]), "+f"(d[46]), "+f"(d[47]), "+f"(d[48]), "+f"(d[49]), "+f"(d[50]), "+f"(d[51]), "+f"(d[52]), "+f"(d[53]), "+f"(d[54]), "+f"(d[55]), "+f"(d[56]), "+f"(d[57]), "+f"(d[58]), "+f"(d[59]), "+f"(d[60]), "+f"(d[61]), "+f"(d[62]), "+f"(d[63]), "+f"(d[64]), "+f"(d[65]), "+f"(d[66]), "+f"(d[67]), "+f"(d[68]), "+f"(d[69]), "+f"(d[70]), "+f"(d[71]), "+f"(d[72]), "+f"(d[73]), "+f"(d[74]), "+f"(d[75]), "+f"(d[76]), "+f"(d[77]), "+f"(d[78]), "+f"(d[79]), "+f"(d[80]), "+f"(d[81]), "+f"(d[82]), "+f"(d[83]), "+f"(d[84]), "+f"(d[85]), "+f"(d[86]), "+f"(d[87]), "+f"(d[88]), "+f"(d[89]), "+f"(d[90]), "+f"(d[91]), "+f"(d[92]), "+f"(d[93]), "+f"(d[94]), "+f"(d[95])
    : "r"(a0), "r"(a1), "r"(db), "r"(h1) : "memory");
}
template <int S> __device__ __forceinline__ void wgmma_aug256(float (&d)[S], uint32_t a0, uint32_t a1, uint32_t db, uint32_t h1) {
  asm volatile("{\n.reg .b64 b;\n.reg .b32 z;\nmov.b32 z, 0;\n"
    "mov.b64 b, {%130, %131};\nwgmma.fence.sync.aligned;\n"
    "wgmma.mma_async.sync.aligned.m64n256k16.f32.bf16.bf16 "
    "{%0, %1, %2, %3, %4, %5, %6, %7, %8, %9, %10, %11, %12, %13, %14, %15, %16, %17, %18, %19, %20, %21, %22, %23, %24, %25, %26, %27, %28, %29, %30, %31, %32, %33, %34, %35, %36, %37, %38, %39, %40, %41, %42, %43, %44, %45, %46, %47, %48, %49, %50, %51, %52, %53, %54, %55, %56, %57, %58, %59, %60, %61, %62, %63, %64, %65, %66, %67, %68, %69, %70, %71, %72, %73, %74, %75, %76, %77, %78, %79, %80, %81, %82, %83, %84, %85, %86, %87, %88, %89, %90, %91, %92, %93, %94, %95, %96, %97, %98, %99, %100, %101, %102, %103, %104, %105, %106, %107, %108, %109, %110, %111, %112, %113, %114, %115, %116, %117, %118, %119, %120, %121, %122, %123, %124, %125, %126, %127}, "
    "{%128, %129, z, z}, b, 1, 1, 1, 1;\n"
    "wgmma.commit_group.sync.aligned;\n}"
    : "+f"(d[0]), "+f"(d[1]), "+f"(d[2]), "+f"(d[3]), "+f"(d[4]), "+f"(d[5]), "+f"(d[6]), "+f"(d[7]), "+f"(d[8]), "+f"(d[9]), "+f"(d[10]), "+f"(d[11]), "+f"(d[12]), "+f"(d[13]), "+f"(d[14]), "+f"(d[15]), "+f"(d[16]), "+f"(d[17]), "+f"(d[18]), "+f"(d[19]), "+f"(d[20]), "+f"(d[21]), "+f"(d[22]), "+f"(d[23]), "+f"(d[24]), "+f"(d[25]), "+f"(d[26]), "+f"(d[27]), "+f"(d[28]), "+f"(d[29]), "+f"(d[30]), "+f"(d[31]), "+f"(d[32]), "+f"(d[33]), "+f"(d[34]), "+f"(d[35]), "+f"(d[36]), "+f"(d[37]), "+f"(d[38]), "+f"(d[39]), "+f"(d[40]), "+f"(d[41]), "+f"(d[42]), "+f"(d[43]), "+f"(d[44]), "+f"(d[45]), "+f"(d[46]), "+f"(d[47]), "+f"(d[48]), "+f"(d[49]), "+f"(d[50]), "+f"(d[51]), "+f"(d[52]), "+f"(d[53]), "+f"(d[54]), "+f"(d[55]), "+f"(d[56]), "+f"(d[57]), "+f"(d[58]), "+f"(d[59]), "+f"(d[60]), "+f"(d[61]), "+f"(d[62]), "+f"(d[63]), "+f"(d[64]), "+f"(d[65]), "+f"(d[66]), "+f"(d[67]), "+f"(d[68]), "+f"(d[69]), "+f"(d[70]), "+f"(d[71]), "+f"(d[72]), "+f"(d[73]), "+f"(d[74]), "+f"(d[75]), "+f"(d[76]), "+f"(d[77]), "+f"(d[78]), "+f"(d[79]), "+f"(d[80]), "+f"(d[81]), "+f"(d[82]), "+f"(d[83]), "+f"(d[84]), "+f"(d[85]), "+f"(d[86]), "+f"(d[87]), "+f"(d[88]), "+f"(d[89]), "+f"(d[90]), "+f"(d[91]), "+f"(d[92]), "+f"(d[93]), "+f"(d[94]), "+f"(d[95]), "+f"(d[96]), "+f"(d[97]), "+f"(d[98]), "+f"(d[99]), "+f"(d[100]), "+f"(d[101]), "+f"(d[102]), "+f"(d[103]), "+f"(d[104]), "+f"(d[105]), "+f"(d[106]), "+f"(d[107]), "+f"(d[108]), "+f"(d[109]), "+f"(d[110]), "+f"(d[111]), "+f"(d[112]), "+f"(d[113]), "+f"(d[114]), "+f"(d[115]), "+f"(d[116]), "+f"(d[117]), "+f"(d[118]), "+f"(d[119]), "+f"(d[120]), "+f"(d[121]), "+f"(d[122]), "+f"(d[123]), "+f"(d[124]), "+f"(d[125]), "+f"(d[126]), "+f"(d[127])
    : "r"(a0), "r"(a1), "r"(db), "r"(h1) : "memory");
}

__device__ __forceinline__ uint32_t clock32() { uint32_t c; asm volatile("mov.u32 %0, %%clock;" : "=r"(c)); return c; }
__device__ __forceinline__ void spin_until(uint32_t c) {
  asm volatile("{\n.reg .pred p;\n.reg .s32 t;\nLAB_WAIT:\nmov.u32 t, %%clock;\nsub.s32 t, t, %0;\nsetp.lt.s32 p, t, 0;\n@p bra.uni LAB_WAIT;\n}" ::"r"(c) : "memory");
}
struct Nop { __device__ __forceinline__ void operator()(int) const {} };
template <int V> struct IC { static constexpr int v = V; };
struct Pipe {
  uint32_t db, g8, a8, pa, tph, aend, curB, curA, prevB, prevA, bo, so, sph, h0, h1, one;
  uint2 nx;
  int w; bool l0;
  __device__ __forceinline__ int lane() const { return LSO ? (so >> 5) & 31 : threadIdx.x & 31; }
  __device__ __forceinline__ void adv_a() { a8 += 8; pa += PA1; if (a8 == aend) a8 -= NA * 8; }
  __device__ __forceinline__ uint32_t take() { const uint32_t a = SB + OFF_A + a8 * 1024; adv_a(); return a; }
  __device__ __forceinline__ uint32_t ahead(int d) const { uint32_t ls = a8 + d * 8; if (ls >= aend) ls -= NA * 8; return SB + OFF_A + ls * 1024; }
  __device__ __forceinline__ uint32_t wait_ahead(int d) {
    uint32_t ls = a8 + d * 8;
    if (ls >= aend) ls -= NA * 8;
    mbar_spin31(SB + BAR_FULLA + ls, pa + d * PA1);
    return SB + OFF_A + ls * 1024;
  }
  template <int N, bool FIRST, int S> __device__ __forceinline__ uint2 iss(float (&acc)[S], bool skip) {
    const uint32_t da = DA0 + a8 * 64;
    if (!FIRST) { if (N != 192) db &= ~0x2000u; else if (db == DB0 + 15 * 512) db = DB0; }
    prevB = curB; prevA = curA;
    curB = g8 & 56; curA = a8;
    g8 += G1;
    a8 += skip ? 16 : 8; pa += skip ? 2 * PA1 : PA1;
    if (a8 >= aend) a8 -= NA * 8;
    const uint32_t fb = SB + BAR_FULLB + (g8 & 56), fa = SB + BAR_FULLA + a8;
    uint2 ok;
    if constexpr (N == 128) ok = FIRST ? wgmma_first128(acc, da, db, h0, h1, one, fb, g8, fa, pa) : wgmma_step128(acc, da, db, h0, h1, one, fb, g8, fa, pa);
    if constexpr (N == 192) ok = FIRST ? wgmma_first192(acc, da, db, h0, h1, one, fb, g8, fa, pa) : wgmma_step192(acc, da, db, h0, h1, one, fb, g8, fa, pa);
    if constexpr (N == 256) ok = FIRST ? wgmma_first256(acc, da, db, h0, h1, one, fb, g8, fa, pa) : wgmma_step256(acc, da, db, h0, h1, one, fb, g8, fa, pa);
    db += N * 8 - 384;
    return ok;
  }
  __device__ __forceinline__ void ensure(uint2 ok) {
    asm volatile(
        "{\n.reg .pred p, q;\n.reg .b64 s, t;\nmov.b64 s, {%1, %1};\nmov.b64 t, {%3, %3};\nsetp.ne.u32 p, %4, 0;\nsetp.ne.u32 q, %5, 0;\n@!p bra.uni LAB_WAIT;\n@q bra.uni DONE;\n"
        "LAB_WAIT:\nmbarrier.try_wait.shared::cta.b64 p, [%0], s;\nmbarrier.try_wait.shared::cta.b64 q, [%2], t;\n"
        "and.pred p, p, q;\n@!p bra.uni LAB_WAIT;\nDONE:\n}" ::"r"(SB + BAR_FULLB + (g8 & 56)), "r"(g8), "r"(SB + BAR_FULLA + a8), "r"(pa), "r"(ok.x), "r"(ok.y) : "memory");
  }
  template <class Hook> __device__ __forceinline__ void validate(bool check, const CUtensorMap* tm16, int c0, int c1, int wp, int j, Hook hook) {
    const uint32_t rows = SB + OFF_A + a8 * 1024 + wp * 2048, ad = a8 * 1024 + so;
    uint32_t v0 = 0, v1 = 0;
    asm volatile("{\n.reg .pred p;\nsetp.ne.u32 p, %3, 0;\n@p ld.shared.b32 %0, [%2];\n@p ld.shared.b32 %1, [%2 + 1024];\n}" : "+r"(v0), "+r"(v1) : "r"(ad), "r"((uint32_t)check));
    hook();
    while (__any_sync(~0u, max(v0, v1) == 0xffffffffu)) {
      const uint32_t bar = SB + BAR_SPEC + (w * 4 + wp) * 8;
      e_load<2048>(rows, tm16, c0 + sched_k(c_sched.v[j][(g8 >> 3) & 511]), c1 + wp * 16, bar);
      mbar_spin(bar, sph);
      sph ^= 1;
      v0 = lds32(ad); v1 = lds32(ad + 1024);
    }
  }
  __device__ __forceinline__ void fence() const { asm volatile("{\n.reg .pred p;\nsetp.eq.u32 p, %0, 2;\nLAB:\n@p pmevent 6;\n@p bra.uni LAB;\n}" ::"r"(one) : "memory"); }
  __device__ __forceinline__ void drain() {
    wg_wait<0>();
    arrive_2(SB + BAR_EMPTYB + curB, SB + BAR_EMPTYA + curA, l0);
    curB = BAR_DUMMY - BAR_EMPTYB; curA = BAR_DUMMY - BAR_EMPTYA;
  }
  __device__ __forceinline__ void signal_server(uint32_t odd) { __syncwarp(); arrive_n(SB + BAR_SRV + w * 16 + odd * 8, l0); }
  __device__ __forceinline__ void signal_loader() { __syncwarp(); arrive_n(SB + BAR_STG + w * 8, l0); }
  template <int N, bool HOLD = false, int S, class Pre = Nop> __device__ __forceinline__ void begin(float (&acc)[S], uint32_t p0, int proft, Pre pre = Pre()) {
    db = DB0 + p0 * 512;
    const uint32_t c1 = HOLD ? clock32() : 0;
    ensure(nx);
    if (HOLD) spin_until(c1 + lds32(SB + OFF_HOLD + w * 4));
    pre(0);
    PROF_T(w, proft, 0);
    ensure(iss<N, true>(acc, false));
  }
  template <int N, bool ENSURE = true, int S, class Hook> __device__ __forceinline__ void run(float (&acc)[S], int i0, int i1, uint32_t skips, int pause, Hook hook) {
    int i = i0;
    const int ev = w ? pause : -1;
#pragma unroll 1
    while (true) {
      const uint2 ok = iss<N, false>(acc, (skips >> i) & 1);
      wg_wait<1>();
      arrive_2(SB + BAR_EMPTYB + prevB, SB + BAR_EMPTYA + prevA, l0);
      if (pause >= 0 && i + 1 == i1) { nx = ok; break; }
      if constexpr (ENSURE) { ensure(ok); hook(i); } else hook(i, ok);
      i++;
      if (pause < 0 && i == i1) break;
      if (pause > 0 && i == ev) { drain(); mbar_spin(SB + BAR_LEAD, tph); }
    }
  }
  template <int N, bool AUG, int S> __device__ __forceinline__ void end(float (&acc)[S], int ns, uint32_t pos, uint32_t au0, uint32_t au1, int proft) {
    uint32_t augB = 0;
    arrive_n(SB + BAR_LEAD + w * (BAR_DUMMY - BAR_LEAD), l0);
    if constexpr (AUG) {
      asm volatile("{\n.reg .pred p;\n.reg .b64 s;\nmov.b64 s, {%1, %1};\nsetp.ne.u32 p, %2, 0;\n@p bra.uni DONE;\nLAB_WAIT:\nmbarrier.try_wait.shared::cta.b64 p, [%0], s;\n@!p bra.uni LAB_WAIT;\nDONE:\n}"
                     ::"r"(SB + BAR_FULLB + (g8 & 56)), "r"(g8), "r"(nx.x) : "memory");
      const uint32_t dc = (((SB + OFF_B) >> 4) | (64u << 16)) + pos * 512;
      if constexpr (N == 192) wgmma_aug192(acc, au0, au1, dc, h1); else wgmma_aug256(acc, au0, au1, dc, h1);
      augB = g8 & 56; g8 += G1;
    }
    tph ^= 1;
    if (ns > 0) wait_ahead(ns - 1);
    nx = make_uint2(mbar_test(SB + BAR_FULLB + (g8 & 56), g8 >> 31), AUG ? mbar_test(SB + BAR_FULLA + a8, pa >> 31) : 1);
    wg_wait<0>();
    arrive_2(SB + BAR_EMPTYB + curB, SB + BAR_EMPTYA + curA, l0);
    if (AUG) arrive_n(SB + BAR_EMPTYB + augB, l0);
    PROF_T(w, proft, 1);
  }
};

__device__ __forceinline__ uint32_t box_addr(uint32_t buf, uint32_t bo, int u) { return (buf + bo) ^ (u * 32); }

__device__ __forceinline__ float bf_round(float x) { return __bfloat162float(__float2bfloat16_rn(x)); }
__device__ __forceinline__ void own_rstd(int w, int wp, int lane, float (&rstd)[2]) {
#pragma unroll
  for (int hh = 0; hh < 2; hh++) rstd[hh] = __uint_as_float(lds32(SB + OFF_RSTD + (w * 72 + 8 + wp * 16 + (lane >> 2) + hh * 8) * 4));
}
__device__ __forceinline__ void stats_fetch(int w, int wp, int lane, uint32_t (&au)[2]) {
  const int g = lane >> 2, q4 = lane & 3;
  float rstd[2];
  own_rstd(w, wp, lane, rstd);
#pragma unroll
  for (int hh = 0; hh < 2; hh++) {
    const float m = __uint_as_float(lds32(SB + OFF_MEAN + (w * 64 + wp * 16 + g + hh * 8) * 4));
    const float v = q4 == 3 ? rcp(rstd[hh]) : -m;
    const float v1 = bf_round(v), v2 = bf_round(v - v1);
    const float p = q4 == 1 ? v2 : (q4 == 2 ? v - v1 - v2 : v1);
    au[hh] = pack_bf16(p, q4 == 3 ? v2 : p);
  }
}

__device__ __forceinline__ void halo_fetch(uint32_t slot, int w, const uint4* src, uint32_t bar) {
  asm volatile("{\n.reg .pred p;\nelect.sync _|p, 0xffffffff;\n@p mbarrier.arrive.expect_tx.shared::cta.b64 _, [%4], 2080;\n"
               "@p cp.async.bulk.shared::cluster.global.mbarrier::complete_tx::bytes [%0], [%2], 2048, [%4];\n"
               "@p cp.async.bulk.shared::cluster.global.mbarrier::complete_tx::bytes [%1], [%3], 32, [%4];\n}"
               ::"r"(slot), "r"(SB + OFF_RSTD + w * 288), "l"(src), "l"(src + 128), "r"(bar) : "memory");
}
struct Attn {
  uint32_t lo[24], hi[24], ha[16], hslot;
  float c[8][4], rstd[2];
  float2 rk[3];
  __device__ __forceinline__ void A(const float (&acc)[96], Pipe& M, int w, int wp, int r, uint4* halo_out) {
    const int lane = M.lane();
    M.signal_loader();
    auto cvt = [&](uint32_t& d, int u) { asm volatile("cvt.rn.bf16x2.f32 %0, %1, %2;" : "=r"(d) : "f"(acc[u + 1]), "f"(acc[u])); };
    auto rest = [&] {
#pragma unroll
      for (int nb = 23; nb >= 0; nb--) {
        cvt(lo[nb], 4 * nb);
        if (nb < 8) cvt(hi[nb], 4 * nb + 2);
        if (nb >= 16) lo[nb] = movm(lo[nb]);
      }
    };
#pragma unroll
    for (int nb = 8; nb < 24; nb++) hi[nb] = pack_bf16(acc[4 * nb + 2], acc[4 * nb + 3]);
    hslot = M.ahead(3);
    const uint32_t hbuf = hslot + wp * 2048 + lane * 16;
#pragma unroll
    for (int nb = 16; nb < 24; nb++) hi[nb] = movm(hi[nb]);
    if (wp == 3) {
      if (r < 15) {
#pragma unroll
        for (int p = 0; p < 4; p++) halo_out[p * 32 + lane] = make_uint4(hi[8 + 4 * p] ? hi[8 + 4 * p] : 0x8000u, hi[9 + 4 * p], hi[10 + 4 * p], hi[11 + 4 * p]);
        const uint32_t rh = lds32(SB + OFF_RSTD + (w * 72 + 64 + (lane & 7)) * 4);
        if (lane < 8) reinterpret_cast<uint32_t*>(halo_out + 128)[lane] = rh ? rh : 0x80000000u;
      }
    } else {
#pragma unroll
      for (int p = 0; p < 4; p++)
        asm volatile("st.shared.v4.b32 [%0], {%1,%2,%3,%4};" ::"r"(hbuf + 2048 + p * 512), "r"(hi[8 + 4 * p]), "r"(hi[9 + 4 * p]), "r"(hi[10 + 4 * p]), "r"(hi[11 + 4 * p]) : "memory");
      __syncwarp();
      arrive_n(SB + BAR_HALO + w * 8, M.l0);
    }
    rest();
  }
  __device__ __forceinline__ void B(int w, int wp, int lane, uint32_t hph) {
    own_rstd(w, wp, lane, rstd);
    mbar_spin(SB + BAR_HALO + w * 8, hph);
#pragma unroll
    for (int p = 0; p < 4; p++)
      asm volatile("ld.shared.v4.b32 {%0,%1,%2,%3}, [%4];" : "=r"(ha[4 * p]), "=r"(ha[4 * p + 1]), "=r"(ha[4 * p + 2]), "=r"(ha[4 * p + 3]) : "r"(hslot + wp * 2048 + lane * 16 + p * 512) : "memory");
#pragma unroll
    for (int u = 0; u < 3; u++) rk[u] = lds64(SB + OFF_RSTD + (w * 72 + wp * 16 + u * 8 + 2 * (lane & 3)) * 4);
  }
  template <class F> __device__ __forceinline__ void C(int wp, int r, int lane, uint32_t zero, F last) {
    const int g = lane >> 2, q = lane & 3;
    const bool nohalo = (wp == 0) && (r == 0);
    const bool up0 = 2 * q > g, up1 = 2 * q + 1 > g;
    const float sc = 0.17677669529663687f * 1.4426950408889634f;
    const float kx0 = up0 ? rk[0].x : rk[1].x, kx1 = up1 ? rk[0].y : rk[1].y;
    const float ky0 = up0 ? rk[1].x : rk[2].x, ky1 = up1 ? rk[1].y : rk[2].y;
    const float fx = rstd[0] * sc, fy = rstd[1] * sc;
    float sm[2][4] = {}, s0[2][4] = {}, s1[2][4] = {};
#pragma unroll
    for (int ks = 0; ks < 2; ks++)
#pragma unroll
      for (int h = 0; h < 2; h++) {
        const int a = 4 * h + 2 * ks;
        mma16(s0[h], lo[a], hi[a], lo[a + 1], hi[a + 1], lo[8 + a], lo[9 + a]);
        mma16(s1[h], lo[a], hi[a], lo[a + 1], hi[a + 1], hi[8 + a], hi[9 + a]);
      }
#pragma unroll
    for (int u = 0; u < 4; u++) { const int a = 4 * (u & 1) + (u & 2); mma16(sm[u & 1], lo[a], hi[a], lo[a + 1], hi[a + 1], ha[a], ha[a + 1]); }
    uint32_t pf[2][4];
    const uint32_t um = (up0 ? 0xffffu : 0u) | (up1 ? 0xffff0000u : 0u);
#pragma unroll
    for (int h = 0; h < 2; h++) {
      if (nohalo) { sm[h][0] = -INFINITY; sm[h][1] = -INFINITY; }
      float x0 = (up0 ? sm[h][0] : s0[h][0]) * (kx0 * fx), x1 = (up1 ? sm[h][1] : s0[h][1]) * (kx1 * fx);
      float y0 = (up0 ? s0[h][2] : s1[h][2]) * (ky0 * fy), y1 = (up1 ? s0[h][3] : s1[h][3]) * (ky1 * fy);
      float mx = fmaxf(x0, x1), my = fmaxf(y0, y1);
      mx = fmaxf(mx, __shfl_xor_sync(~0u, mx, 1)); my = fmaxf(my, __shfl_xor_sync(~0u, my, 1));
      mx = fmaxf(mx, __shfl_xor_sync(~0u, mx, 2)); my = fmaxf(my, __shfl_xor_sync(~0u, my, 2));
      x0 = ex2(x0 - mx); x1 = ex2(x1 - mx); y0 = ex2(y0 - my); y1 = ex2(y1 - my);
      float sx = x0 + x1, sy = y0 + y1;
      x0 *= kx0; x1 *= kx1; y0 *= ky0; y1 *= ky1;
      sx += __shfl_xor_sync(~0u, sx, 1); sy += __shfl_xor_sync(~0u, sy, 1);
      sx += __shfl_xor_sync(~0u, sx, 2); sy += __shfl_xor_sync(~0u, sy, 2);
      sx = rcp(sx); sy = rcp(sy);
      x0 *= sx; x1 *= sx; y0 *= sy; y1 *= sy;
      const uint32_t px = pack_bf16(x0, x1), py = pack_bf16(y0, y1);
      pf[h][0] = px & um; pf[h][1] = px & ~um; pf[h][2] = py & um; pf[h][3] = py & ~um;
    }
#pragma unroll
    for (int u = 0; u < 4; u++) {
#pragma unroll
      for (int e = 0; e < 4; e++) { c[2 * u][e] = 0.f; c[2 * u + 1][e] = 0.f; }
      mma8(c[2 * u], ha[8 + 2 * u], ha[9 + 2 * u], pf[u >> 1][0]);
      mma8(c[2 * u + 1], lo[16 + 2 * u], lo[17 + 2 * u], pf[u >> 1][2]);
    }
#pragma unroll
    for (int u = 0; u < 4; u++) {
      mma8(c[2 * u], lo[16 + 2 * u], lo[17 + 2 * u], pf[u >> 1][1]);
      mma8(c[2 * u + 1], hi[16 + 2 * u], hi[17 + 2 * u], pf[u >> 1][3]);
    }
    uint32_t dep = 0;
    last();
#pragma unroll
    for (int u = 0; u < (EFIRST == 3 ? 0 : 8); u++) dep |= __float_as_uint(c[u][0]);
    asm volatile("bar.sync %0, 256;" ::"r"(3 + (dep & zero)) : "memory");
  }
  __device__ __forceinline__ void E(Pipe& M, bool urgent) {
#pragma unroll
    for (int u = 0; u < 4; u++)
      asm volatile("stmatrix.sync.aligned.m8n8.x4.trans.shared.b16 [%0], {%1, %2, %3, %4};" ::"r"(box_addr(hslot, M.bo, u)),
                   "r"(pack_bf16(c[2 * u][0], c[2 * u][1])), "r"(pack_bf16(c[2 * u + 1][0], c[2 * u + 1][1])),
                   "r"(pack_bf16(c[2 * u][2], c[2 * u][3])), "r"(pack_bf16(c[2 * u + 1][2], c[2 * u + 1][3])) : "memory");
    __syncwarp();
    arrive_n(SB + (urgent ? BAR_STG + M.w * 8 : BAR_SRV + M.w * 16 + 8), M.l0);
  }
};

__device__ __forceinline__ void epi_res(const float (&acc)[64], const float (&pre)[64], float sc0, float sc1, uint32_t (&xr)[32], Pipe& M, int wp) {
  Pipe T = M;
  const uint32_t buf0 = T.take(), buf1 = T.take();
#pragma unroll
  for (int u = 0; u < 8; u++) {
#pragma unroll
    for (int nb = 2 * u; nb < 2 * u + 2; nb++) {
      xr[2 * nb] = pack_bf16(fmaf(acc[4 * nb], sc0, pre[2 * nb]), fmaf(acc[4 * nb + 1], sc0, pre[32 + 2 * nb]));
      xr[2 * nb + 1] = pack_bf16(fmaf(acc[4 * nb + 2], sc1, pre[2 * nb + 1]), fmaf(acc[4 * nb + 3], sc1, pre[33 + 2 * nb]));
    }
    stsm4(box_addr(u < 4 ? buf0 : buf1, M.bo, u & 3), xr[4 * u], xr[4 * u + 1], xr[4 * u + 2], xr[4 * u + 3]);
    if (u == 3) { M.signal_loader(); M.fence(); }
  }
  __syncwarp();
  arrive_n(SB + BAR_STG2 + M.w * 8, M.l0);
  fence_async_smem();
  wg_bar(M.w);
}
__device__ __forceinline__ void presum(float (&pre)[64], const uint32_t (&xr)[32], int lane, float usebias) {
  const uint32_t bias = SB + OFF_VEC + (lane & 3) * 8;
#pragma unroll
  for (int nb = 0; nb < 16; nb++) {
    const float2 b = lds64(bias + nb * 32);
#pragma unroll
    for (int u = 2 * nb; u < 2 * nb + 2; u++) {
      pre[32 + u] = fmaf(b.y, usebias, bf_hi(xr[u])); pre[u] = fmaf(b.x, usebias, bf_lo(xr[u]));
      asm volatile("" : "+f"(pre[u]), "+f"(pre[32 + u]));
    }
  }
}
template <int U0, int U1, int S, int Q> __device__ __forceinline__ void pack_relu(uint32_t (&o)[Q], const float (&acc)[S]) {
#pragma unroll
  for (int u = U0; u < U1; u++) asm volatile("cvt.rn.relu.bf16x2.f32 %0, %1, %2;" : "=r"(o[u]) : "f"(acc[2 * u + 1]), "f"(acc[2 * u]));
}
__device__ __forceinline__ uint32_t sq_bf16x2(uint32_t a) { uint32_t d; asm("mul.rn.bf16x2 %0, %1, %1;" : "=r"(d) : "r"(a)); return d; }
template <int Q> __device__ __forceinline__ void ffn_stage(const uint32_t (&o)[Q], int i, Pipe& M) {
  i -= M.w;
  if (i == 1 || i == 4 || i == 7 || (Q == 64 && i == 10)) {
    const uint32_t buf = M.wait_ahead(2 - M.w);
#pragma unroll
    for (int b = 0; b < Q / 16; b++)
      if (i == 3 * b + 1) {
#pragma unroll
        for (int u = 4 * b; u < 4 * b + 4; u++)
          stsm4(box_addr(buf, M.bo, u & 3), sq_bf16x2(o[4 * u]), sq_bf16x2(o[4 * u + 1]), sq_bf16x2(o[4 * u + 2]), sq_bf16x2(o[4 * u + 3]));
      }
    M.signal_server((i & 1) ^ (Q == 64));
  }
}

__device__ __forceinline__ void wait_flags(const uint8_t* f, uint32_t tag, int lane) {
  const uint32_t t4 = (tag & 0xff) * 0x01010101u;
  const uint32_t* fp = reinterpret_cast<const uint32_t*>(f) + (lane & (FG / 4 - 1));
  while (__any_sync(~0u, __vsub4(ld_relaxed(fp), t4) & 0x80808080u)) {}
  asm volatile("fence.acquire.gpu;\nfence.proxy.async.global;" ::: "memory");
}
__device__ __forceinline__ uint32_t get_epoch() { mbar_spin(SB + BAR_EPOCH, 0); return __shfl_sync(~0u, lds32(SB + OFF_HOLD + 8), 0); }
__device__ __forceinline__ void aloader(const Params& P, const Ptrs& Q, int bid, int r, int j, int lane, int w, uint32_t e, uint32_t epoch) {
  const uint32_t abase = SB + OFF_A + w * NA * 8192, fbase = SB + BAR_FULLA + w * NA * 8, ebase = SB + BAR_EMPTYA + w * NA * 8;
  uint32_t slot = NPRO, ph = 1, nst = 0, hph = 0, npace = 0;
  int t = -1, kind = -1, a0 = 0, a1 = 0;
  const CUtensorMap* tmA = nullptr;
  uint64_t pol = 0;
  uint4* hin = Q.s->halo[0][0] + (r * 16 + j * 2 + w - 16) * 136;
  uint32_t* const pace = Q.s->pace[0] + (bid & -PG) * 4;
  const uint8_t* const flags = Q.s->flags[r / (FG / 8)][w];
  auto adv = [&] { if (++slot == NA) { slot = 0; ph ^= 1; } };
#pragma unroll 1
  for (int g = NPRO; g <= NSTEP; g++) {
    const uint32_t cur = e;
    e = c_sched.v[j][g + 1];
    if (!(cur & E_RARE)) {
      if (cur & E_HAND) { mbar_spin(ebase + slot * 8, ph); e_arrive(fbase + slot * 8, 1); adv(); }
    } else {
      if (cur & F_NEW) {
        t++; kind = kind == 5 ? 0 : kind + 1;
        const bool narrow = kind == 2 || kind == 5;
        static_assert(TM_XIN == 0 && TM_X == 1 && TM_XA == 2 && TM_O == 3 && TM_H == 4, "map order");
        tmA = &P.tm[t < 2 ? 0 : (0x422311 >> (4 * kind)) & 15];
        pol = ((AEF >> t) & 1) ? 0x12F0000000000000ull : 0x1000000000000000ull;
        a0 = narrow ? 0 : w * 1024; a1 = narrow ? r * 128 + w * 64 : r * 64;
      }
      const bool xo = cur & E_XPUB0;
      uint32_t s = slot;
      if (cur & (E_HAND | E_ATTN | E_XPUB0)) {
        if (cur & E_KEEP) e_arrive(ebase + slot * 8, 4);
#pragma unroll 1
        for (int u = xo ? 0 : 1; u < 2; u++) { mbar_wait(ebase + slot * 8, ph); e_arrive(fbase + slot * 8, 1); adv(); }
      }
      uint32_t hold = 0;
      int lag = 0;
      if ((xo && t < 12) || (cur & F_GATH)) {
        uint32_t v;
        uint32_t v1;
        do asm volatile("ld.relaxed.gpu.global.v2.u32 {%0, %1}, [%2];" : "=r"(v), "=r"(v1) : "l"(pace + npace + (lane & (PG - 1)) * 2) : "memory");
        while (__any_sync(~0u, ((v ^ (epoch * 16 + t - 1)) | (v ^ v1)) & 31));
        v += v1;
        npace ^= PG * 2;
        lag = min((int)(v - __shfl_sync(~0u, v, bid & (PG - 1))), 8000) * LAGM >> 5;
        hold = __reduce_max_sync(~0u, lag);
        asm volatile("st.shared.b32 [%0], %1;" ::"r"(SB + OFF_HOLD + w * 4), "r"(hold) : "memory");
      }
      if (cur & (E_ATTN | E_XPUB0)) {
        const uint32_t s2 = s == NA - 1 ? 0 : s + 1;
        mbar_wait(SB + BAR_STG + w * 8, nst & 1);
        nst++;
        LT(0);
        const uint32_t c1 = clock32();
        e_store(tmA, a0 + sched_k(cur), a1, abase + s * 8192);
        if (xo) {
          mbar_spin(SB + BAR_STG2 + w * 8, ~t & 1);
          e_store(tmA, a0 + sched_k(cur) + 64, a1, abase + s2 * 8192);
          if (t == 12) break;
        } else e_arrive(SB + BAR_OWN + w * 8, 1);
        LT(1);
        spin_until(c1 + hold + (xo ? SDELAY : SDELAYO));
        LT(2);
        LT(5);
      }
      if (cur & E_SIG) {
        e_arrive(SB + BAR_SRV + w * 16, 4);
      }
      if (cur & E_REL) bulk_wait_all();
      if (cur & E_HALO) {
        mbar_spin(SB + BAR_STG + w * 8, nst & 1);
        nst++;
        const uint32_t hs = abase + (slot >= 3 ? slot - 3 : slot + 3) * 8192, ad = hs + lane * 32 + (lane & 4) * 4;
        if (r == 0) {
#pragma unroll
          for (int p = 0; p < 4; p++) sts128(hs + lane * 16 + p * 512, 0, 0, 0, 0);
          asm volatile("st.shared.b32 [%0], %1;" ::"r"(SB + OFF_RSTD + w * 288 + (lane & 7) * 4), "r"(0x3f800000) : "memory");
        } else {
          spin_until(clock32() + HDELAY);
          do {
            halo_fetch(hs, w, hin, SB + BAR_SPEC + 80 + w * 8);
            mbar_spin(SB + BAR_SPEC + 80 + w * 8, hph);
            hph ^= 1;
          } while (__any_sync(~0u, min(min(lds32(ad), lds32(ad + 1024)), lds32(SB + OFF_RSTD + w * 288)) == 0));
        }
        e_arrive(SB + BAR_HALO + w * 8, 1);
      }
      if ((cur & E_REL) && (kind == 1 || kind == 2) && r > 0) {
        uint4* hz = hin + lane;
        hin += 256 * 136;
#pragma unroll
        for (int p = 0; p < 4; p++) hz[p * 32] = make_uint4(0, 0, 0, 0);
        if (lane < 2) hz[128] = make_uint4(0, 0, 0, 0);
      }
      if (cur & E_WAIT) {
        wait_flags(flags + ((cur & E_PART1) ? FG : 0), epoch * 16 + t, lane);
      }
    }
    if (!(cur & (F_AUG | F_NOA))) {
      mbar_wait(ebase + slot * 8, ph);
      e_load(abase + slot * 8192, tmA, a0 + sched_k(cur), a1, fbase + slot * 8, pol);
      adv();
      if (cur & F_STAMP) {
        uint32_t stamp;
        asm volatile("mov.u32 %0, %%globaltimer_lo;" : "=r"(stamp));
        asm volatile("st.relaxed.gpu.global.u32 [%0], %1;" ::"l"(pace + npace + (bid & (PG - 1)) * 2 + w), "r"((stamp & ~31u) | ((epoch * 16 + t) & 31)) : "memory");
      }
    }
  }
  bulk_wait_all();
}

__device__ __forceinline__ void bloader(const Params& P, const Ptrs& Q, bool aux, int j, int lane, uint32_t e, uint32_t epoch) {
  const uint32_t* const sched = c_sched.v[aux ? 8 : j];
  int kind = -1, c2 = 0, c3 = 0, na = 0;
  const CUtensorMap* tmB = nullptr;
  uint32_t sph = 0, efm = aux ? 0 : BEF * 2;
  uint64_t pol = 0;
#pragma unroll 1
  for (int g = aux ? 8 + (j & 1) : NPRO; g < (aux ? NSTEP_AUX : NSTEP); g += 1 + aux) {
    const uint32_t cur = e;
    e = sched[g + 1 + aux];
    if (cur & F_NEW) {
      kind = kind == 5 ? 0 : kind + ((cur >> 29) & 3);
      static_assert(TM_WQKV == 5 && TM_WO == 6 && TM_W1A == 7 && TM_W1B == 8 && TM_W2 == 9, "map order");
      tmB = &P.tm[(0x978655 >> (4 * kind)) & 15];
      efm >>= 1;
      pol = (efm & 1) ? 0x12F0000000000000ull : 0x1000000000000000ull;
      na = (0x243233 >> (4 * kind)) & 15;
      c2 = ((0x277200 >> (4 * kind)) & 15) * j + (kind == 4 ? 3 : 0);
      c3 = kind <= 1 ? kind * 8 + j : 0;
    }
    const int need = g - (int)((cur >> 5) & 15);
    const uint32_t dst = SB + OFF_B + (cur & 31) * 8192, bar = SB + BAR_FULLB + (g & 7) * 8;
    mbar_wait(SB + BAR_EMPTYB + (need & 7) * 8, (need >> 3) & 1);
    if (!(cur & F_AUG)) {
      asm volatile("{\n.reg .pred p;\nelect.sync _|p, 0xffffffff;\n@p mbarrier.arrive.expect_tx.shared::cta.b64 _, [%2], %7;\n"
                   "@p cp.async.bulk.tensor.4d.shared::cluster.global.mbarrier::complete_tx::bytes.L2::cache_hint [%0], [%1, {%3, %4, %5, %6}], [%2], %8;\n}"
                   ::"r"(dst), "l"(tmB), "r"(bar), "r"(0), "r"(sched_k(cur)), "r"(c2), "r"(c3), "r"(na * 8192), "l"(pol) : "memory");
    } else {
      const bool chk = g < NSTEP / 2;
      const uint32_t b2 = chk ? SB + BAR_AUG : bar, ad = dst + lane * 16 + (lane >> 3) * 4;
      while (true) {
        asm volatile("{\n.reg .pred p;\nelect.sync _|p, 0xffffffff;\n@p mbarrier.arrive.expect_tx.shared::cta.b64 _, [%2], 4096;\n"
                     "@p cp.async.bulk.shared::cluster.global.mbarrier::complete_tx::bytes [%0], [%1], 4096, [%2];\n}"
                     ::"r"(dst), "l"(Q.s->aug[epoch & 1][(kind - (kind >= 3)) * 8 + j]), "r"(b2) : "memory");
        if (!chk) break;
        mbar_spin(b2, sph);
        sph ^= 1;
        uint32_t mn = ~0u;
#pragma unroll
        for (int u = 0; u < 8; u++) mn = min(mn, lds32(ad + u * 512));
        if (!__any_sync(~0u, mn == 0)) { e_arrive(bar, 1); break; }
      }
      __syncwarp();
    }
  }
}

constexpr uint32_t job_slots(int layer) {
  const int pos[10] = {11, 26, 63, 73, 77, 81, 92, 96, 100, 104};
  uint32_t v = 0;
  for (int m = 0; m < 10; m++) v |= (uint32_t)((layer * 148 + pos[m]) % NA) << (3 * m);
  return v;
}
constexpr uint32_t JOB_SLOTS0 = job_slots(0), JOB_SLOTS1 = job_slots(1);
__device__ __forceinline__ void server(const Params& P, const Ptrs& Q, int bid, int r, int j, int lane, uint32_t epoch) {
  if (CPF) spin_until(clock32() + CPF);
  epoch += __shfl_sync(~0u, c_sched.v[j][lane < 18 ? lane * 16 : 0] >> 31, 0);
  {
    const uint2 b = reinterpret_cast<const uint2*>(Q.b2 + j * 128)[lane];
    sts128(SB + OFF_VEC + lane * 16, b.x << 16, b.x & 0xffff0000u, b.y << 16, b.y & 0xffff0000u);
  }
  int hl = 0;
  uint32_t fph = 0, pend = SB + BAR_DUMMY3;
#pragma unroll 1
  for (int n = 0; n < 20; n++) {
    const int layer = n >= 10, m = n - 10 * layer;
    const bool stat = m == 0 || m == 2;
    const uint32_t slot = ((layer ? JOB_SLOTS1 : JOB_SLOTS0) >> (m * 3)) & 7;
    auto fetch = [&](int w) {
      asm volatile("{\n.reg .pred p;\nelect.sync _|p, 0xffffffff;\n@p mbarrier.arrive.expect_tx.shared::cta.b64 _, [%2], 4096;\n"
                   "@p cp.async.bulk.shared::cluster.global.mbarrier::complete_tx::bytes [%0], [%1], 4096, [%2];\n}"
                   ::"r"(SB + OFF_A + (w * NA + slot) * 8192), "l"(&Q.s->stats[hl][r * 32 + w * 16][0][0]), "r"(SB + BAR_SPEC + 64 + w * 8) : "memory");
    };
#pragma unroll 1
    for (int w = 0; w < 2; w++) {
      mbar_spin(SB + BAR_SRV + w * 16 + (n & 1) * 8, (n >> 1) & 1);
      if (stat) fetch(w);
      else {
        e_store(&P.tm[m == 1 ? TM_O : TM_H], m == 1 ? j * 64 : 448 * j + (m - 3) * 64, r * 128 + w * 64, SB + OFF_A + (w * NA + slot) * 8192);
        bulk_wait_read<1>();
        e_arrive(pend, 4);
        pend = SB + BAR_EMPTYA + (w * NA + slot) * 8;
      }
    }
    if (stat) {
#pragma unroll 1
      for (int w = 0; w < 2; w++) {
        const uint32_t src = SB + OFF_A + (w * NA + slot) * 8192 + (lane >> 1) * 256 + ((lane >> 1) & 7) * 32 + (lane & 1) * 16;
        float ms[2], md[2], mq[2], m0[2];
        while (true) {
          mbar_spin(SB + BAR_SPEC + 64 + w * 8, (fph >> w) & 1);
          fph ^= 1u << w;
          uint32_t bad = 0;
          ms[0] = ms[1] = md[0] = md[1] = mq[0] = mq[1] = m0[0] = m0[1] = 0.f;
#pragma unroll 1
          for (int p = 0; p < 8; p += 2) {
            const float4 v2[2] = {lds128(src ^ (p * 32)), lds128(src ^ (p * 32) ^ 32)};
            if (p == 0) { m0[0] = v2[0].x; m0[1] = v2[0].z; }
#pragma unroll
            for (int z = 0; z < 2; z++) {
              const float4 v = v2[z];
              const float a = v.x - m0[0], b = v.z - m0[1];
              bad |= __float_as_uint(v.y) ^ epoch;
              ms[0] += a; md[0] = fmaf(a, a, md[0]); mq[0] += __uint_as_float(__float_as_uint(v.y) & ~63u);
              ms[1] += b; md[1] = fmaf(b, b, md[1]); mq[1] += v.w;
            }
          }
          if (!__any_sync(~0u, bad & 63)) break;
          fetch(w);
          __syncwarp();
        }
        e_arrive(SB + BAR_EMPTYA + (w * NA + slot) * 8, 4);
        const int row = (lane >> 3) * 16 + (lane & 7);
#pragma unroll
        for (int z = 0; z < 2; z++) {
          const float d = ms[z] * 0.125f;
          asm volatile("st.shared.f32 [%0], %1;" ::"r"(SB + OFF_MEAN + (w * 64 + row + z * 8) * 4), "f"(m0[z] + d) : "memory");
          const float rs = rsq(fmaf(mq[z], 1.f / 1024.f, fmaxf(fmaf(md[z], 0.125f, -d * d), 0.f)) + 1e-5f);
          asm volatile("st.shared.f32 [%0], %1;" ::"r"(SB + OFF_RSTD + (w * 72 + 8 + row + z * 8) * 4), "f"(rs) : "memory");
        }
        e_arrive(SB + BAR_STAT + w * 8, 8);
      }
    }
    if (stat && n != 12) {
#pragma unroll 1
      for (int u = 0; u < (m ? 2 : 3); u++) {
        const uint32_t pitch = u == 2 ? 448 : 128;
        uint4* p = reinterpret_cast<uint4*>(u == 2 ? Q.s->h : (m ? Q.out : Q.s->x)) + (u == 2 ? 64 + j * 8 : j * 16 + u * 8) + ((r * 128 + (lane >> 3)) * pitch + (lane & 7));
#pragma unroll 1
        for (int k = 0; k < 32 / FUN; k++) {
#pragma unroll
          for (int z = 0; z < FUN; z++) {
            *p = make_uint4(~0u, ~0u, ~0u, ~0u);
            p += 4 * pitch;
            asm volatile("" : "+l"(p));
          }
        }
      }
      __syncwarp();
    }
    if ((0x222 >> m) & 1) {
      bulk_wait_all();
      e_arrive(pend, 4);
      pend = SB + BAR_DUMMY3;
      if (lane < 2) st_release8(&Q.s->flags[r / (FG / 8)][lane][(r & (FG / 8 - 1)) * 8 + j + (m == 9 ? FG : 0)], epoch * 16 + layer * 6 + (m == 1 ? 2 : 5));
      __syncwarp();
    }
    hl += stat;
  }
}

__device__ __forceinline__ void aux_math(const Ptrs& Q, int bid, int jj, int warp, int lane) {
  const int g = lane >> 2, q = lane & 3, c0 = (warp & 3) * 2;
  uint32_t st = warp >> 2, bf[16][4] = {};
  const uint32_t ad0 = SB + ((lane >> 4) * 8 + (lane & 7)) * 128 + (((c0 + ((lane >> 3) & 1)) ^ (lane & 7)) << 4);
#pragma unroll 1
  for (int t = 0; t < 4; t++) {
    float acc[4][4] = {};
    uint32_t bias[8];
#pragma unroll
    for (int a = 0; a < 8; a++) bias[a] = t >= 2 ? reinterpret_cast<const uint32_t*>(Q.b1 + 448 * jj + (t - 2) * 192 + c0 * 8)[(a >> 1) * 32 + (a & 1) * 4 + q] : 0u;
#pragma unroll 1
    for (int i = 0; i < 16; i++, st += 2) {
      const uint32_t ad = ad0 + (c_sched.v[8][st] & 31) * 8192;
      mbar_spin(SB + BAR_FULLB + (st & 7) * 8, (st >> 3) & 1);
#pragma unroll
      for (int u = 0; u < 16; u++)
        asm volatile("{\n.reg .pred p;\nsetp.ne.u32 p, %5, 0;\n@p ldmatrix.sync.aligned.m8n8.x4.trans.shared.b16 {%0,%1,%2,%3}, [%4];\n}"
                     : "+r"(bf[u][0]), "+r"(bf[u][1]), "+r"(bf[u][2]), "+r"(bf[u][3])
                     : "r"(ad + (u & 3) * 8192 + (u >> 2) * 2048), "r"((u & 3) != 3 || t == 3 ? 1 : 0) : "memory");
      __syncwarp();
      e_arrive(SB + BAR_EMPTYB + (st & 7) * 8, 2);
#pragma unroll
      for (int u = 0; u < 16; u++) mma16(acc[u & 3], bf[u][0], bf[u][1], bf[u][2], bf[u][3], 0x3F803F80u, 0x3F803F80u);
    }
    const uint32_t epoch = lds32(SB + OFF_HOLD + 8);
    const uint32_t o = (t * 8 + jj) * 1024 + g * 32 + ((c0 ^ g) << 2) + q + (epoch & 1) * 32768;
    uint32_t *const p0 = Q.s->aug[0][0] + o, *const p1 = Q.s->aug[0][0] + (o ^ 4);
#pragma unroll
    for (int a = 0; a < 8; a++) {
      const float u = acc[a >> 1][(a & 1) * 2];
      uint32_t h = movm(pack_bf16(u, u - bf_round(u)));
      if (g >= 6) h = bias[a];
      ((a & 1) ? p1 : p0)[(a >> 1) * 256] = h ? h : 0x8000u;
    }
    uint4* const z = reinterpret_cast<uint4*>(Q.s->aug[~epoch & 1][t * 8 + jj]) + (threadIdx.x & 127);
    z[0] = z[128] = make_uint4(0, 0, 0, 0);
  }
}

template <bool BYSM> __global__ void __launch_bounds__(NTHREADS, 1) mega_kernel(const __grid_constant__ Ptrs Q, const __grid_constant__ Params P) {
  extern __shared__ __align__(1024) uint8_t smem_raw[];
  constexpr uint32_t sb = SB;
  const uint32_t centry = clock32();
  const int warp = __shfl_sync(~0u, threadIdx.x >> 5, 0), lane = threadIdx.x & 31;
  const int bid = BYSM ? work_id() : blockIdx.x;
  const bool aux = bid >= NMAIN;
  const int r = Q44 ? ((bid >> 5) << 2) | (bid & 3) : ((bid >> 4) << 1) | (bid & 1), j = (aux ? bid * 2 : bid >> (1 + Q44)) & 7;
  PRO(0);
  {
    const uint32_t b = sb + OFF_BAR + warp * 48, cnt = warp < 6 ? 1 : (warp < 10 ? 4 : 8);
    asm volatile("{\n.reg .pred p;\nelect.sync _|p, 0xffffffff;\n@p mbarrier.init.shared::cta.b64 [%0], %1;\n@p mbarrier.init.shared::cta.b64 [%0 + 8], %1;\n"
                 "@p mbarrier.init.shared::cta.b64 [%0 + 16], %1;\n@p mbarrier.init.shared::cta.b64 [%0 + 24], %1;\n"
                 "@p mbarrier.init.shared::cta.b64 [%0 + 32], %1;\n@p mbarrier.init.shared::cta.b64 [%0 + 40], %1;\nfence.mbarrier_init.release.cluster;\n}"
                 ::"r"(b), "r"(cnt) : "memory");
  }
  __syncthreads();
  {
    static_assert(NPRO == 4, "prologue stages");
    const int st = ((11 - warp) * (aux ? 32 : 11)) >> 5, op = aux ? (st < 8) * 2 : 11 - warp - 3 * st, sd = aux ? st >> STGX : (op == 2 ? st : st & 2);
    const uint32_t bar0 = sb + OFF_BAR + (op * 6 + st) * 8;
    const int kc = aux ? (st >> 1) * 64 : (((st & 2 ? ROUND1 : ROUND0) >> (4 * j)) & 15) * 128 + (st & 1) * 64;
    spin_until(centry + (sd ? STG0 + sd * STG1 : 0));
    if (op == 2) {
      asm volatile("{\n.reg .pred p;\nelect.sync _|p, 0xffffffff;\n@p mbarrier.arrive.expect_tx.shared::cta.b64 _, [%2], 24576;\n"
                   "@p cp.async.bulk.tensor.4d.shared::cluster.global.mbarrier::complete_tx::bytes [%0], [%1, {%3, %4, %3, %5}], [%2];\n}"
                   ::"r"(sb + OFF_B + (aux ? (st & 1) * 114688 + (st >> 1) * 24576 : (st + pos0(0) / 3 - (st + pos0(0) / 3 >= 5 ? 5 : 0)) * 24576)), "l"(&P.tm[TM_WQKV]), "r"(bar0), "r"(0), "r"(kc), "r"(j + (st & aux)) : "memory");
    } else if (!aux) e_load(sb + OFF_A + (op * 6 + st) * 8192, &P.tm[TM_XIN], op * 1024 + kc, r * 64, bar0);
    PRO(1);
    asm volatile("prefetch.tensormap [%0];" ::"l"(&P.tm[warp]) : "memory");
  }
  if (warp >= 8) {
    asm volatile("setmaxnreg.dec.sync.aligned.u32 24;");
    if (warp == 11) {
      if (smem_u32(smem_raw) != SB) __trap();
      const uint32_t epoch = __shfl_sync(~0u, ld_relaxed(&Q.s->epoch[bid]) + 1, 0);
      Q.s->epoch[bid] = epoch;
      asm volatile("st.shared.b32 [%0], %1;" ::"r"(sb + OFF_HOLD + 8), "r"(epoch) : "memory");
      e_arrive(sb + BAR_EPOCH, 1);
      PRO(2);
      if (!aux) server(P, Q, bid, r, j, lane, epoch);
    } else {
      const uint32_t e = c_sched.v[aux ? 8 : j][aux ? warp : NPRO];
      spin_until(centry + STGL + (aux ? STGLX : (warp > 8 ? STGLW : 0)) + (e >> 31));
      PRO(2);
      const uint32_t epoch = get_epoch();
      PRO(3);
      if (warp <= 8 + aux) bloader(P, Q, aux, j + warp - 8, lane, e, epoch);
      else if (!aux) aloader(P, Q, bid, r, j, lane, warp - 9, e, epoch);
    }
  } else if (aux) aux_math(Q, bid, j + (warp >> 2), warp, lane);
  else {
    asm volatile("setmaxnreg.inc.sync.aligned.u32 240;");
    const int w = warp >> 2, wp = warp & 3;
    {
      uint32_t xr[32];
#pragma unroll
      for (int u = 0; u < 32; u++) if (NOI) asm volatile("" : "=r"(xr[u])); else xr[u] = 0;
      Pipe M;
      M.db = 0; M.g8 = 0; M.a8 = w * NA * 8; M.pa = 0; M.tph = 0; M.aend = (w + 1) * NA * 8;
      M.h0 = gridDim.y * 0x40000040u; M.h1 = gridDim.z * 0x40000040u; M.one = gridDim.z;
      M.curB = M.curA = M.prevB = M.prevA = M.sph = 0; M.nx = make_uint2(0, 0); M.w = w; M.l0 = lane == 0;
      M.bo = (wp * 16 + (lane & 15)) * 128 + (((lane >> 4) ^ (lane & 7)) << 4);
      M.so = __shfl_sync(~0u, SB + OFF_A + wp * 2048 + lane * 32 + (lane >> 2) * 4, lane);
      M.bo = __shfl_sync(~0u, M.bo, lane);
      auto nop = [](int) {};
      const uint32_t zero = gridDim.y - 1;
      PROF_T(w, 0, 3);
      if (STARTC) spin_until(centry + STARTC);
#pragma unroll 1
      for (int hl = 0; hl < 4; hl++) {
        const int t0 = hl * 3;
        const bool ffn = hl & 1;
        float acc[96], acn[64];
        uint32_t au[2] = {0u, 0u};
        {
          const int d = hl ? 0 : ((OWNP * 2u) >> (4 * j)) & 15;
          auto own = [&](auto h, uint32_t dep = 0) {
#pragma unroll
            for (int u = 4 * h.v; u < 4 * h.v + 4; u++)
              asm volatile("ldmatrix.sync.aligned.m8n8.x4.shared.b16 {%0,%1,%2,%3}, [%4];" : "=r"(xr[4 * u]), "=r"(xr[4 * u + 1]), "=r"(xr[4 * u + 2]), "=r"(xr[4 * u + 3])
                           : "r"(box_addr(sb + OFF_A + M.a8 * 1024, M.bo + dep, u & 3)) : "memory");
          };
          M.begin<192>(acc, ffn ? pos0(3) : pos0(0), t0, [&](int) { if (hl + d == 0) own(IC<0>{}); });
          if (hl + d == 0) own(IC<1>{}, (xr[0] | xr[4] | xr[8] | xr[12]) & zero);
          float ss[2] = {0.f, 0.f}, sq[2] = {0.f, 0.f};
          auto part = [&](auto c0, auto n) {
#pragma unroll
            for (int v = 0; v < 4 * n.v; v++) {
              const int u = c0.v + v / n.v * 4 + v % n.v;
              float a, b;
              asm volatile("shl.b32 %0, %2, 16;\nand.b32 %1, %2, 0xffff0000;" : "=f"(a), "=f"(b) : "r"(xr[u]));
              ss[u & 1] += a + b; sq[u & 1] = fmaf(a, a, fmaf(b, b, sq[u & 1]));
            }
          };
          const uint64_t plan = hl ? (ffn ? PLAN1 : PLAN2) : (d ? (d == 6 ? PLAN6 : PLAN0) : PLANZ);
          auto todo = [&](int i) { uint64_t v; asm volatile("shr.u64 %0, %1, %2;" : "=l"(v) : "l"(plan), "r"((i + 1 - d) * 8)); return (uint32_t)v; };
          uint32_t m = todo(1);
          M.run<192, false>(acc, 1, 16, 1u << 10, 16 - (ffn ? LEAD3 : LEAD0), [&](int i, uint2 ok) {
           CT(0);
           if (m & 127) {
             if (m & 1) part(IC<0>{}, IC<2>{});
             if (m & 2) part(IC<2>{}, IC<2>{});
             if (m & 4) part(IC<16>{}, IC<1>{});
             if (m & 8) part(IC<17>{}, IC<1>{});
             if (m & 16) part(IC<18>{}, IC<1>{});
             if (m & 32) part(IC<19>{}, IC<1>{});
             if (m & 64) {
               const uint32_t epoch = lds32(sb + OFF_HOLD + 8);
#pragma unroll
               for (int o = 1; o < 4; o *= 2)
#pragma unroll
                 for (int z = 0; z < 2; z++) { ss[z] += __shfl_xor_sync(~0u, ss[z], o); sq[z] += __shfl_xor_sync(~0u, sq[z], o); }
               const float m0 = ss[0] * (1.f / 128.f), m1 = ss[1] * (1.f / 128.f);
               const int rowpair = r * 64 + w * 32 + wp * 8 + (M.lane() >> 2);
               if ((M.lane() & 3) == 0)
                 st_pkt(&Q.s->stats[hl][rowpair >> 1][j][rowpair & 1], __float_as_uint(m0), (__float_as_uint(fmaxf(fmaf(-ss[0], m0, sq[0]), 0.f)) & ~63u) | (epoch & 63),
                        __float_as_uint(m1), __float_as_uint(fmaxf(fmaf(-ss[1], m1, sq[1]), 0.f)));
             }
           }
           CT(1);
           M.ensure(ok);
           CT(3);
           M.validate(hl != 0, &P.tm[ffn ? TM_XA16 : TM_X16], w * 1024, r * 64, wp, j, [&] {
            if (m & 128) { if (m & 1) own(IC<1>{}); else own(IC<0>{}); }
            m = todo(i + 1);
            if (i == STATI) { mbar_spin(sb + BAR_STAT + w * 8, hl & 1); stats_fetch(w, wp, M.lane(), au); }
           });
           CT(4);
          });
          M.end<192, true>(acc, ffn ? 0 : 4, ffn ? posa(3) : posa(0), au[0], au[1], t0);
          PROF_T(w, t0, 2);
        }
        if (!ffn) {
          Attn T;
#pragma unroll 1
          for (int wave = 0; wave < 2; wave++) {
            AP(9);
            uint4* const hp = Q.s->halo[0][0] + (uint32_t)(((hl + wave) * 256 + r * 16 + j * 2 + w) * 136);
            T.A(acc, M, w, wp, r, hp);
            AP(0);
            if (wave == 0) {
              M.begin<192, PACE2 & 1>(acc, pos0(1), t0 + 1);
              M.run<192>(acc, 1, NH1, 4, -1, nop);
              T.B(w, wp, M.lane(), 0);
              M.drain();
            } else {
              M.begin<128, (PACE2 >> 1) & 1>(acn, pos0(2), t0 + 2);
              M.run<128>(acn, 1, NH2, 4, -1, nop);
              T.B(w, wp, M.lane(), 1);
              M.drain();
#pragma unroll
              for (int z = 0; z < 64; z++) asm volatile("mov.b32 %0, %1;" : "=f"(acc[z]) : "f"(acn[z]));
            }
            AP(2);
            T.C(wp, r, M.lane(), zero, [&] { if (EFIRST == 3 || (EFIRST == 2 && wave)) T.E(M, wave); });
            AP(3);
            if (wave == 1) break;
            M.run<192>(acc, NH1, 16, 1u << 7, 16 - LEAD1, [&](int i) { if (EFIRST < 3 && i == NH1) T.E(M, false); });
            M.end<192, true>(acc, 4, posa(1), au[0], au[1], t0 + 1);
            PROF_T(w, t0 + 1, 2);
          }
#pragma unroll
          for (int z = 0; z < 64; z++) asm volatile("mov.b32 %0, %1;" : "=f"(acn[z]) : "f"(acc[z]));
          if (EFIRST == 1) T.E(M, true);
          else if (!EFIRST) {
            M.ensure(M.iss<128, false>(acn, false));
            T.E(M, true);
          }
        } else {
          uint32_t pk[48], pk2[64];
          pack_relu<0, 48>(pk, acc);
          {
            float acc2[128];
            M.begin<256, (PACE2 >> 3) & 1>(acc2, pos0(4), t0 + 1);
            M.run<256>(acc2, 1, 16, 0x248, 16 - LEAD4, [&](int i) { ffn_stage(pk, i, M); });
            M.end<256, true>(acc2, 0, posa(4), au[0], au[1], t0 + 1);
            pack_relu<0, 64>(pk2, acc2);
            PROF_T(w, t0 + 1, 2);
          }
          M.begin<128, (PACE2 >> 4) & 1>(acn, pos0(5), t0 + 2);
          M.run<128>(acn, 1, 13, 0x1248, -1, [&](int i) { ffn_stage(pk2, i, M); });
        }
        {
          const int ks = ffn ? 56 : 16, pause = ks - (ffn ? LEAD5 : LEAD2), vfrom = ffn ? 99 : 7;
          const int imid = w ? pause : (ffn ? 20 : IPRE);
          auto check = [&](int i) {
            if (i >= vfrom) {
              if (i == 7) mbar_spin(sb + BAR_OWN + w * 8, hl >> 1);
              M.validate(true, &P.tm[TM_O16], 0, r * 128 + w * 64, wp, j, [] {});
            }
          };
          M.run<128>(acn, ffn ? 13 : NH2 + !EFIRST, imid, 0, -1, check);
          if (w) M.drain();
          float pre[64], rstd[2];
          presum(pre, xr, M.lane(), ffn ? 1.f : 0.f);
          own_rstd(w, wp, M.lane(), rstd);
          if (w) mbar_spin(SB + BAR_LEAD, M.tph);
          M.run<128>(acn, imid, ks, 0, 0, check);
          M.end<128, false>(acn, 2, 0, 0, 0, t0 + 2);
          epi_res(acn, pre, ffn ? rstd[0] * rstd[0] : 1.f, ffn ? rstd[1] * rstd[1] : 1.f, xr, M, wp);
          PROF_T(w, t0 + 2, 2);
        }
      }
    }
  }
}

typedef CUresult (*EncFn)(CUtensorMap*, CUtensorMapDataType, cuuint32_t, void*, const cuuint64_t*, const cuuint64_t*, const cuuint32_t*,
                          const cuuint32_t*, CUtensorMapInterleave, CUtensorMapSwizzle, CUtensorMapL2promotion, CUtensorMapFloatOOBfill);

void enc2(EncFn enc, CUtensorMap* tm, const void* p, uint64_t cols, uint64_t rows, uint32_t boxrows = 64, CUtensorMapL2promotion promo = APROMO) {
  cuuint64_t gd[2] = {cols, rows}, gs[1] = {cols * 2};
  cuuint32_t box[2] = {64, boxrows}, es[2] = {1, 1};
  enc(tm, CU_TENSOR_MAP_DATA_TYPE_BFLOAT16, 2, const_cast<void*>(p), gd, gs, box, es, CU_TENSOR_MAP_INTERLEAVE_NONE, CU_TENSOR_MAP_SWIZZLE_128B,
      promo, CU_TENSOR_MAP_FLOAT_OOB_FILL_NONE);
}
void enc4(EncFn enc, CUtensorMap* tm, const void* p, uint64_t K, uint64_t N, uint64_t d2, uint64_t s2, uint64_t d3, uint64_t s3, uint32_t na) {
  cuuint64_t gd[4] = {64, K, d2, d3}, gs[3] = {N * 2, s2, s3};
  cuuint32_t box[4] = {64, 64, na, 1}, es[4] = {1, 1, 1, 1};
  enc(tm, CU_TENSOR_MAP_DATA_TYPE_BFLOAT16, 4, const_cast<void*>(p), gd, gs, box, es, CU_TENSOR_MAP_INTERLEAVE_NONE, CU_TENSOR_MAP_SWIZZLE_128B,
      WPROMO, CU_TENSOR_MAP_FLOAT_OOB_FILL_NONE);
}

}

extern "C" void kernel_launch(void* const* d_in, const int* in_sizes, int n_in, void* d_out, int out_size) {
  static EncFn enc = nullptr;
  static Scratch* ps = nullptr;
  static void (*kernel)(Ptrs, Params) = mega_kernel<true>;
  if (!enc) {
    cudaDriverEntryPointQueryResult qr;
    cudaGetDriverEntryPoint("cuTensorMapEncodeTiled", (void**)&enc, cudaEnableDefault, &qr);
    int dev = 0, nsm = 0;
    cudaGetDevice(&dev);
    cudaDeviceGetAttribute(&nsm, cudaDevAttrMultiProcessorCount, dev);
    if (nsm != NMAIN + NAUX) kernel = mega_kernel<false>;
    cudaFuncSetAttribute(kernel, cudaFuncAttributeMaxDynamicSharedMemorySize, SMEM_BYTES);
    cudaGetSymbolAddress((void**)&ps, g_s);
  }
  Params P;
  Ptrs Q;
  Q.s = ps;
  void *p_h = ps->h, *p_x = ps->x;
  enc2(enc, &P.tm[TM_XIN], d_in[0], 2048, 1024, 64, XPROMO);
  enc2(enc, &P.tm[TM_X], d_out, 2048, 1024);
  enc2(enc, &P.tm[TM_XA], p_x, 2048, 1024);
  enc2(enc, &P.tm[TM_O], p_h, 3584, 2048);
  enc2(enc, &P.tm[TM_H], p_h, 3584, 2048);
  enc2(enc, &P.tm[TM_X16], d_out, 2048, 1024, 16);
  enc2(enc, &P.tm[TM_XA16], p_x, 2048, 1024, 16);
  enc2(enc, &P.tm[TM_O16], p_h, 3584, 2048, 16);
  enc4(enc, &P.tm[TM_WQKV], d_in[1], 1024, 3072, 3, 2048, 16, 128, 3);
  enc4(enc, &P.tm[TM_WO], d_in[2], 1024, 1024, 16, 128, 1, 128, 2);
  enc4(enc, &P.tm[TM_W1A], d_in[4], 1024, 3584, 56, 128, 1, 128, 4);
  enc4(enc, &P.tm[TM_W1B], d_in[4], 1024, 3584, 56, 128, 1, 128, 3);
  enc4(enc, &P.tm[TM_W2], d_in[6], 3584, 1024, 16, 128, 1, 128, 2);
  Q.out = (__nv_bfloat16*)d_out;
  Q.b1 = (const __nv_bfloat16*)d_in[5];
  Q.b2 = (const __nv_bfloat16*)d_in[7];
  kernel<<<NMAIN + NAUX, NTHREADS, SMEM_BYTES, cudaStreamPerThread>>>(Q, P);
}
```

```cpp
#include <cuda_runtime.h>
#include <cuda_bf16.h>
#include <cuda.h>
#include <stdint.h>

#define LEAD0 2
#define LEAD1 1
#define LEAD2 4
#define LEAD3 2
#define LEAD4 1
#define LEAD5 5
#define WPROMO CU_TENSOR_MAP_L2_PROMOTION_L2_128B
#define PLAN1 0x7f0000ull
#define PLAN2 0x400000003f0000ull
#define P0S 0x640096
#define PAS 0x430ff
#define PA0 0x70000a00050000ull
#define PB0 0x6000120009040000ull
#define PA2 0x600012000c8180ull
#define PB2 0x400030000a048180ull
#define PA4 0x70000e8180ull
#define PB4 0x60001a048180ull
#define PA6 0x7c8380ull
#define PB6 0x7c8380ull
#define LAGM 27
#define APROMO CU_TENSOR_MAP_L2_PROMOTION_L2_128B
#define PFT 500
#define LSO 1
#define STATI 13
#define PACE2 0x1a
#define ST2 12
#define STB 3
#define PROBE 4
#define XO 0
#define FORD 0x01234567, 0x01234567, 0x01234567, 0x01234567, 0x04567123, 0x04567123, 0x04567123, 0x04765123
#define SIG0 14
#define STGX 2
#define STGM 3
#define NPRO 4
#define XPROMO CU_TENSOR_MAP_L2_PROMOTION_L2_256B
#define IPRE 7
#define FILLT 1
#define EARLYC 1
#define OWNDLY 0
#define EPW 0
#define CPF 5000
#define STG0 800
#define STG1 400
#define STGL (STG0 + 4 * STG1)
#define STGLW 0
#define STGLX 0
#define STARTC 0
#define FUN 4
#define XEF 0
#define BEF 0xff8
#define AEF 0xdb6
#define SEF 0
#define SDELAYO 1000
#define SDELAY 300
#define HDELAY 450
#define Q44 1
#define FG 8
#define NOI 1
#define EFIRST 1
#define STA 1
#define PG (Q44 ? 32 : 16)
#define NH1 6
#define NH2 3
namespace {

constexpr int NMAIN = 128, NAUX = 4, NTHREADS = 384;
constexpr uint32_t OFF_B = 0;
constexpr uint32_t OFF_A = 131072;
constexpr uint32_t OFF_VEC = 229376;
constexpr uint32_t OFF_BAR = 231424;
constexpr uint32_t OFF_RSTD = OFF_VEC + 512, OFF_MEAN = OFF_VEC + 1088, OFF_HOLD = OFF_VEC + 2032;
constexpr uint32_t SMEM_BYTES = OFF_BAR + 960;
constexpr uint32_t BAR_FULLA = OFF_BAR, BAR_FULLB = OFF_BAR + 96, BAR_OWN = OFF_BAR + 160, BAR_EPOCH = OFF_BAR + 176, BAR_AUG = OFF_BAR + 184, BAR_SPEC = OFF_BAR + 192,
                   BAR_EMPTYA = OFF_BAR + 288, BAR_STG = OFF_BAR + 384, BAR_SRV = OFF_BAR + 400, BAR_LEAD = OFF_BAR + 432, BAR_HALO = OFF_BAR + 440, BAR_STG2 = OFF_BAR + 456,
                   BAR_DUMMY3 = OFF_BAR + 472, BAR_EMPTYB = OFF_BAR + 480, BAR_STAT = OFF_BAR + 544, BAR_DUMMY = OFF_BAR + 560;
constexpr int NA = 6;
constexpr uint32_t SB = 1024;
constexpr uint32_t SPIN_LIMIT = 1u << 22;

enum { TM_XIN = 0, TM_X, TM_XA, TM_O, TM_H, TM_WQKV, TM_WO, TM_W1A, TM_W1B, TM_W2, TM_X16, TM_XA16, TM_O16, TM_COUNT };

struct Scratch;
struct Ptrs {
  Scratch* s;
  __nv_bfloat16* out;
  const __nv_bfloat16* b1;
  const __nv_bfloat16* x;
  const __nv_bfloat16* b2;
};
struct Params { CUtensorMap tm[TM_COUNT]; };

constexpr int NSTEP = 280, NSTEP_AUX = 128;
enum : uint32_t { F_STAMP = 1u << 28, F_GATH = 1u << 15, F_NEW = 1u << 16, F_AUG = 1u << 17, F_NOA = 1u << 18, E_HAND = 1u << 19, E_ATTN = 1u << 20, E_XPUB0 = 1u << 21,
                  E_WAIT = 1u << 22, E_REL = 1u << 23, E_KEEP = 1u << 24, E_PART1 = 1u << 25, E_HALO = 1u << 26,
                  E_SIG = 1u << 27, E_RARE = F_NEW | E_KEEP | (0xfu << 20) | (3u << 26) };
constexpr uint32_t first_order(int j) {
  constexpr uint32_t t[8] = {FORD};
  uint32_t v = 0;
  for (int p = 0; p < 8; p++) v |= ((t[j] >> (28 - 4 * p)) & 15) << (4 * p);
  return v;
}
constexpr uint32_t own_rounds() { uint32_t v = 0; for (int j = 0; j < 8; j++) for (int p = 0; p < 8; p++) if (((first_order(j) >> (4 * p)) & 15) == j) v |= p << (4 * j); return v; }
constexpr uint32_t OWNP = own_rounds();
constexpr uint32_t first_round(int p) { uint32_t v = 0; for (int j = 0; j < 8; j++) v |= ((first_order(j) >> (4 * p)) & 15) << (4 * j); return v; }
constexpr uint32_t ROUND0 = first_round(0), ROUND1 = first_round(1);
__host__ __device__ constexpr int pos0(int kind) { return (P0S >> (4 * kind)) & 15; }
__host__ __device__ constexpr int posa(int kind) { return (PAS >> (4 * kind)) & 15; }
struct Sched { uint32_t v[9][NSTEP + 8]; };
constexpr Sched make_sched() {
  Sched T{};
  for (int j = 0; j < 8; j++) {
    int owner[16] = {};
    for (int i = 0; i < 16; i++) owner[i] = -100;
    int p = 0, g = 0;
    for (int t = 0; t < 12; t++) {
      const int kind = t % 6, ks = kind == 5 ? 56 : (kind == 2 ? 16 : 17);
      for (int i = 0; i < ks; i++) {
        const bool augs = ks == 17 && i == 16;
        const int na = (kind == 2 || kind == 5) ? 2 : (augs ? 1 : (kind == 4 ? 4 : 3));
        if (i == 0) p = pos0(kind);
        if (augs) p = posa(kind);
        if (p + na > 16) p = 0;
        int need = g - 8;
        for (int a = p; a < p + na; a++) { if (owner[a] > need) need = owner[a]; owner[a] = g; }
        uint32_t k = i, f = i == (t ? 0 : NPRO) ? F_NEW | (1u << 29) : 0;
        if (augs) { k = 0; f |= F_AUG; }
        else if (kind == 0 || kind == 3) {
          const int o = i - 2;
          if (t == 0) k = ((first_order(j) >> (4 * (i >> 1))) & 15) * 2 + (i & 1);
          else if (i < 2) { k = 2 * j + i; f |= F_NOA | (i == 0 ? E_XPUB0 : 0); }
          else { const int half = o >= 7; int u = o - 7 * half; { const int b = (XO & 3) == 0 ? 0 : ((XO & 3) == 1 ? (j & 4) ^ 4 : j & 4); u += u >= (j ^ b); u ^= b; } k = 2 * u + half; if (i == 6) f |= E_REL; }
          if (i == 11) f |= E_HAND;
          if (i == (t ? 11 : SIG0)) f |= E_SIG;
        } else if (kind == 1 || kind == 4) {
          if (kind == 1) f |= i == 3 ? E_HAND : (i == 8 ? E_HAND | E_KEEP : (i == 5 ? E_HALO : 0));
          if (kind == 1) f |= i == 13 ? E_REL : 0;
          else if (i == 4 || i == 7 || i == 10) f |= E_HAND;
        } else if (kind == 2) {
          f |= i == 0 ? E_WAIT : (i == 3 ? E_HAND : (i == 5 ? E_HALO : 0));
          if (i == 8) { k = 8 + j; f |= E_ATTN | E_KEEP | F_NOA; }
          if (i > 8) { const int b = (XO >> 2) == 0 ? 0 : ((XO >> 2) == 1 ? (j & 4) ^ 4 : j & 4); k = 8 + ((i - 9 + (i - 9 >= (j ^ b))) ^ b); }
          if (i == 11) f |= E_REL;
        } else {
          k = i < 24 ? (i / 3) * 7 + i % 3 : ((i - 24) / 4) * 7 + 3 + (i - 24) % 4;
          if (i == 4 || i == 7 || i == 10 || i == 13) f |= E_HAND;
          f |= i == 0 ? E_WAIT : (i == 24 ? E_WAIT | E_PART1 : 0);
        }
        if ((kind == 2 || kind == 5) && t < 11 && i == ks - (kind == 2 ? STA : STB)) f |= F_STAMP;
        if (((PACE2 >> kind) & 1) && i == ST2) f |= F_STAMP;
        if (i == 0 && t && ((PACE2 >> ((t - 1) % 6)) & 1)) f |= F_GATH;
        T.v[j][g] = p | ((g - need) << 5) | (k << 9) | f;
        p += na; g++;
      }
    }
    T.v[j][NSTEP] = F_NEW | F_NOA | E_XPUB0 | (2 * j << 9);
  }
  for (int w = 0; w < 2; w++) {
    int owner[14] = {};
    for (int i = 0; i < 14; i++) owner[i] = -100;
    for (int g = w, p = 0; g < NSTEP_AUX; g += 2) {
      const int na = g < 96 ? 3 : 4;
      if (p + na > 14) p = 0;
      int need = g - 8;
      for (int a = p; a < p + na; a++) { if (owner[a] > need) need = owner[a]; owner[a] = g; }
      T.v[8][g] = (p + 14 * w) | ((g - need) << 5) | ((g & 31) >> 1 << 9) | ((g & 30) && g - w != 8 ? 0 : F_NEW | (g - w == 64 ? 2u : 1u) << 29);
      p += na;
    }
  }
  return T;
}
__constant__ Sched c_sched = make_sched();
__device__ __forceinline__ int sched_k(uint32_t e) { return (e >> 3) & 0xfc0; }

struct Scratch {
  __nv_bfloat16 x[2048 * 1024];
  __nv_bfloat16 h[2048 * 3584];
  uint32_t epoch[160];
  uint8_t flags[16][2][64];
  uint32_t pace[8][64];
  uint32_t aug[2][32][1024];
  uint4 stats[4][512][8][2];
  uint4 halo[4][256][136];
};
__device__ __align__(1024) Scratch g_s;
#define PROF_T(w, t, i)
#define PRO(i)
#define LT(i)
#define CT(n)
#define ST(i)
#define AP(i)

__device__ __forceinline__ int work_id() {
  uint32_t smid;
  asm volatile("mov.u32 %0, %%smid;" : "=r"(smid));
  const int t = smid >> 1, u = t - 32, d = (u * 37) >> 8;
  int id = (t & 7) * 16 + (t >> 3) * 2;
  if (t >= 32) id = (1 + u - 7 * d) * 16 + (4 + d) * 2;
  if (t >= 60) id = t < 62 ? t * 2 + 8 : t * 2 - 116;
  return id + (smid & 1);
}

__device__ __forceinline__ uint32_t smem_u32(const void* p) { return (uint32_t)__cvta_generic_to_shared(p); }
__device__ __forceinline__ void mbar_init(uint32_t bar, int cnt) { asm volatile("mbarrier.init.shared::cta.b64 [%0], %1;" ::"r"(bar), "r"(cnt)); }
__device__ __forceinline__ void mbar_expect_tx(uint32_t bar, uint32_t bytes) { asm volatile("mbarrier.arrive.expect_tx.shared::cta.b64 _, [%0], %1;" ::"r"(bar), "r"(bytes) : "memory"); }
__device__ __forceinline__ void mbar_arrive(uint32_t bar, uint32_t cnt) { asm volatile("mbarrier.arrive.shared::cta.b64 _, [%0], %1;" ::"r"(bar), "r"(cnt) : "memory"); }
__device__ __forceinline__ void arrive_n(uint32_t bar, bool) { asm volatile("{\n.reg .pred p;\nelect.sync _|p, 0xffffffff;\n@p mbarrier.arrive.shared::cta.b64 _, [%0];\n}" ::"r"(bar) : "memory"); }
__device__ __forceinline__ void arrive_2(uint32_t b0, uint32_t b1, bool) {
  asm volatile("{\n.reg .pred p;\nelect.sync _|p, 0xffffffff;\n@p mbarrier.arrive.shared::cta.b64 _, [%0];\n@p mbarrier.arrive.shared::cta.b64 _, [%1];\n}" ::"r"(b0), "r"(b1) : "memory");
}
__device__ __forceinline__ void mbar_wait(uint32_t bar, uint32_t parity) {
  asm volatile(
      "{\n.reg .pred p;\n.reg .u32 c;\nmov.u32 c, 0;\n"
      "LAB_WAIT:\nmbarrier.try_wait.parity.shared::cta.b64 p, [%0], %1;\n@p bra.uni DONE;\n"
      "add.u32 c, c, 1;\nsetp.lt.u32 p, c, 4000000;\n@p bra.uni LAB_WAIT;\ntrap;\nDONE:\n}" ::"r"(bar), "r"(parity) : "memory");
}
__device__ __forceinline__ void mbar_spin(uint32_t bar, uint32_t parity) {
  asm volatile("{\n.reg .pred p;\nLAB_WAIT:\nmbarrier.try_wait.parity.shared::cta.b64 p, [%0], %1;\n@!p pmevent 7;\n@!p bra.uni LAB_WAIT;\n}" ::"r"(bar), "r"(parity) : "memory");
}
__device__ __forceinline__ void mbar_spin31(uint32_t bar, uint32_t ph) {
  asm volatile("{\n.reg .pred p;\n.reg .b64 s;\nmov.b64 s, {%1, %1};\nLAB_WAIT:\nmbarrier.try_wait.shared::cta.b64 p, [%0], s;\n@!p pmevent 7;\n@!p bra.uni LAB_WAIT;\n}" ::"r"(bar), "r"(ph) : "memory");
}
__device__ __forceinline__ bool elect_one() {
  uint32_t p;
  asm volatile("{\n.reg .pred P;\nelect.sync _|P, 0xffffffff;\nselp.u32 %0, 1, 0, P;\n}" : "=r"(p));
  return p != 0;
}
__device__ __forceinline__ bool mbar_test(uint32_t bar, uint32_t parity) {
  uint32_t ok;
  asm volatile("{\n.reg .pred p;\nmbarrier.test_wait.parity.shared::cta.b64 p, [%1], %2;\nselp.u32 %0, 1, 0, p;\n}" : "=r"(ok) : "r"(bar), "r"(parity) : "memory");
  return ok != 0;
}
__device__ __forceinline__ void tma_ld2(uint32_t dst, const CUtensorMap* tm, int c0, int c1, uint32_t bar) {
  asm volatile("cp.async.bulk.tensor.2d.shared::cluster.global.mbarrier::complete_tx::bytes [%0], [%1, {%3, %4}], [%2];" ::"r"(dst), "l"(tm), "r"(bar), "r"(c0), "r"(c1) : "memory");
}
__device__ __forceinline__ void tma_ld4(uint32_t dst, const CUtensorMap* tm, int c1, int c2, int c3, uint32_t bar, uint64_t pol = 0x1000000000000000ull) {
  asm volatile("cp.async.bulk.tensor.4d.shared::cluster.global.mbarrier::complete_tx::bytes.L2::cache_hint [%0], [%1, {%3, %4, %5, %6}], [%2], %7;" ::"r"(dst), "l"(tm), "r"(bar), "r"(0), "r"(c1), "r"(c2), "r"(c3), "l"(pol) : "memory");
}
__device__ __forceinline__ void tma_st2(const CUtensorMap* tm, int c0, int c1, uint32_t src) {
  asm volatile("cp.async.bulk.tensor.2d.global.shared::cta.bulk_group [%0, {%2, %3}], [%1];" ::"l"(tm), "r"(src), "r"(c0), "r"(c1) : "memory");
}
__device__ __forceinline__ void bulk_ld(uint32_t dst, const void* src, uint32_t bytes, uint32_t bar) {
  asm volatile("cp.async.bulk.shared::cluster.global.mbarrier::complete_tx::bytes [%0], [%1], %2, [%3];" ::"r"(dst), "l"(src), "r"(bytes), "r"(bar) : "memory");
}
__device__ __forceinline__ void e_arrive(uint32_t bar, uint32_t cnt) {
  if (cnt == 1) asm volatile("{\n.reg .pred p;\nelect.sync _|p, 0xffffffff;\n@p mbarrier.arrive.shared::cta.b64 _, [%0];\n}" ::"r"(bar) : "memory");
  else asm volatile("{\n.reg .pred p;\nelect.sync _|p, 0xffffffff;\n@p mbarrier.arrive.shared::cta.b64 _, [%0], %1;\n}" ::"r"(bar), "r"(cnt) : "memory");
}
template <int BYTES = 8192> __device__ __forceinline__ void e_load(uint32_t dst, const CUtensorMap* tm, int c0, int c1, uint32_t bar, uint64_t pol = 0x1000000000000000ull) {
  asm volatile("{\n.reg .pred p;\nelect.sync _|p, 0xffffffff;\n@p mbarrier.arrive.expect_tx.shared::cta.b64 _, [%2], %5;\n"
               "@p cp.async.bulk.tensor.2d.shared::cluster.global.mbarrier::complete_tx::bytes.L2::cache_hint [%0], [%1, {%3, %4}], [%2], %6;\n}"
               ::"r"(dst), "l"(tm), "r"(bar), "r"(c0), "r"(c1), "n"(BYTES), "l"(pol) : "memory");
}
__device__ __forceinline__ void e_store(const CUtensorMap* tm, int c0, int c1, uint32_t src) {
  asm volatile("{\n.reg .pred p;\nfence.proxy.async.shared::cta;\nelect.sync _|p, 0xffffffff;\n"
               "@p cp.async.bulk.tensor.2d.global.shared::cta.bulk_group [%0, {%2, %3}], [%1];\ncp.async.bulk.commit_group;\n}"
               ::"l"(tm), "r"(src), "r"(c0), "r"(c1) : "memory");
}
__device__ __forceinline__ void bulk_commit() { asm volatile("cp.async.bulk.commit_group;" ::: "memory"); }
template <int N> __device__ __forceinline__ void bulk_wait_read() { asm volatile("cp.async.bulk.wait_group.read %0;" ::"n"(N) : "memory"); }
__device__ __forceinline__ void bulk_wait_all() { asm volatile("cp.async.bulk.wait_group 0;" ::: "memory"); }
__device__ __forceinline__ void fence_async_smem() { asm volatile("fence.proxy.async.shared::cta;" ::: "memory"); }
__device__ __forceinline__ void wg_fence() { asm volatile("wgmma.fence.sync.aligned;" ::: "memory"); }
__device__ __forceinline__ void wg_commit() { asm volatile("wgmma.commit_group.sync.aligned;" ::: "memory"); }
template <int N> __device__ __forceinline__ void wg_wait() { asm volatile("wgmma.wait_group.sync.aligned %0;" ::"n"(N) : "memory"); }
__device__ __forceinline__ void wg_bar(int w) { asm volatile("bar.sync %0, 128;" ::"r"(w + 1) : "memory"); }
__device__ __forceinline__ uint32_t ld_acquire(const uint32_t* p) { uint32_t v; asm volatile("ld.acquire.gpu.global.u32 %0, [%1];" : "=r"(v) : "l"(p) : "memory"); return v; }
__device__ __forceinline__ uint4 ld_relaxed4(const uint32_t* p) {
  uint4 v; asm volatile("ld.relaxed.gpu.global.v4.u32 {%0,%1,%2,%3}, [%4];" : "=r"(v.x), "=r"(v.y), "=r"(v.z), "=r"(v.w) : "l"(p) : "memory"); return v;
}
__device__ __forceinline__ void st_release8(uint8_t* p, uint32_t v) { asm volatile("st.release.gpu.global.u8 [%0], %1;" ::"l"(p), "r"(v) : "memory"); }
__device__ __forceinline__ uint32_t ld_relaxed(const uint32_t* p) { uint32_t v; asm volatile("ld.relaxed.gpu.global.u32 %0, [%1];" : "=r"(v) : "l"(p) : "memory"); return v; }
__device__ __forceinline__ void st_release(uint32_t* p, uint32_t v) { asm volatile("st.release.gpu.global.u32 [%0], %1;" ::"l"(p), "r"(v) : "memory"); }
__device__ __forceinline__ void st_pkt(uint4* p, uint32_t a, uint32_t b, uint32_t c, uint32_t d) {
  asm volatile("{\n.reg .b64 lo, hi;\n.reg .b128 v;\nmov.b64 lo, {%1, %2};\nmov.b64 hi, {%3, %4};\nmov.b128 v, {lo, hi};\nst.relaxed.gpu.global.b128 [%0], v;\n}" ::"l"(p), "r"(a), "r"(b), "r"(c), "r"(d) : "memory");
}
__device__ __forceinline__ uint4 ld_pkt(const uint4* p) {
  uint4 r;
  asm volatile("{\n.reg .b64 lo, hi;\n.reg .b128 v;\nld.relaxed.gpu.global.b128 v, [%4];\nmov.b128 {lo, hi}, v;\nmov.b64 {%0, %1}, lo;\nmov.b64 {%2, %3}, hi;\n}" : "=r"(r.x), "=r"(r.y), "=r"(r.z), "=r"(r.w) : "l"(p) : "memory");
  return r;
}
__device__ __forceinline__ uint32_t pack_bf16(float lo, float hi) { uint32_t d; asm("cvt.rn.bf16x2.f32 %0, %1, %2;" : "=r"(d) : "f"(hi), "f"(lo)); return d; }
__device__ __forceinline__ float ex2(float x) { float y; asm("ex2.approx.ftz.f32 %0, %1;" : "=f"(y) : "f"(x)); return y; }
__device__ __forceinline__ float rsq(float x) { float y; asm("rsqrt.approx.ftz.f32 %0, %1;" : "=f"(y) : "f"(x)); return y; }
__device__ __forceinline__ float rcp(float x) { float y; asm("rcp.approx.ftz.f32 %0, %1;" : "=f"(y) : "f"(x)); return y; }
__device__ __forceinline__ float bf_lo(uint32_t v) { return __uint_as_float(v << 16); }
__device__ __forceinline__ float bf_hi(uint32_t v) { return __uint_as_float(v & 0xffff0000u); }
__device__ __forceinline__ void stsm4(uint32_t addr, uint32_t a, uint32_t b, uint32_t c, uint32_t d) {
  asm volatile("stmatrix.sync.aligned.m8n8.x4.shared.b16 [%0], {%1, %2, %3, %4};" ::"r"(addr), "r"(a), "r"(b), "r"(c), "r"(d) : "memory");
}
__device__ __forceinline__ uint32_t movm(uint32_t a) { uint32_t d; asm volatile("movmatrix.sync.aligned.m8n8.trans.b16 %0, %1;" : "=r"(d) : "r"(a)); return d; }
__device__ __forceinline__ void mma16(float (&c)[4], uint32_t a0, uint32_t a1, uint32_t a2, uint32_t a3, uint32_t b0, uint32_t b1) {
  asm volatile("mma.sync.aligned.m16n8k16.row.col.f32.bf16.bf16.f32 {%0,%1,%2,%3}, {%4,%5,%6,%7}, {%8,%9}, {%0,%1,%2,%3};"
               : "+f"(c[0]), "+f"(c[1]), "+f"(c[2]), "+f"(c[3]) : "r"(a0), "r"(a1), "r"(a2), "r"(a3), "r"(b0), "r"(b1));
}
__device__ __forceinline__ void mma8(float (&c)[4], uint32_t a0, uint32_t a1, uint32_t b0) {
  asm volatile("mma.sync.aligned.m16n8k8.row.col.f32.bf16.bf16.f32 {%0,%1,%2,%3}, {%4,%5}, {%6}, {%0,%1,%2,%3};"
               : "+f"(c[0]), "+f"(c[1]), "+f"(c[2]), "+f"(c[3]) : "r"(a0), "r"(a1), "r"(b0));
}
__device__ __forceinline__ void sts128(uint32_t a, uint32_t x, uint32_t y, uint32_t z, uint32_t w) {
  asm volatile("st.shared.v4.b32 [%0], {%1,%2,%3,%4};" ::"r"(a), "r"(x), "r"(y), "r"(z), "r"(w) : "memory");
}
__device__ __forceinline__ float2 lds64(uint32_t a) { float2 v; asm volatile("ld.shared.v2.f32 {%0,%1}, [%2];" : "=f"(v.x), "=f"(v.y) : "r"(a)); return v; }
__device__ __forceinline__ float4 lds128(uint32_t a) { float4 v; asm volatile("ld.shared.v4.f32 {%0,%1,%2,%3}, [%4];" : "=f"(v.x), "=f"(v.y), "=f"(v.z), "=f"(v.w) : "r"(a)); return v; }
__device__ __forceinline__ uint32_t lds32(uint32_t a) { uint32_t v; asm volatile("ld.shared.b32 %0, [%1];" : "=r"(v) : "r"(a)); return v; }
constexpr uint32_t PA1 = 0x80000000u / NA + 1, G1 = 8 + (1u << 28);
constexpr uint32_t DA0 = ((SB + OFF_A) >> 4) | (1u << 16), DB0 = ((SB + OFF_B) >> 4) | (512u << 16);
template <int S> __device__ __forceinline__ uint2 wgmma_first128(float (&d)[S], uint32_t da, uint32_t& db, uint32_t h0, uint32_t h1, uint32_t one, uint32_t b0, uint32_t p0, uint32_t b1, uint32_t p1) {
  uint2 ok;
  asm volatile("{\n.reg .b64 a, b, s;\n.reg .b32 t, u;\n.reg .pred p, q;\nwgmma.fence.sync.aligned;\n"
    "mov.b32 t, %67;\n"
    "mov.b64 a, {t, %68};\nmov.b64 b, {%66, %69};\n"
    "wgmma.mma_async.sync.aligned.m64n128k16.f32.bf16.bf16 "
    "{%2, %3, %4, %5, %6, %7, %8, %9, %10, %11, %12, %13, %14, %15, %16, %17, %18, %19, %20, %21, %22, %23, %24, %25, %26, %27, %28, %29, %30, %31, %32, %33, %34, %35, %36, %37, %38, %39, %40, %41, %42, %43, %44, %45, %46, %47, %48, %49, %50, %51, %52, %53, %54, %55, %56, %57, %58, %59, %60, %61, %62, %63, %64, %65}, "
    "a, b, 0, 1, 1, 0, 1;\n"
    "mad.lo.u32 t, %70, 2, t;\nmad.lo.u32 %66, %70, 128, %66;\n"
    "mov.b64 a, {t, %68};\nmov.b64 b, {%66, %69};\n"
    "wgmma.mma_async.sync.aligned.m64n128k16.f32.bf16.bf16 "
    "{%2, %3, %4, %5, %6, %7, %8, %9, %10, %11, %12, %13, %14, %15, %16, %17, %18, %19, %20, %21, %22, %23, %24, %25, %26, %27, %28, %29, %30, %31, %32, %33, %34, %35, %36, %37, %38, %39, %40, %41, %42, %43, %44, %45, %46, %47, %48, %49, %50, %51, %52, %53, %54, %55, %56, %57, %58, %59, %60, %61, %62, %63, %64, %65}, "
    "a, b, 1, 1, 1, 0, 1;\n"
    "mad.lo.u32 t, %70, 2, t;\nmad.lo.u32 %66, %70, 128, %66;\n"
    "mov.b64 a, {t, %68};\nmov.b64 b, {%66, %69};\n"
    "wgmma.mma_async.sync.aligned.m64n128k16.f32.bf16.bf16 "
    "{%2, %3, %4, %5, %6, %7, %8, %9, %10, %11, %12, %13, %14, %15, %16, %17, %18, %19, %20, %21, %22, %23, %24, %25, %26, %27, %28, %29, %30, %31, %32, %33, %34, %35, %36, %37, %38, %39, %40, %41, %42, %43, %44, %45, %46, %47, %48, %49, %50, %51, %52, %53, %54, %55, %56, %57, %58, %59, %60, %61, %62, %63, %64, %65}, "
    "a, b, 1, 1, 1, 0, 1;\n"
    "mov.b64 s, {%72, %72};\nmbarrier.test_wait.shared::cta.b64 p, [%71], s;\nmov.b64 s, {%74, %74};\nmbarrier.test_wait.shared::cta.b64 q, [%73], s;\n"
    "mad.lo.u32 t, %70, 2, t;\nmad.lo.u32 %66, %70, 128, %66;\n"
    "mov.b64 a, {t, %68};\nmov.b64 b, {%66, %69};\n"
    "wgmma.mma_async.sync.aligned.m64n128k16.f32.bf16.bf16 "
    "{%2, %3, %4, %5, %6, %7, %8, %9, %10, %11, %12, %13, %14, %15, %16, %17, %18, %19, %20, %21, %22, %23, %24, %25, %26, %27, %28, %29, %30, %31, %32, %33, %34, %35, %36, %37, %38, %39, %40, %41, %42, %43, %44, %45, %46, %47, %48, %49, %50, %51, %52, %53, %54, %55, %56, %57, %58, %59, %60, %61, %62, %63, %64, %65}, "
    "a, b, 1, 1, 1, 0, 1;\n"
    "wgmma.commit_group.sync.aligned;\nselp.u32 %0, 1, 0, p;\nselp.u32 %1, 1, 0, q;\n}"
    : "=r"(ok.x), "=r"(ok.y), "=f"(d[0]), "=f"(d[1]), "=f"(d[2]), "=f"(d[3]), "=f"(d[4]), "=f"(d[5]), "=f"(d[6]), "=f"(d[7]), "=f"(d[8]), "=f"(d[9]), "=f"(d[10]), "=f"(d[11]), "=f"(d[12]), "=f"(d[13]), "=f"(d[14]), "=f"(d[15]), "=f"(d[16]), "=f"(d[17]), "=f"(d[18]), "=f"(d[19]), "=f"(d[20]), "=f"(d[21]), "=f"(d[22]), "=f"(d[23]), "=f"(d[24]), "=f"(d[25]), "=f"(d[26]), "=f"(d[27]), "=f"(d[28]), "=f"(d[29]), "=f"(d[30]), "=f"(d[31]), "=f"(d[32]), "=f"(d[33]), "=f"(d[34]), "=f"(d[35]), "=f"(d[36]), "=f"(d[37]), "=f"(d[38]), "=f"(d[39]), "=f"(d[40]), "=f"(d[41]), "=f"(d[42]), "=f"(d[43]), "=f"(d[44]), "=f"(d[45]), "=f"(d[46]), "=f"(d[47]), "=f"(d[48]), "=f"(d[49]), "=f"(d[50]), "=f"(d[51]), "=f"(d[52]), "=f"(d[53]), "=f"(d[54]), "=f"(d[55]), "=f"(d[56]), "=f"(d[57]), "=f"(d[58]), "=f"(d[59]), "=f"(d[60]), "=f"(d[61]), "=f"(d[62]), "=f"(d[63]), "+r"(db)
    : "r"(da), "r"(h0), "r"(h1), "r"(one), "r"(b0), "r"(p0), "r"(b1), "r"(p1) : "memory");
  return ok;
}
template <int S> __device__ __forceinline__ uint2 wgmma_step128(float (&d)[S], uint32_t da, uint32_t& db, uint32_t h0, uint32_t h1, uint32_t one, uint32_t b0, uint32_t p0, uint32_t b1, uint32_t p1) {
  uint2 ok;
  asm volatile("{\n.reg .b64 a, b, s;\n.reg .b32 t, u;\n.reg .pred p, q;\nwgmma.fence.sync.aligned;\n"
    "mov.b32 t, %67;\n"
    "mov.b64 a, {t, %68};\nmov.b64 b, {%66, %69};\n"
    "wgmma.mma_async.sync.aligned.m64n128k16.f32.bf16.bf16 "
    "{%2, %3, %4, %5, %6, %7, %8, %9, %10, %11, %12, %13, %14, %15, %16, %17, %18, %19, %20, %21, %22, %23, %24, %25, %26, %27, %28, %29, %30, %31, %32, %33, %34, %35, %36, %37, %38, %39, %40, %41, %42, %43, %44, %45, %46, %47, %48, %49, %50, %51, %52, %53, %54, %55, %56, %57, %58, %59, %60, %61, %62, %63, %64, %65}, "
    "a, b, 1, 1, 1, 0, 1;\n"
    "mad.lo.u32 t, %70, 2, t;\nmad.lo.u32 %66, %70, 128, %66;\n"
    "mov.b64 a, {t, %68};\nmov.b64 b, {%66, %69};\n"
    "wgmma.mma_async.sync.aligned.m64n128k16.f32.bf16.bf16 "
    "{%2, %3, %4, %5, %6, %7, %8, %9, %10, %11, %12, %13, %14, %15, %16, %17, %18, %19, %20, %21, %22, %23, %24, %25, %26, %27, %28, %29, %30, %31, %32, %33, %34, %35, %36, %37, %38, %39, %40, %41, %42, %43, %44, %45, %46, %47, %48, %49, %50, %51, %52, %53, %54, %55, %56, %57, %58, %59, %60, %61, %62, %63, %64, %65}, "
    "a, b, 1, 1, 1, 0, 1;\n"
    "mad.lo.u32 t, %70, 2, t;\nmad.lo.u32 %66, %70, 128, %66;\n"
    "mov.b64 a, {t, %68};\nmov.b64 b, {%66, %69};\n"
    "wgmma.mma_async.sync.aligned.m64n128k16.f32.bf16.bf16 "
    "{%2, %3, %4, %5, %6, %7, %8, %9, %10, %11, %12, %13, %14, %15, %16, %17, %18, %19, %20, %21, %22, %23, %24, %25, %26, %27, %28, %29, %30, %31, %32, %33, %34, %35, %36, %37, %38, %39, %40, %41, %42, %43, %44, %45, %46, %47, %48, %49, %50, %51, %52, %53, %54, %55, %56, %57, %58, %59, %60, %61, %62, %63, %64, %65}, "
    "a, b, 1, 1, 1, 0, 1;\n"
    "mov.b64 s, {%72, %72};\nmbarrier.test_wait.shared::cta.b64 p, [%71], s;\nmov.b64 s, {%74, %74};\nmbarrier.test_wait.shared::cta.b64 q, [%73], s;\n"
    "mad.lo.u32 t, %70, 2, t;\nmad.lo.u32 %66, %70, 128, %66;\n"
    "mov.b64 a, {t, %68};\nmov.b64 b, {%66, %69};\n"
    "wgmma.mma_async.sync.aligned.m64n128k16.f32.bf16.bf16 "
    "{%2, %3, %4, %5, %6, %7, %8, %9, %10, %11, %12, %13, %14, %15, %16, %17, %18, %19, %20, %21, %22, %23, %24, %25, %26, %27, %28, %29, %30, %31, %32, %33, %34, %35, %36, %37, %38, %39, %40, %41, %42, %43, %44, %45, %46, %47, %48, %49, %50, %51, %52, %53, %54, %55, %56, %57, %58, %59, %60, %61, %62, %63, %64, %65}, "
    "a, b, 1, 1, 1, 0, 1;\n"
    "wgmma.commit_group.sync.aligned;\nselp.u32 %0, 1, 0, p;\nselp.u32 %1, 1, 0, q;\n}"
    : "=r"(ok.x), "=r"(ok.y), "+f"(d[0]), "+f"(d[1]), "+f"(d[2]), "+f"(d[3]), "+f"(d[4]), "+f"(d[5]), "+f"(d[6]), "+f"(d[7]), "+f"(d[8]), "+f"(d[9]), "+f"(d[10]), "+f"(d[11]), "+f"(d[12]), "+f"(d[13]), "+f"(d[14]), "+f"(d[15]), "+f"(d[16]), "+f"(d[17]), "+f"(d[18]), "+f"(d[19]), "+f"(d[20]), "+f"(d[21]), "+f"(d[22]), "+f"(d[23]), "+f"(d[24]), "+f"(d[25]), "+f"(d[26]), "+f"(d[27]), "+f"(d[28]), "+f"(d[29]), "+f"(d[30]), "+f"(d[31]), "+f"(d[32]), "+f"(d[33]), "+f"(d[34]), "+f"(d[35]), "+f"(d[36]), "+f"(d[37]), "+f"(d[38]), "+f"(d[39]), "+f"(d[40]), "+f"(d[41]), "+f"(d[42]), "+f"(d[43]), "+f"(d[44]), "+f"(d[45]), "+f"(d[46]), "+f"(d[47]), "+f"(d[48]), "+f"(d[49]), "+f"(d[50]), "+f"(d[51]), "+f"(d[52]), "+f"(d[53]), "+f"(d[54]), "+f"(d[55]), "+f"(d[56]), "+f"(d[57]), "+f"(d[58]), "+f"(d[59]), "+f"(d[60]), "+f"(d[61]), "+f"(d[62]), "+f"(d[63]), "+r"(db)
    : "r"(da), "r"(h0), "r"(h1), "r"(one), "r"(b0), "r"(p0), "r"(b1), "r"(p1) : "memory");
  return ok;
}
template <int S> __device__ __forceinline__ uint2 wgmma_first192(float (&d)[S], uint32_t da, uint32_t& db, uint32_t h0, uint32_t h1, uint32_t one, uint32_t b0, uint32_t p0, uint32_t b1, uint32_t p1) {
  uint2 ok;
  asm volatile("{\n.reg .b64 a, b, s;\n.reg .b32 t, u;\n.reg .pred p, q;\nwgmma.fence.sync.aligned;\n"
    "mov.b32 t, %99;\n"
    "mov.b64 a, {t, %100};\nmov.b64 b, {%98, %101};\n"
    "wgmma.mma_async.sync.aligned.m64n192k16.f32.bf16.bf16 "
    "{%2, %3, %4, %5, %6, %7, %8, %9, %10, %11, %12, %13, %14, %15, %16, %17, %18, %19, %20, %21, %22, %23, %24, %25, %26, %27, %28, %29, %30, %31, %32, %33, %34, %35, %36, %37, %38, %39, %40, %41, %42, %43, %44, %45, %46, %47, %48, %49, %50, %51, %52, %53, %54, %55, %56, %57, %58, %59, %60, %61, %62, %63, %64, %65, %66, %67, %68, %69, %70, %71, %72, %73, %74, %75, %76, %77, %78, %79, %80, %81, %82, %83, %84, %85, %86, %87, %88, %89, %90, %91, %92, %93, %94, %95, %96, %97}, "
    "a, b, 0, 1, 1, 0, 1;\n"
    "mad.lo.u32 t, %102, 2, t;\nmad.lo.u32 %98, %102, 128, %98;\n"
    "mov.b64 a, {t, %100};\nmov.b64 b, {%98, %101};\n"
    "wgmma.mma_async.sync.aligned.m64n192k16.f32.bf16.bf16 "
    "{%2, %3, %4, %5, %6, %7, %8, %9, %10, %11, %12, %13, %14, %15, %16, %17, %18, %19, %20, %21, %22, %23, %24, %25, %26, %27, %28, %29, %30, %31, %32, %33, %34, %35, %36, %37, %38, %39, %40, %41, %42, %43, %44, %45, %46, %47, %48, %49, %50, %51, %52, %53, %54, %55, %56, %57, %58, %59, %60, %61, %62, %63, %64, %65, %66, %67, %68, %69, %70, %71, %72, %73, %74, %75, %76, %77, %78, %79, %80, %81, %82, %83, %84, %85, %86, %87, %88, %89, %90, %91, %92, %93, %94, %95, %96, %97}, "
    "a, b, 1, 1, 1, 0, 1;\n"
    "mad.lo.u32 t, %102, 2, t;\nmad.lo.u32 %98, %102, 128, %98;\n"
    "mov.b64 a, {t, %100};\nmov.b64 b, {%98, %101};\n"
    "wgmma.mma_async.sync.aligned.m64n192k16.f32.bf16.bf16 "
    "{%2, %3, %4, %5, %6, %7, %8, %9, %10, %11, %12, %13, %14, %15, %16, %17, %18, %19, %20, %21, %22, %23, %24, %25, %26, %27, %28, %29, %30, %31, %32, %33, %34, %35, %36, %37, %38, %39, %40, %41, %42, %43, %44, %45, %46, %47, %48, %49, %50, %51, %52, %53, %54, %55, %56, %57, %58, %59, %60, %61, %62, %63, %64, %65, %66, %67, %68, %69, %70, %71, %72, %73, %74, %75, %76, %77, %78, %79, %80, %81, %82, %83, %84, %85, %86, %87, %88, %89, %90, %91, %92, %93, %94, %95, %96, %97}, "
    "a, b, 1, 1, 1, 0, 1;\n"
    "mov.b64 s, {%104, %104};\nmbarrier.test_wait.shared::cta.b64 p, [%103], s;\nmov.b64 s, {%106, %106};\nmbarrier.test_wait.shared::cta.b64 q, [%105], s;\n"
    "mad.lo.u32 t, %102, 2, t;\nmad.lo.u32 %98, %102, 128, %98;\n"
    "mov.b64 a, {t, %100};\nmov.b64 b, {%98, %101};\n"
    "wgmma.mma_async.sync.aligned.m64n192k16.f32.bf16.bf16 "
    "{%2, %3, %4, %5, %6, %7, %8, %9, %10, %11, %12, %13, %14, %15, %16, %17, %18, %19, %20, %21, %22, %23, %24, %25, %26, %27, %28, %29, %30, %31, %32, %33, %34, %35, %36, %37, %38, %39, %40, %41, %42, %43, %44, %45, %46, %47, %48, %49, %50, %51, %52, %53, %54, %55, %56, %57, %58, %59, %60, %61, %62, %63, %64, %65, %66, %67, %68, %69, %70, %71, %72, %73, %74, %75, %76, %77, %78, %79, %80, %81, %82, %83, %84, %85, %86, %87, %88, %89, %90, %91, %92, %93, %94, %95, %96, %97}, "
    "a, b, 1, 1, 1, 0, 1;\n"
    "wgmma.commit_group.sync.aligned;\nselp.u32 %0, 1, 0, p;\nselp.u32 %1, 1, 0, q;\n}"
    : "=r"(ok.x), "=r"(ok.y), "=f"(d[0]), "=f"(d[1]), "=f"(d[2]), "=f"(d[3]), "=f"(d[4]), "=f"(d[5]), "=f"(d[6]), "=f"(d[7]), "=f"(d[8]), "=f"(d[9]), "=f"(d[10]), "=f"(d[11]), "=f"(d[12]), "=f"(d[13]), "=f"(d[14]), "=f"(d[15]), "=f"(d[16]), "=f"(d[17]), "=f"(d[18]), "=f"(d[19]), "=f"(d[20]), "=f"(d[21]), "=f"(d[22]), "=f"(d[23]), "=f"(d[24]), "=f"(d[25]), "=f"(d[26]), "=f"(d[27]), "=f"(d[28]), "=f"(d[29]), "=f"(d[30]), "=f"(d[31]), "=f"(d[32]), "=f"(d[33]), "=f"(d[34]), "=f"(d[35]), "=f"(d[36]), "=f"(d[37]), "=f"(d[38]), "=f"(d[39]), "=f"(d[40]), "=f"(d[41]), "=f"(d[42]), "=f"(d[43]), "=f"(d[44]), "=f"(d[45]), "=f"(d[46]), "=f"(d[47]), "=f"(d[48]), "=f"(d[49]), "=f"(d[50]), "=f"(d[51]), "=f"(d[52]), "=f"(d[53]), "=f"(d[54]), "=f"(d[55]), "=f"(d[56]), "=f"(d[57]), "=f"(d[58]), "=f"(d[59]), "=f"(d[60]), "=f"(d[61]), "=f"(d[62]), "=f"(d[63]), "=f"(d[64]), "=f"(d[65]), "=f"(d[66]), "=f"(d[67]), "=f"(d[68]), "=f"(d[69]), "=f"(d[70]), "=f"(d[71]), "=f"(d[72]), "=f"(d[73]), "=f"(d[74]), "=f"(d[75]), "=f"(d[76]), "=f"(d[77]), "=f"(d[78]), "=f"(d[79]), "=f"(d[80]), "=f"(d[81]), "=f"(d[82]), "=f"(d[83]), "=f"(d[84]), "=f"(d[85]), "=f"(d[86]), "=f"(d[87]), "=f"(d[88]), "=f"(d[89]), "=f"(d[90]), "=f"(d[91]), "=f"(d[92]), "=f"(d[93]), "=f"(d[94]), "=f"(d[95]), "+r"(db)
    : "r"(da), "r"(h0), "r"(h1), "r"(one), "r"(b0), "r"(p0), "r"(b1), "r"(p1) : "memory");
  return ok;
}
template <int S> __device__ __forceinline__ uint2 wgmma_step192(float (&d)[S], uint32_t da, uint32_t& db, uint32_t h0, uint32_t h1, uint32_t one, uint32_t b0, uint32_t p0, uint32_t b1, uint32_t p1) {
  uint2 ok;
  asm volatile("{\n.reg .b64 a, b, s;\n.reg .b32 t, u;\n.reg .pred p, q;\nwgmma.fence.sync.aligned;\n"
    "mov.b32 t, %99;\n"
    "mov.b64 a, {t, %100};\nmov.b64 b, {%98, %101};\n"
    "wgmma.mma_async.sync.aligned.m64n192k16.f32.bf16.bf16 "
    "{%2, %3, %4, %5, %6, %7, %8, %9, %10, %11, %12, %13, %14, %15, %16, %17, %18, %19, %20, %21, %22, %23, %24, %25, %26, %27, %28, %29, %30, %31, %32, %33, %34, %35, %36, %37, %38, %39, %40, %41, %42, %43, %44, %45, %46, %47, %48, %49, %50, %51, %52, %53, %54, %55, %56, %57, %58, %59, %60, %61, %62, %63, %64, %65, %66, %67, %68, %69, %70, %71, %72, %73, %74, %75, %76, %77, %78, %79, %80, %81, %82, %83, %84, %85, %86, %87, %88, %89, %90, %91, %92, %93, %94, %95, %96, %97}, "
    "a, b, 1, 1, 1, 0, 1;\n"
    "mad.lo.u32 t, %102, 2, t;\nmad.lo.u32 %98, %102, 128, %98;\n"
    "mov.b64 a, {t, %100};\nmov.b64 b, {%98, %101};\n"
    "wgmma.mma_async.sync.aligned.m64n192k16.f32.bf16.bf16 "
    "{%2, %3, %4, %5, %6, %7, %8, %9, %10, %11, %12, %13, %14, %15, %16, %17, %18, %19, %20, %21, %22, %23, %24, %25, %26, %27, %28, %29, %30, %31, %32, %33, %34, %35, %36, %37, %38, %39, %40, %41, %42, %43, %44, %45, %46, %47, %48, %49, %50, %51, %52, %53, %54, %55, %56, %57, %58, %59, %60, %61, %62, %63, %64, %65, %66, %67, %68, %69, %70, %71, %72, %73, %74, %75, %76, %77, %78, %79, %80, %81, %82, %83, %84, %85, %86, %87, %88, %89, %90, %91, %92, %93, %94, %95, %96, %97}, "
    "a, b, 1, 1, 1, 0, 1;\n"
    "mad.lo.u32 t, %102, 2, t;\nmad.lo.u32 %98, %102, 128, %98;\n"
    "mov.b64 a, {t, %100};\nmov.b64 b, {%98, %101};\n"
    "wgmma.mma_async.sync.aligned.m64n192k16.f32.bf16.bf16 "
    "{%2, %3, %4, %5, %6, %7, %8, %9, %10, %11, %12, %13, %14, %15, %16, %17, %18, %19, %20, %21, %22, %23, %24, %25, %26, %27, %28, %29, %30, %31, %32, %33, %34, %35, %36, %37, %38, %39, %40, %41, %42, %43, %44, %45, %46, %47, %48, %49, %50, %51, %52, %53, %54, %55, %56, %57, %58, %59, %60, %61, %62, %63, %64, %65, %66, %67, %68, %69, %70, %71, %72, %73, %74, %75, %76, %77, %78, %79, %80, %81, %82, %83, %84, %85, %86, %87, %88, %89, %90, %91, %92, %93, %94, %95, %96, %97}, "
    "a, b, 1, 1, 1, 0, 1;\n"
    "mov.b64 s, {%104, %104};\nmbarrier.test_wait.shared::cta.b64 p, [%103], s;\nmov.b64 s, {%106, %106};\nmbarrier.test_wait.shared::cta.b64 q, [%105], s;\n"
    "mad.lo.u32 t, %102, 2, t;\nmad.lo.u32 %98, %102, 128, %98;\n"
    "mov.b64 a, {t, %100};\nmov.b64 b, {%98, %101};\n"
    "wgmma.mma_async.sync.aligned.m64n192k16.f32.bf16.bf16 "
    "{%2, %3, %4, %5, %6, %7, %8, %9, %10, %11, %12, %13, %14, %15, %16, %17, %18, %19, %20, %21, %22, %23, %24, %25, %26, %27, %28, %29, %30, %31, %32, %33, %34, %35, %36, %37, %38, %39, %40, %41, %42, %43, %44, %45, %46, %47, %48, %49, %50, %51, %52, %53, %54, %55, %56, %57, %58, %59, %60, %61, %62, %63, %64, %65, %66, %67, %68, %69, %70, %71, %72, %73, %74, %75, %76, %77, %78, %79, %80, %81, %82, %83, %84, %85, %86, %87, %88, %89, %90, %91, %92, %93, %94, %95, %96, %97}, "
    "a, b, 1, 1, 1, 0, 1;\n"
    "wgmma.commit_group.sync.aligned;\nselp.u32 %0, 1, 0, p;\nselp.u32 %1, 1, 0, q;\n}"
    : "=r"(ok.x), "=r"(ok.y), "+f"(d[0]), "+f"(d[1]), "+f"(d[2]), "+f"(d[3]), "+f"(d[4]), "+f"(d[5]), "+f"(d[6]), "+f"(d[7]), "+f"(d[8]), "+f"(d[9]), "+f"(d[10]), "+f"(d[11]), "+f"(d[12]), "+f"(d[13]), "+f"(d[14]), "+f"(d[15]), "+f"(d[16]), "+f"(d[17]), "+f"(d[18]), "+f"(d[19]), "+f"(d[20]), "+f"(d[21]), "+f"(d[22]), "+f"(d[23]), "+f"(d[24]), "+f"(d[25]), "+f"(d[26]), "+f"(d[27]), "+f"(d[28]), "+f"(d[29]), "+f"(d[30]), "+f"(d[31]), "+f"(d[32]), "+f"(d[33]), "+f"(d[34]), "+f"(d[35]), "+f"(d[36]), "+f"(d[37]), "+f"(d[38]), "+f"(d[39]), "+f"(d[40]), "+f"(d[41]), "+f"(d[42]), "+f"(d[43]), "+f"(d[44]), "+f"(d[45]), "+f"(d[46]), "+f"(d[47]), "+f"(d[48]), "+f"(d[49]), "+f"(d[50]), "+f"(d[51]), "+f"(d[52]), "+f"(d[53]), "+f"(d[54]), "+f"(d[55]), "+f"(d[56]), "+f"(d[57]), "+f"(d[58]), "+f"(d[59]), "+f"(d[60]), "+f"(d[61]), "+f"(d[62]), "+f"(d[63]), "+f"(d[64]), "+f"(d[65]), "+f"(d[66]), "+f"(d[67]), "+f"(d[68]), "+f"(d[69]), "+f"(d[70]), "+f"(d[71]), "+f"(d[72]), "+f"(d[73]), "+f"(d[74]), "+f"(d[75]), "+f"(d[76]), "+f"(d[77]), "+f"(d[78]), "+f"(d[79]), "+f"(d[80]), "+f"(d[81]), "+f"(d[82]), "+f"(d[83]), "+f"(d[84]), "+f"(d[85]), "+f"(d[86]), "+f"(d[87]), "+f"(d[88]), "+f"(d[89]), "+f"(d[90]), "+f"(d[91]), "+f"(d[92]), "+f"(d[93]), "+f"(d[94]), "+f"(d[95]), "+r"(db)
    : "r"(da), "r"(h0), "r"(h1), "r"(one), "r"(b0), "r"(p0), "r"(b1), "r"(p1) : "memory");
  return ok;
}
template <int S> __device__ __forceinline__ uint2 wgmma_first256(float (&d)[S], uint32_t da, uint32_t& db, uint32_t h0, uint32_t h1, uint32_t one, uint32_t b0, uint32_t p0, uint32_t b1, uint32_t p1) {
  uint2 ok;
  asm volatile("{\n.reg .b64 a, b, s;\n.reg .b32 t, u;\n.reg .pred p, q;\nwgmma.fence.sync.aligned;\n"
    "mov.b32 t, %131;\n"
    "mov.b64 a, {t, %132};\nmov.b64 b, {%130, %133};\n"
    "wgmma.mma_async.sync.aligned.m64n256k16.f32.bf16.bf16 "
    "{%2, %3, %4, %5, %6, %7, %8, %9, %10, %11, %12, %13, %14, %15, %16, %17, %18, %19, %20, %21, %22, %23, %24, %25, %26, %27, %28, %29, %30, %31, %32, %33, %34, %35, %36, %37, %38, %39, %40, %41, %42, %43, %44, %45, %46, %47, %48, %49, %50, %51, %52, %53, %54, %55, %56, %57, %58, %59, %60, %61, %62, %63, %64, %65, %66, %67, %68, %69, %70, %71, %72, %73, %74, %75, %76, %77, %78, %79, %80, %81, %82, %83, %84, %85, %86, %87, %88, %89, %90, %91, %92, %93, %94, %95, %96, %97, %98, %99, %100, %101, %102, %103, %104, %105, %106, %107, %108, %109, %110, %111, %112, %113, %114, %115, %116, %117, %118, %119, %120, %121, %122, %123, %124, %125, %126, %127, %128, %129}, "
    "a, b, 0, 1, 1, 0, 1;\n"
    "mad.lo.u32 t, %134, 2, t;\nmad.lo.u32 %130, %134, 128, %130;\n"
    "mov.b64 a, {t, %132};\nmov.b64 b, {%130, %133};\n"
    "wgmma.mma_async.sync.aligned.m64n256k16.f32.bf16.bf16 "
    "{%2, %3, %4, %5, %6, %7, %8, %9, %10, %11, %12, %13, %14, %15, %16, %17, %18, %19, %20, %21, %22, %23, %24, %25, %26, %27, %28, %29, %30, %31, %32, %33, %34, %35, %36, %37, %38, %39, %40, %41, %42, %43, %44, %45, %46, %47, %48, %49, %50, %51, %52, %53, %54, %55, %56, %57, %58, %59, %60, %61, %62, %63, %64, %65, %66, %67, %68, %69, %70, %71, %72, %73, %74, %75, %76, %77, %78, %79, %80, %81, %82, %83, %84, %85, %86, %87, %88, %89, %90, %91, %92, %93, %94, %95, %96, %97, %98, %99, %100, %101, %102, %103, %104, %105, %106, %107, %108, %109, %110, %111, %112, %113, %114, %115, %116, %117, %118, %119, %120, %121, %122, %123, %124, %125, %126, %127, %128, %129}, "
    "a, b, 1, 1, 1, 0, 1;\n"
    "mov.b64 s, {%136, %136};\nmbarrier.test_wait.shared::cta.b64 p, [%135], s;\nmov.b64 s, {%138, %138};\nmbarrier.test_wait.shared::cta.b64 q, [%137], s;\n"
    "mad.lo.u32 t, %134, 2, t;\nmad.lo.u32 %130, %134, 128, %130;\n"
    "mov.b64 a, {t, %132};\nmov.b64 b, {%130, %133};\n"
    "wgmma.mma_async.sync.aligned.m64n256k16.f32.bf16.bf16 "
    "{%2, %3, %4, %5, %6, %7, %8, %9, %10, %11, %12, %13, %14, %15, %16, %17, %18, %19, %20, %21, %22, %23, %24, %25, %26, %27, %28, %29, %30, %31, %32, %33, %34, %35, %36, %37, %38, %39, %40, %41, %42, %43, %44, %45, %46, %47, %48, %49, %50, %51, %52, %53, %54, %55, %56, %57, %58, %59, %60, %61, %62, %63, %64, %65, %66, %67, %68, %69, %70, %71, %72, %73, %74, %75, %76, %77, %78, %79, %80, %81, %82, %83, %84, %85, %86, %87, %88, %89, %90, %91, %92, %93, %94, %95, %96, %97, %98, %99, %100, %101, %102, %103, %104, %105, %106, %107, %108, %109, %110, %111, %112, %113, %114, %115, %116, %117, %118, %119, %120, %121, %122, %123, %124, %125, %126, %127, %128, %129}, "
    "a, b, 1, 1, 1, 0, 1;\n"
    "mad.lo.u32 t, %134, 2, t;\nmad.lo.u32 %130, %134, 128, %130;\n"
    "mov.b64 a, {t, %132};\nmov.b64 b, {%130, %133};\n"
    "wgmma.mma_async.sync.aligned.m64n256k16.f32.bf16.bf16 "
    "{%2, %3, %4, %5, %6, %7, %8, %9, %10, %11, %12, %13, %14, %15, %16, %17, %18, %19, %20, %21, %22, %23, %24, %25, %26, %27, %28, %29, %30, %31, %32, %33, %34, %35, %36, %37, %38, %39, %40, %41, %42, %43, %44, %45, %46, %47, %48, %49, %50, %51, %52, %53, %54, %55, %56, %57, %58, %59, %60, %61, %62, %63, %64, %65, %66, %67, %68, %69, %70, %71, %72, %73, %74, %75, %76, %77, %78, %79, %80, %81, %82, %83, %84, %85, %86, %87, %88, %89, %90, %91, %92, %93, %94, %95, %96, %97, %98, %99, %100, %101, %102, %103, %104, %105, %106, %107, %108, %109, %110, %111, %112, %113, %114, %115, %116, %117, %118, %119, %120, %121, %122, %123, %124, %125, %126, %127, %128, %129}, "
    "a, b, 1, 1, 1, 0, 1;\n"
    "wgmma.commit_group.sync.aligned;\nselp.u32 %0, 1, 0, p;\nselp.u32 %1, 1, 0, q;\n}"
    : "=r"(ok.x), "=r"(ok.y), "=f"(d[0]), "=f"(d[1]), "=f"(d[2]), "=f"(d[3]), "=f"(d[4]), "=f"(d[5]), "=f"(d[6]), "=f"(d[7]), "=f"(d[8]), "=f"(d[9]), "=f"(d[10]), "=f"(d[11]), "=f"(d[12]), "=f"(d[13]), "=f"(d[14]), "=f"(d[15]), "=f"(d[16]), "=f"(d[17]), "=f"(d[18]), "=f"(d[19]), "=f"(d[20]), "=f"(d[21]), "=f"(d[22]), "=f"(d[23]), "=f"(d[24]), "=f"(d[25]), "=f"(d[26]), "=f"(d[27]), "=f"(d[28]), "=f"(d[29]), "=f"(d[30]), "=f"(d[31]), "=f"(d[32]), "=f"(d[33]), "=f"(d[34]), "=f"(d[35]), "=f"(d[36]), "=f"(d[37]), "=f"(d[38]), "=f"(d[39]), "=f"(d[40]), "=f"(d[41]), "=f"(d[42]), "=f"(d[43]), "=f"(d[44]), "=f"(d[45]), "=f"(d[46]), "=f"(d[47]), "=f"(d[48]), "=f"(d[49]), "=f"(d[50]), "=f"(d[51]), "=f"(d[52]), "=f"(d[53]), "=f"(d[54]), "=f"(d[55]), "=f"(d[56]), "=f"(d[57]), "=f"(d[58]), "=f"(d[59]), "=f"(d[60]), "=f"(d[61]), "=f"(d[62]), "=f"(d[63]), "=f"(d[64]), "=f"(d[65]), "=f"(d[66]), "=f"(d[67]), "=f"(d[68]), "=f"(d[69]), "=f"(d[70]), "=f"(d[71]), "=f"(d[72]), "=f"(d[73]), "=f"(d[74]), "=f"(d[75]), "=f"(d[76]), "=f"(d[77]), "=f"(d[78]), "=f"(d[79]), "=f"(d[80]), "=f"(d[81]), "=f"(d[82]), "=f"(d[83]), "=f"(d[84]), "=f"(d[85]), "=f"(d[86]), "=f"(d[87]), "=f"(d[88]), "=f"(d[89]), "=f"(d[90]), "=f"(d[91]), "=f"(d[92]), "=f"(d[93]), "=f"(d[94]), "=f"(d[95]), "=f"(d[96]), "=f"(d[97]), "=f"(d[98]), "=f"(d[99]), "=f"(d[100]), "=f"(d[101]), "=f"(d[102]), "=f"(d[103]), "=f"(d[104]), "=f"(d[105]), "=f"(d[106]), "=f"(d[107]), "=f"(d[108]), "=f"(d[109]), "=f"(d[110]), "=f"(d[111]), "=f"(d[112]), "=f"(d[113]), "=f"(d[114]), "=f"(d[115]), "=f"(d[116]), "=f"(d[117]), "=f"(d[118]), "=f"(d[119]), "=f"(d[120]), "=f"(d[121]), "=f"(d[122]), "=f"(d[123]), "=f"(d[124]), "=f"(d[125]), "=f"(d[126]), "=f"(d[127]), "+r"(db)
    : "r"(da), "r"(h0), "r"(h1), "r"(one), "r"(b0), "r"(p0), "r"(b1), "r"(p1) : "memory");
  return ok;
}
template <int S> __device__ __forceinline__ uint2 wgmma_step256(float (&d)[S], uint32_t da, uint32_t& db, uint32_t h0, uint32_t h1, uint32_t one, uint32_t b0, uint32_t p0, uint32_t b1, uint32_t p1) {
  uint2 ok;
  asm volatile("{\n.reg .b64 a, b, s;\n.reg .b32 t, u;\n.reg .pred p, q;\nwgmma.fence.sync.aligned;\n"
    "mov.b32 t, %131;\n"
    "mov.b64 a, {t, %132};\nmov.b64 b, {%130, %133};\n"
    "wgmma.mma_async.sync.aligned.m64n256k16.f32.bf16.bf16 "
    "{%2, %3, %4, %5, %6, %7, %8, %9, %10, %11, %12, %13, %14, %15, %16, %17, %18, %19, %20, %21, %22, %23, %24, %25, %26, %27, %28, %29, %30, %31, %32, %33, %34, %35, %36, %37, %38, %39, %40, %41, %42, %43, %44, %45, %46, %47, %48, %49, %50, %51, %52, %53, %54, %55, %56, %57, %58, %59, %60, %61, %62, %63, %64, %65, %66, %67, %68, %69, %70, %71, %72, %73, %74, %75, %76, %77, %78, %79, %80, %81, %82, %83, %84, %85, %86, %87, %88, %89, %90, %91, %92, %93, %94, %95, %96, %97, %98, %99, %100, %101, %102, %103, %104, %105, %106, %107, %108, %109, %110, %111, %112, %113, %114, %115, %116, %117, %118, %119, %120, %121, %122, %123, %124, %125, %126, %127, %128, %129}, "
    "a, b, 1, 1, 1, 0, 1;\n"
    "mad.lo.u32 t, %134, 2, t;\nmad.lo.u32 %130, %134, 128, %130;\n"
    "mov.b64 a, {t, %132};\nmov.b64 b, {%130, %133};\n"
    "wgmma.mma_async.sync.aligned.m64n256k16.f32.bf16.bf16 "
    "{%2, %3, %4, %5, %6, %7, %8, %9, %10, %11, %12, %13, %14, %15, %16, %17, %18, %19, %20, %21, %22, %23, %24, %25, %26, %27, %28, %29, %30, %31, %32, %33, %34, %35, %36, %37, %38, %39, %40, %41, %42, %43, %44, %45, %46, %47, %48, %49, %50, %51, %52, %53, %54, %55, %56, %57, %58, %59, %60, %61, %62, %63, %64, %65, %66, %67, %68, %69, %70, %71, %72, %73, %74, %75, %76, %77, %78, %79, %80, %81, %82, %83, %84, %85, %86, %87, %88, %89, %90, %91, %92, %93, %94, %95, %96, %97, %98, %99, %100, %101, %102, %103, %104, %105, %106, %107, %108, %109, %110, %111, %112, %113, %114, %115, %116, %117, %118, %119, %120, %121, %122, %123, %124, %125, %126, %127, %128, %129}, "
    "a, b, 1, 1, 1, 0, 1;\n"
    "mov.b64 s, {%136, %136};\nmbarrier.test_wait.shared::cta.b64 p, [%135], s;\nmov.b64 s, {%138, %138};\nmbarrier.test_wait.shared::cta.b64 q, [%137], s;\n"
    "mad.lo.u32 t, %134, 2, t;\nmad.lo.u32 %130, %134, 128, %130;\n"
    "mov.b64 a, {t, %132};\nmov.b64 b, {%130, %133};\n"
    "wgmma.mma_async.sync.aligned.m64n256k16.f32.bf16.bf16 "
    "{%2, %3, %4, %5, %6, %7, %8, %9, %10, %11, %12, %13, %14, %15, %16, %17, %18, %19, %20, %21, %22, %23, %24, %25, %26, %27, %28, %29, %30, %31, %32, %33, %34, %35, %36, %37, %38, %39, %40, %41, %42, %43, %44, %45, %46, %47, %48, %49, %50, %51, %52, %53, %54, %55, %56, %57, %58, %59, %60, %61, %62, %63, %64, %65, %66, %67, %68, %69, %70, %71, %72, %73, %74, %75, %76, %77, %78, %79, %80, %81, %82, %83, %84, %85, %86, %87, %88, %89, %90, %91, %92, %93, %94, %95, %96, %97, %98, %99, %100, %101, %102, %103, %104, %105, %106, %107, %108, %109, %110, %111, %112, %113, %114, %115, %116, %117, %118, %119, %120, %121, %122, %123, %124, %125, %126, %127, %128, %129}, "
    "a, b, 1, 1, 1, 0, 1;\n"
    "mad.lo.u32 t, %134, 2, t;\nmad.lo.u32 %130, %134, 128, %130;\n"
    "mov.b64 a, {t, %132};\nmov.b64 b, {%130, %133};\n"
    "wgmma.mma_async.sync.aligned.m64n256k16.f32.bf16.bf16 "
    "{%2, %3, %4, %5, %6, %7, %8, %9, %10, %11, %12, %13, %14, %15, %16, %17, %18, %19, %20, %21, %22, %23, %24, %25, %26, %27, %28, %29, %30, %31, %32, %33, %34, %35, %36, %37, %38, %39, %40, %41, %42, %43, %44, %45, %46, %47, %48, %49, %50, %51, %52, %53, %54, %55, %56, %57, %58, %59, %60, %61, %62, %63, %64, %65, %66, %67, %68, %69, %70, %71, %72, %73, %74, %75, %76, %77, %78, %79, %80, %81, %82, %83, %84, %85, %86, %87, %88, %89, %90, %91, %92, %93, %94, %95, %96, %97, %98, %99, %100, %101, %102, %103, %104, %105, %106, %107, %108, %109, %110, %111, %112, %113, %114, %115, %116, %117, %118, %119, %120, %121, %122, %123, %124, %125, %126, %127, %128, %129}, "
    "a, b, 1, 1, 1, 0, 1;\n"
    "wgmma.commit_group.sync.aligned;\nselp.u32 %0, 1, 0, p;\nselp.u32 %1, 1, 0, q;\n}"
    : "=r"(ok.x), "=r"(ok.y), "+f"(d[0]), "+f"(d[1]), "+f"(d[2]), "+f"(d[3]), "+f"(d[4]), "+f"(d[5]), "+f"(d[6]), "+f"(d[7]), "+f"(d[8]), "+f"(d[9]), "+f"(d[10]), "+f"(d[11]), "+f"(d[12]), "+f"(d[13]), "+f"(d[14]), "+f"(d[15]), "+f"(d[16]), "+f"(d[17]), "+f"(d[18]), "+f"(d[19]), "+f"(d[20]), "+f"(d[21]), "+f"(d[22]), "+f"(d[23]), "+f"(d[24]), "+f"(d[25]), "+f"(d[26]), "+f"(d[27]), "+f"(d[28]), "+f"(d[29]), "+f"(d[30]), "+f"(d[31]), "+f"(d[32]), "+f"(d[33]), "+f"(d[34]), "+f"(d[35]), "+f"(d[36]), "+f"(d[37]), "+f"(d[38]), "+f"(d[39]), "+f"(d[40]), "+f"(d[41]), "+f"(d[42]), "+f"(d[43]), "+f"(d[44]), "+f"(d[45]), "+f"(d[46]), "+f"(d[47]), "+f"(d[48]), "+f"(d[49]), "+f"(d[50]), "+f"(d[51]), "+f"(d[52]), "+f"(d[53]), "+f"(d[54]), "+f"(d[55]), "+f"(d[56]), "+f"(d[57]), "+f"(d[58]), "+f"(d[59]), "+f"(d[60]), "+f"(d[61]), "+f"(d[62]), "+f"(d[63]), "+f"(d[64]), "+f"(d[65]), "+f"(d[66]), "+f"(d[67]), "+f"(d[68]), "+f"(d[69]), "+f"(d[70]), "+f"(d[71]), "+f"(d[72]), "+f"(d[73]), "+f"(d[74]), "+f"(d[75]), "+f"(d[76]), "+f"(d[77]), "+f"(d[78]), "+f"(d[79]), "+f"(d[80]), "+f"(d[81]), "+f"(d[82]), "+f"(d[83]), "+f"(d[84]), "+f"(d[85]), "+f"(d[86]), "+f"(d[87]), "+f"(d[88]), "+f"(d[89]), "+f"(d[90]), "+f"(d[91]), "+f"(d[92]), "+f"(d[93]), "+f"(d[94]), "+f"(d[95]), "+f"(d[96]), "+f"(d[97]), "+f"(d[98]), "+f"(d[99]), "+f"(d[100]), "+f"(d[101]), "+f"(d[102]), "+f"(d[103]), "+f"(d[104]), "+f"(d[105]), "+f"(d[106]), "+f"(d[107]), "+f"(d[108]), "+f"(d[109]), "+f"(d[110]), "+f"(d[111]), "+f"(d[112]), "+f"(d[113]), "+f"(d[114]), "+f"(d[115]), "+f"(d[116]), "+f"(d[117]), "+f"(d[118]), "+f"(d[119]), "+f"(d[120]), "+f"(d[121]), "+f"(d[122]), "+f"(d[123]), "+f"(d[124]), "+f"(d[125]), "+f"(d[126]), "+f"(d[127]), "+r"(db)
    : "r"(da), "r"(h0), "r"(h1), "r"(one), "r"(b0), "r"(p0), "r"(b1), "r"(p1) : "memory");
  return ok;
}
template <int S> __device__ __forceinline__ void wgmma_aug192(float (&d)[S], uint32_t a0, uint32_t a1, uint32_t db, uint32_t h1) {
  asm volatile("{\n.reg .b64 b;\n.reg .b32 z;\nmov.b32 z, 0;\n"
    "mov.b64 b, {%98, %99};\nwgmma.fence.sync.aligned;\n"
    "wgmma.mma_async.sync.aligned.m64n192k16.f32.bf16.bf16 "
    "{%0, %1, %2, %3, %4, %5, %6, %7, %8, %9, %10, %11, %12, %13, %14, %15, %16, %17, %18, %19, %20, %21, %22, %23, %24, %25, %26, %27, %28, %29, %30, %31, %32, %33, %34, %35, %36, %37, %38, %39, %40, %41, %42, %43, %44, %45, %46, %47, %48, %49, %50, %51, %52, %53, %54, %55, %56, %57, %58, %59, %60, %61, %62, %63, %64, %65, %66, %67, %68, %69, %70, %71, %72, %73, %74, %75, %76, %77, %78, %79, %80, %81, %82, %83, %84, %85, %86, %87, %88, %89, %90, %91, %92, %93, %94, %95}, "
    "{%96, %97, z, z}, b, 1, 1, 1, 1;\n"
    "wgmma.commit_group.sync.aligned;\n}"
    : "+f"(d[0]), "+f"(d[1]), "+f"(d[2]), "+f"(d[3]), "+f"(d[4]), "+f"(d[5]), "+f"(d[6]), "+f"(d[7]), "+f"(d[8]), "+f"(d[9]), "+f"(d[10]), "+f"(d[11]), "+f"(d[12]), "+f"(d[13]), "+f"(d[14]), "+f"(d[15]), "+f"(d[16]), "+f"(d[17]), "+f"(d[18]), "+f"(d[19]), "+f"(d[20]), "+f"(d[21]), "+f"(d[22]), "+f"(d[23]), "+f"(d[24]), "+f"(d[25]), "+f"(d[26]), "+f"(d[27]), "+f"(d[28]), "+f"(d[29]), "+f"(d[30]), "+f"(d[31]), "+f"(d[32]), "+f"(d[33]), "+f"(d[34]), "+f"(d[35]), "+f"(d[36]), "+f"(d[37]), "+f"(d[38]), "+f"(d[39]), "+f"(d[40]), "+f"(d[41]), "+f"(d[42]), "+f"(d[43]), "+f"(d[44]), "+f"(d[45]), "+f"(d[46]), "+f"(d[47]), "+f"(d[48]), "+f"(d[49]), "+f"(d[50]), "+f"(d[51]), "+f"(d[52]), "+f"(d[53]), "+f"(d[54]), "+f"(d[55]), "+f"(d[56]), "+f"(d[57]), "+f"(d[58]), "+f"(d[59]), "+f"(d[60]), "+f"(d[61]), "+f"(d[62]), "+f"(d[63]), "+f"(d[64]), "+f"(d[65]), "+f"(d[66]), "+f"(d[67]), "+f"(d[68]), "+f"(d[69]), "+f"(d[70]), "+f"(d[71]), "+f"(d[72]), "+f"(d[73]), "+f"(d[74]), "+f"(d[75]), "+f"(d[76]), "+f"(d[77]), "+f"(d[78]), "+f"(d[79]), "+f"(d[80]), "+f"(d[81]), "+f"(d[82]), "+f"(d[83]), "+f"(d[84]), "+f"(d[85]), "+f"(d[86]), "+f"(d[87]), "+f"(d[88]), "+f"(d[89]), "+f"(d[90]), "+f"(d[91]), "+f"(d[92]), "+f"(d[93]), "+f"(d[94]), "+f"(d[95])
    : "r"(a0), "r"(a1), "r"(db), "r"(h1) : "memory");
}
template <int S> __device__ __forceinline__ void wgmma_aug256(float (&d)[S], uint32_t a0, uint32_t a1, uint32_t db, uint32_t h1) {
  asm volatile("{\n.reg .b64 b;\n.reg .b32 z;\nmov.b32 z, 0;\n"
    "mov.b64 b, {%130, %131};\nwgmma.fence.sync.aligned;\n"
    "wgmma.mma_async.sync.aligned.m64n256k16.f32.bf16.bf16 "
    "{%0, %1, %2, %3, %4, %5, %6, %7, %8, %9, %10, %11, %12, %13, %14, %15, %16, %17, %18, %19, %20, %21, %22, %23, %24, %25, %26, %27, %28, %29, %30, %31, %32, %33, %34, %35, %36, %37, %38, %39, %40, %41, %42, %43, %44, %45, %46, %47, %48, %49, %50, %51, %52, %53, %54, %55, %56, %57, %58, %59, %60, %61, %62, %63, %64, %65, %66, %67, %68, %69, %70, %71, %72, %73, %74, %75, %76, %77, %78, %79, %80, %81, %82, %83, %84, %85, %86, %87, %88, %89, %90, %91, %92, %93, %94, %95, %96, %97, %98, %99, %100, %101, %102, %103, %104, %105, %106, %107, %108, %109, %110, %111, %112, %113, %114, %115, %116, %117, %118, %119, %120, %121, %122, %123, %124, %125, %126, %127}, "
    "{%128, %129, z, z}, b, 1, 1, 1, 1;\n"
    "wgmma.commit_group.sync.aligned;\n}"
    : "+f"(d[0]), "+f"(d[1]), "+f"(d[2]), "+f"(d[3]), "+f"(d[4]), "+f"(d[5]), "+f"(d[6]), "+f"(d[7]), "+f"(d[8]), "+f"(d[9]), "+f"(d[10]), "+f"(d[11]), "+f"(d[12]), "+f"(d[13]), "+f"(d[14]), "+f"(d[15]), "+f"(d[16]), "+f"(d[17]), "+f"(d[18]), "+f"(d[19]), "+f"(d[20]), "+f"(d[21]), "+f"(d[22]), "+f"(d[23]), "+f"(d[24]), "+f"(d[25]), "+f"(d[26]), "+f"(d[27]), "+f"(d[28]), "+f"(d[29]), "+f"(d[30]), "+f"(d[31]), "+f"(d[32]), "+f"(d[33]), "+f"(d[34]), "+f"(d[35]), "+f"(d[36]), "+f"(d[37]), "+f"(d[38]), "+f"(d[39]), "+f"(d[40]), "+f"(d[41]), "+f"(d[42]), "+f"(d[43]), "+f"(d[44]), "+f"(d[45]), "+f"(d[46]), "+f"(d[47]), "+f"(d[48]), "+f"(d[49]), "+f"(d[50]), "+f"(d[51]), "+f"(d[52]), "+f"(d[53]), "+f"(d[54]), "+f"(d[55]), "+f"(d[56]), "+f"(d[57]), "+f"(d[58]), "+f"(d[59]), "+f"(d[60]), "+f"(d[61]), "+f"(d[62]), "+f"(d[63]), "+f"(d[64]), "+f"(d[65]), "+f"(d[66]), "+f"(d[67]), "+f"(d[68]), "+f"(d[69]), "+f"(d[70]), "+f"(d[71]), "+f"(d[72]), "+f"(d[73]), "+f"(d[74]), "+f"(d[75]), "+f"(d[76]), "+f"(d[77]), "+f"(d[78]), "+f"(d[79]), "+f"(d[80]), "+f"(d[81]), "+f"(d[82]), "+f"(d[83]), "+f"(d[84]), "+f"(d[85]), "+f"(d[86]), "+f"(d[87]), "+f"(d[88]), "+f"(d[89]), "+f"(d[90]), "+f"(d[91]), "+f"(d[92]), "+f"(d[93]), "+f"(d[94]), "+f"(d[95]), "+f"(d[96]), "+f"(d[97]), "+f"(d[98]), "+f"(d[99]), "+f"(d[100]), "+f"(d[101]), "+f"(d[102]), "+f"(d[103]), "+f"(d[104]), "+f"(d[105]), "+f"(d[106]), "+f"(d[107]), "+f"(d[108]), "+f"(d[109]), "+f"(d[110]), "+f"(d[111]), "+f"(d[112]), "+f"(d[113]), "+f"(d[114]), "+f"(d[115]), "+f"(d[116]), "+f"(d[117]), "+f"(d[118]), "+f"(d[119]), "+f"(d[120]), "+f"(d[121]), "+f"(d[122]), "+f"(d[123]), "+f"(d[124]), "+f"(d[125]), "+f"(d[126]), "+f"(d[127])
    : "r"(a0), "r"(a1), "r"(db), "r"(h1) : "memory");
}

__device__ __forceinline__ uint32_t clock32() { uint32_t c; asm volatile("mov.u32 %0, %%clock;" : "=r"(c)); return c; }
__device__ __forceinline__ void spin_until(uint32_t c) {
  asm volatile("{\n.reg .pred p;\n.reg .s32 t;\nLAB_WAIT:\nmov.u32 t, %%clock;\nsub.s32 t, t, %0;\nsetp.lt.s32 p, t, 0;\n@p bra.uni LAB_WAIT;\n}" ::"r"(c) : "memory");
}
struct Nop { __device__ __forceinline__ void operator()(int) const {} };
template <int V> struct IC { static constexpr int v = V; };
struct Pipe {
  uint32_t db, g8, a8, pa, tph, aend, curB, curA, prevB, prevA, bo, so, sph, h0, h1, one;
  uint2 nx;
  int w; bool l0;
  __device__ __forceinline__ int lane() const { return LSO ? (so >> 5) & 31 : threadIdx.x & 31; }
  __device__ __forceinline__ void adv_a() { a8 += 8; pa += PA1; if (a8 == aend) a8 -= NA * 8; }
  __device__ __forceinline__ uint32_t take() { const uint32_t a = SB + OFF_A + a8 * 1024; adv_a(); return a; }
  __device__ __forceinline__ uint32_t ahead(int d) const { uint32_t ls = a8 + d * 8; if (ls >= aend) ls -= NA * 8; return SB + OFF_A + ls * 1024; }
  __device__ __forceinline__ uint32_t wait_ahead(int d) {
    uint32_t ls = a8 + d * 8;
    if (ls >= aend) ls -= NA * 8;
    mbar_spin31(SB + BAR_FULLA + ls, pa + d * PA1);
    return SB + OFF_A + ls * 1024;
  }
  template <int N, bool FIRST, int S> __device__ __forceinline__ uint2 iss(float (&acc)[S], bool skip) {
    const uint32_t da = DA0 + a8 * 64;
    if (!FIRST) { if (N != 192) db &= ~0x2000u; else if (db == DB0 + 15 * 512) db = DB0; }
    prevB = curB; prevA = curA;
    curB = g8 & 56; curA = a8;
    g8 += G1;
    a8 += skip ? 16 : 8; pa += skip ? 2 * PA1 : PA1;
    if (a8 >= aend) a8 -= NA * 8;
    const uint32_t fb = SB + BAR_FULLB + (g8 & 56), fa = SB + BAR_FULLA + a8;
    uint2 ok;
    if constexpr (N == 128) ok = FIRST ? wgmma_first128(acc, da, db, h0, h1, one, fb, g8, fa, pa) : wgmma_step128(acc, da, db, h0, h1, one, fb, g8, fa, pa);
    if constexpr (N == 192) ok = FIRST ? wgmma_first192(acc, da, db, h0, h1, one, fb, g8, fa, pa) : wgmma_step192(acc, da, db, h0, h1, one, fb, g8, fa, pa);
    if constexpr (N == 256) ok = FIRST ? wgmma_first256(acc, da, db, h0, h1, one, fb, g8, fa, pa) : wgmma_step256(acc, da, db, h0, h1, one, fb, g8, fa, pa);
    db += N * 8 - 384;
    return ok;
  }
  __device__ __forceinline__ void ensure(uint2 ok) {
    asm volatile(
        "{\n.reg .pred p, q;\n.reg .b64 s, t;\nmov.b64 s, {%1, %1};\nmov.b64 t, {%3, %3};\nsetp.ne.u32 p, %4, 0;\nsetp.ne.u32 q, %5, 0;\n@!p bra.uni LAB_WAIT;\n@q bra.uni DONE;\n"
        "LAB_WAIT:\nmbarrier.try_wait.shared::cta.b64 p, [%0], s;\nmbarrier.try_wait.shared::cta.b64 q, [%2], t;\n"
        "and.pred p, p, q;\n@!p bra.uni LAB_WAIT;\nDONE:\n}" ::"r"(SB + BAR_FULLB + (g8 & 56)), "r"(g8), "r"(SB + BAR_FULLA + a8), "r"(pa), "r"(ok.x), "r"(ok.y) : "memory");
  }
  template <class Hook> __device__ __forceinline__ void validate(bool check, const CUtensorMap* tm16, int c0, int c1, int wp, int j, Hook hook) {
    const uint32_t rows = SB + OFF_A + a8 * 1024 + wp * 2048, ad = a8 * 1024 + so;
    uint32_t v0 = 0, v1 = 0;
    asm volatile("{\n.reg .pred p;\nsetp.ne.u32 p, %3, 0;\n@p ld.shared.b32 %0, [%2];\n@p ld.shared.b32 %1, [%2 + 1024];\n}" : "+r"(v0), "+r"(v1) : "r"(ad), "r"((uint32_t)check));
    hook();
    while (__any_sync(~0u, max(v0, v1) == 0xffffffffu)) {
      const uint32_t bar = SB + BAR_SPEC + (w * 4 + wp) * 8;
      e_load<2048>(rows, tm16, c0 + sched_k(c_sched.v[j][(g8 >> 3) & 511]), c1 + wp * 16, bar);
      mbar_spin(bar, sph);
      sph ^= 1;
      v0 = lds32(ad); v1 = lds32(ad + 1024);
    }
  }
  __device__ __forceinline__ void fence() const { asm volatile("{\n.reg .pred p;\nsetp.eq.u32 p, %0, 2;\nLAB:\n@p pmevent 6;\n@p bra.uni LAB;\n}" ::"r"(one) : "memory"); }
  __device__ __forceinline__ void drain() {
    wg_wait<0>();
    arrive_2(SB + BAR_EMPTYB + curB, SB + BAR_EMPTYA + curA, l0);
    curB = BAR_DUMMY - BAR_EMPTYB; curA = BAR_DUMMY - BAR_EMPTYA;
  }
  __device__ __forceinline__ void signal_server(uint32_t odd) { __syncwarp(); arrive_n(SB + BAR_SRV + w * 16 + odd * 8, l0); }
  __device__ __forceinline__ void signal_loader() { __syncwarp(); arrive_n(SB + BAR_STG + w * 8, l0); }
  template <int N, bool HOLD = false, int S, class Pre = Nop> __device__ __forceinline__ void begin(float (&acc)[S], uint32_t p0, int proft, Pre pre = Pre()) {
    db = DB0 + p0 * 512;
    const uint32_t c1 = HOLD ? clock32() : 0;
    ensure(nx);
    if (HOLD) spin_until(c1 + lds32(SB + OFF_HOLD + w * 4));
    pre(0);
    PROF_T(w, proft, 0);
    ensure(iss<N, true>(acc, false));
  }
  template <int N, bool ENSURE = true, int S, class Hook> __device__ __forceinline__ void run(float (&acc)[S], int i0, int i1, uint32_t skips, int pause, Hook hook) {
    int i = i0;
    const int ev = w ? pause : -1;
#pragma unroll 1
    while (true) {
      const uint2 ok = iss<N, false>(acc, (skips >> i) & 1);
      wg_wait<1>();
      arrive_2(SB + BAR_EMPTYB + prevB, SB + BAR_EMPTYA + prevA, l0);
      if (pause >= 0 && i + 1 == i1) { nx = ok; break; }
      if constexpr (ENSURE) { ensure(ok); hook(i); } else hook(i, ok);
      i++;
      if (pause < 0 && i == i1) break;
      if (pause > 0 && i == ev) { drain(); mbar_spin(SB + BAR_LEAD, tph); }
    }
  }
  template <int N, bool AUG, int S> __device__ __forceinline__ void end(float (&acc)[S], int ns, uint32_t pos, uint32_t au0, uint32_t au1, int proft) {
    uint32_t augB = 0;
    arrive_n(SB + BAR_LEAD + w * (BAR_DUMMY - BAR_LEAD), l0);
    if constexpr (AUG) {
      asm volatile("{\n.reg .pred p;\n.reg .b64 s;\nmov.b64 s, {%1, %1};\nsetp.ne.u32 p, %2, 0;\n@p bra.uni DONE;\nLAB_WAIT:\nmbarrier.try_wait.shared::cta.b64 p, [%0], s;\n@!p bra.uni LAB_WAIT;\nDONE:\n}"
                     ::"r"(SB + BAR_FULLB + (g8 & 56)), "r"(g8), "r"(nx.x) : "memory");
      const uint32_t dc = (((SB + OFF_B) >> 4) | (64u << 16)) + pos * 512;
      if constexpr (N == 192) wgmma_aug192(acc, au0, au1, dc, h1); else wgmma_aug256(acc, au0, au1, dc, h1);
      augB = g8 & 56; g8 += G1;
    }
    tph ^= 1;
    if (ns > 0) wait_ahead(ns - 1);
    nx = make_uint2(mbar_test(SB + BAR_FULLB + (g8 & 56), g8 >> 31), AUG ? mbar_test(SB + BAR_FULLA + a8, pa >> 31) : 1);
    wg_wait<0>();
    arrive_2(SB + BAR_EMPTYB + curB, SB + BAR_EMPTYA + curA, l0);
    if (AUG) arrive_n(SB + BAR_EMPTYB + augB, l0);
    PROF_T(w, proft, 1);
  }
};

__device__ __forceinline__ uint32_t box_addr(uint32_t buf, uint32_t bo, int u) { return (buf + bo) ^ (u * 32); }

__device__ __forceinline__ float bf_round(float x) { return __bfloat162float(__float2bfloat16_rn(x)); }
__device__ __forceinline__ void own_rstd(int w, int wp, int lane, float (&rstd)[2]) {
#pragma unroll
  for (int hh = 0; hh < 2; hh++) rstd[hh] = __uint_as_float(lds32(SB + OFF_RSTD + (w * 72 + 8 + wp * 16 + (lane >> 2) + hh * 8) * 4));
}
__device__ __forceinline__ void stats_fetch(int w, int wp, int lane, uint32_t (&au)[2]) {
  const int g = lane >> 2, q4 = lane & 3;
  float rstd[2];
  own_rstd(w, wp, lane, rstd);
#pragma unroll
  for (int hh = 0; hh < 2; hh++) {
    const float m = __uint_as_float(lds32(SB + OFF_MEAN + (w * 64 + wp * 16 + g + hh * 8) * 4));
    const float v = q4 == 3 ? rcp(rstd[hh]) : -m;
    const float v1 = bf_round(v), v2 = bf_round(v - v1);
    const float p = q4 == 1 ? v2 : (q4 == 2 ? v - v1 - v2 : v1);
    au[hh] = pack_bf16(p, q4 == 3 ? v2 : p);
  }
}

__device__ __forceinline__ void halo_fetch(uint32_t slot, int w, const uint4* src, uint32_t bar) {
  asm volatile("{\n.reg .pred p;\nelect.sync _|p, 0xffffffff;\n@p mbarrier.arrive.expect_tx.shared::cta.b64 _, [%4], 2080;\n"
               "@p cp.async.bulk.shared::cluster.global.mbarrier::complete_tx::bytes [%0], [%2], 2048, [%4];\n"
               "@p cp.async.bulk.shared::cluster.global.mbarrier::complete_tx::bytes [%1], [%3], 32, [%4];\n}"
               ::"r"(slot), "r"(SB + OFF_RSTD + w * 288), "l"(src), "l"(src + 128), "r"(bar) : "memory");
}
struct Attn {
  uint32_t lo[24], hi[24], ha[16], hslot;
  float c[8][4], rstd[2];
  float2 rk[3];
  __device__ __forceinline__ void A(const float (&acc)[96], Pipe& M, int w, int wp, int r, uint4* halo_out) {
    const int lane = M.lane();
    M.signal_loader();
    auto cvt = [&](uint32_t& d, int u) { asm volatile("cvt.rn.bf16x2.f32 %0, %1, %2;" : "=r"(d) : "f"(acc[u + 1]), "f"(acc[u])); };
    auto rest = [&] {
#pragma unroll
      for (int nb = 23; nb >= 0; nb--) {
        cvt(lo[nb], 4 * nb);
        if (nb < 8) cvt(hi[nb], 4 * nb + 2);
        if (nb >= 16) lo[nb] = movm(lo[nb]);
      }
    };
#pragma unroll
    for (int nb = 8; nb < 24; nb++) hi[nb] = pack_bf16(acc[4 * nb + 2], acc[4 * nb + 3]);
    hslot = M.ahead(3);
    const uint32_t hbuf = hslot + wp * 2048 + lane * 16;
#pragma unroll
    for (int nb = 16; nb < 24; nb++) hi[nb] = movm(hi[nb]);
    if (wp == 3) {
      if (r < 15) {
#pragma unroll
        for (int p = 0; p < 4; p++) halo_out[p * 32 + lane] = make_uint4(hi[8 + 4 * p] ? hi[8 + 4 * p] : 0x8000u, hi[9 + 4 * p], hi[10 + 4 * p], hi[11 + 4 * p]);
        const uint32_t rh = lds32(SB + OFF_RSTD + (w * 72 + 64 + (lane & 7)) * 4);
        if (lane < 8) reinterpret_cast<uint32_t*>(halo_out + 128)[lane] = rh ? rh : 0x80000000u;
      }
    } else {
#pragma unroll
      for (int p = 0; p < 4; p++)
        asm volatile("st.shared.v4.b32 [%0], {%1,%2,%3,%4};" ::"r"(hbuf + 2048 + p * 512), "r"(hi[8 + 4 * p]), "r"(hi[9 + 4 * p]), "r"(hi[10 + 4 * p]), "r"(hi[11 + 4 * p]) : "memory");
      __syncwarp();
      arrive_n(SB + BAR_HALO + w * 8, M.l0);
    }
    rest();
  }
  __device__ __forceinline__ void B(int w, int wp, int lane, uint32_t hph) {
    own_rstd(w, wp, lane, rstd);
    mbar_spin(SB + BAR_HALO + w * 8, hph);
#pragma unroll
    for (int p = 0; p < 4; p++)
      asm volatile("ld.shared.v4.b32 {%0,%1,%2,%3}, [%4];" : "=r"(ha[4 * p]), "=r"(ha[4 * p + 1]), "=r"(ha[4 * p + 2]), "=r"(ha[4 * p + 3]) : "r"(hslot + wp * 2048 + lane * 16 + p * 512) : "memory");
#pragma unroll
    for (int u = 0; u < 3; u++) rk[u] = lds64(SB + OFF_RSTD + (w * 72 + wp * 16 + u * 8 + 2 * (lane & 3)) * 4);
  }
  template <class F> __device__ __forceinline__ void C(int wp, int r, int lane, uint32_t zero, F last) {
    const int g = lane >> 2, q = lane & 3;
    const bool nohalo = (wp == 0) && (r == 0);
    const bool up0 = 2 * q > g, up1 = 2 * q + 1 > g;
    const float sc = 0.17677669529663687f * 1.4426950408889634f;
    const float kx0 = up0 ? rk[0].x : rk[1].x, kx1 = up1 ? rk[0].y : rk[1].y;
    const float ky0 = up0 ? rk[1].x : rk[2].x, ky1 = up1 ? rk[1].y : rk[2].y;
    const float fx = rstd[0] * sc, fy = rstd[1] * sc;
    float sm[2][4] = {}, s0[2][4] = {}, s1[2][4] = {};
#pragma unroll
    for (int ks = 0; ks < 2; ks++)
#pragma unroll
      for (int h = 0; h < 2; h++) {
        const int a = 4 * h + 2 * ks;
        mma16(s0[h], lo[a], hi[a], lo[a + 1], hi[a + 1], lo[8 + a], lo[9 + a]);
        mma16(s1[h], lo[a], hi[a], lo[a + 1], hi[a + 1], hi[8 + a], hi[9 + a]);
      }
#pragma unroll
    for (int u = 0; u < 4; u++) { const int a = 4 * (u & 1) + (u & 2); mma16(sm[u & 1], lo[a], hi[a], lo[a + 1], hi[a + 1], ha[a], ha[a + 1]); }
    uint32_t pf[2][4];
    const uint32_t um = (up0 ? 0xffffu : 0u) | (up1 ? 0xffff0000u : 0u);
#pragma unroll
    for (int h = 0; h < 2; h++) {
      if (nohalo) { sm[h][0] = -INFINITY; sm[h][1] = -INFINITY; }
      float x0 = (up0 ? sm[h][0] : s0[h][0]) * (kx0 * fx), x1 = (up1 ? sm[h][1] : s0[h][1]) * (kx1 * fx);
      float y0 = (up0 ? s0[h][2] : s1[h][2]) * (ky0 * fy), y1 = (up1 ? s0[h][3] : s1[h][3]) * (ky1 * fy);
      float mx = fmaxf(x0, x1), my = fmaxf(y0, y1);
      mx = fmaxf(mx, __shfl_xor_sync(~0u, mx, 1)); my = fmaxf(my, __shfl_xor_sync(~0u, my, 1));
      mx = fmaxf(mx, __shfl_xor_sync(~0u, mx, 2)); my = fmaxf(my, __shfl_xor_sync(~0u, my, 2));
      x0 = ex2(x0 - mx); x1 = ex2(x1 - mx); y0 = ex2(y0 - my); y1 = ex2(y1 - my);
      float sx = x0 + x1, sy = y0 + y1;
      x0 *= kx0; x1 *= kx1; y0 *= ky0; y1 *= ky1;
      sx += __shfl_xor_sync(~0u, sx, 1); sy += __shfl_xor_sync(~0u, sy, 1);
      sx += __shfl_xor_sync(~0u, sx, 2); sy += __shfl_xor_sync(~0u, sy, 2);
      sx = rcp(sx); sy = rcp(sy);
      x0 *= sx; x1 *= sx; y0 *= sy; y1 *= sy;
      const uint32_t px = pack_bf16(x0, x1), py = pack_bf16(y0, y1);
      pf[h][0] = px & um; pf[h][1] = px & ~um; pf[h][2] = py & um; pf[h][3] = py & ~um;
    }
#pragma unroll
    for (int u = 0; u < 4; u++) {
#pragma unroll
      for (int e = 0; e < 4; e++) { c[2 * u][e] = 0.f; c[2 * u + 1][e] = 0.f; }
      mma8(c[2 * u], ha[8 + 2 * u], ha[9 + 2 * u], pf[u >> 1][0]);
      mma8(c[2 * u + 1], lo[16 + 2 * u], lo[17 + 2 * u], pf[u >> 1][2]);
    }
#pragma unroll
    for (int u = 0; u < 4; u++) {
      mma8(c[2 * u], lo[16 + 2 * u], lo[17 + 2 * u], pf[u >> 1][1]);
      mma8(c[2 * u + 1], hi[16 + 2 * u], hi[17 + 2 * u], pf[u >> 1][3]);
    }
    uint32_t dep = 0;
    last();
#pragma unroll
    for (int u = 0; u < (EFIRST == 3 ? 0 : 8); u++) dep |= __float_as_uint(c[u][0]);
    asm volatile("bar.sync %0, 256;" ::"r"(3 + (dep & zero)) : "memory");
  }
  __device__ __forceinline__ void E(Pipe& M, bool urgent) {
#pragma unroll
    for (int u = 0; u < 4; u++)
      asm volatile("stmatrix.sync.aligned.m8n8.x4.trans.shared.b16 [%0], {%1, %2, %3, %4};" ::"r"(box_addr(hslot, M.bo, u)),
                   "r"(pack_bf16(c[2 * u][0], c[2 * u][1])), "r"(pack_bf16(c[2 * u + 1][0], c[2 * u + 1][1])),
                   "r"(pack_bf16(c[2 * u][2], c[2 * u][3])), "r"(pack_bf16(c[2 * u + 1][2], c[2 * u + 1][3])) : "memory");
    __syncwarp();
    arrive_n(SB + (urgent ? BAR_STG + M.w * 8 : BAR_SRV + M.w * 16 + 8), M.l0);
  }
};

__device__ __forceinline__ void epi_res(const float (&acc)[64], const float (&pre)[64], float sc0, float sc1, uint32_t (&xr)[32], Pipe& M, int wp) {
  Pipe T = M;
  const uint32_t buf0 = T.take(), buf1 = T.take();
#pragma unroll
  for (int u = 0; u < 8; u++) {
#pragma unroll
    for (int nb = 2 * u; nb < 2 * u + 2; nb++) {
      xr[2 * nb] = pack_bf16(fmaf(acc[4 * nb], sc0, pre[2 * nb]), fmaf(acc[4 * nb + 1], sc0, pre[32 + 2 * nb]));
      xr[2 * nb + 1] = pack_bf16(fmaf(acc[4 * nb + 2], sc1, pre[2 * nb + 1]), fmaf(acc[4 * nb + 3], sc1, pre[33 + 2 * nb]));
    }
    stsm4(box_addr(u < 4 ? buf0 : buf1, M.bo, u & 3), xr[4 * u], xr[4 * u + 1], xr[4 * u + 2], xr[4 * u + 3]);
    if (u == 3) { M.signal_loader(); M.fence(); }
  }
  __syncwarp();
  arrive_n(SB + BAR_STG2 + M.w * 8, M.l0);
  fence_async_smem();
  wg_bar(M.w);
}
__device__ __forceinline__ void presum(float (&pre)[64], const uint32_t (&xr)[32], int lane, float usebias) {
  const uint32_t bias = SB + OFF_VEC + (lane & 3) * 8;
#pragma unroll
  for (int nb = 0; nb < 16; nb++) {
    const float2 b = lds64(bias + nb * 32);
#pragma unroll
    for (int u = 2 * nb; u < 2 * nb + 2; u++) {
      pre[32 + u] = fmaf(b.y, usebias, bf_hi(xr[u])); pre[u] = fmaf(b.x, usebias, bf_lo(xr[u]));
      asm volatile("" : "+f"(pre[u]), "+f"(pre[32 + u]));
    }
  }
}
template <int U0, int U1, int S, int Q> __device__ __forceinline__ void pack_relu(uint32_t (&o)[Q], const float (&acc)[S]) {
#pragma unroll
  for (int u = U0; u < U1; u++) asm volatile("cvt.rn.relu.bf16x2.f32 %0, %1, %2;" : "=r"(o[u]) : "f"(acc[2 * u + 1]), "f"(acc[2 * u]));
}
__device__ __forceinline__ uint32_t sq_bf16x2(uint32_t a) { uint32_t d; asm("mul.rn.bf16x2 %0, %1, %1;" : "=r"(d) : "r"(a)); return d; }
template <int Q> __device__ __forceinline__ void ffn_stage(const uint32_t (&o)[Q], int i, Pipe& M) {
  i -= M.w;
  if (i == 1 || i == 4 || i == 7 || (Q == 64 && i == 10)) {
    const uint32_t buf = M.wait_ahead(2 - M.w);
#pragma unroll
    for (int b = 0; b < Q / 16; b++)
      if (i == 3 * b + 1) {
#pragma unroll
        for (int u = 4 * b; u < 4 * b + 4; u++)
          stsm4(box_addr(buf, M.bo, u & 3), sq_bf16x2(o[4 * u]), sq_bf16x2(o[4 * u + 1]), sq_bf16x2(o[4 * u + 2]), sq_bf16x2(o[4 * u + 3]));
      }
    M.signal_server((i & 1) ^ (Q == 64));
  }
}

__device__ __forceinline__ void wait_flags(const uint8_t* f, uint32_t tag, int lane) {
  const uint32_t t4 = (tag & 0xff) * 0x01010101u;
  const uint32_t* fp = reinterpret_cast<const uint32_t*>(f) + (lane & (FG / 4 - 1));
  while (__any_sync(~0u, __vsub4(ld_relaxed(fp), t4) & 0x80808080u)) {}
  asm volatile("fence.acquire.gpu;\nfence.proxy.async.global;" ::: "memory");
}
__device__ __forceinline__ uint32_t get_epoch() { mbar_spin(SB + BAR_EPOCH, 0); return __shfl_sync(~0u, lds32(SB + OFF_HOLD + 8), 0); }
__device__ __forceinline__ void aloader(const Params& P, const Ptrs& Q, int bid, int r, int j, int lane, int w, uint32_t e, uint32_t epoch) {
  const uint32_t abase = SB + OFF_A + w * NA * 8192, fbase = SB + BAR_FULLA + w * NA * 8, ebase = SB + BAR_EMPTYA + w * NA * 8;
  uint32_t slot = NPRO, ph = 1, nst = 0, hph = 0, npace = 0;
  int t = -1, kind = -1, a0 = 0, a1 = 0;
  const CUtensorMap* tmA = nullptr;
  uint64_t pol = 0;
  uint4* hin = Q.s->halo[0][0] + (r * 16 + j * 2 + w - 16) * 136;
  uint32_t* const pace = Q.s->pace[0] + (bid & -PG) * 4;
  const uint8_t* const flags = Q.s->flags[r / (FG / 8)][w];
  auto adv = [&] { if (++slot == NA) { slot = 0; ph ^= 1; } };
#pragma unroll 1
  for (int g = NPRO; g <= NSTEP; g++) {
    const uint32_t cur = e;
    e = c_sched.v[j][g + 1];
    if (!(cur & E_RARE)) {
      if (cur & E_HAND) { mbar_spin(ebase + slot * 8, ph); e_arrive(fbase + slot * 8, 1); adv(); }
    } else {
      if (cur & F_NEW) {
        t++; kind = kind == 5 ? 0 : kind + 1;
        const bool narrow = kind == 2 || kind == 5;
        static_assert(TM_XIN == 0 && TM_X == 1 && TM_XA == 2 && TM_O == 3 && TM_H == 4, "map order");
        tmA = &P.tm[t < 2 ? 0 : (0x422311 >> (4 * kind)) & 15];
        pol = ((AEF >> t) & 1) ? 0x12F0000000000000ull : 0x1000000000000000ull;
        a0 = narrow ? 0 : w * 1024; a1 = narrow ? r * 128 + w * 64 : r * 64;
      }
      const bool xo = cur & E_XPUB0;
      uint32_t s = slot;
      if (cur & (E_HAND | E_ATTN | E_XPUB0)) {
        if (cur & E_KEEP) e_arrive(ebase + slot * 8, 4);
#pragma unroll 1
        for (int u = xo ? 0 : 1; u < 2; u++) { mbar_wait(ebase + slot * 8, ph); e_arrive(fbase + slot * 8, 1); adv(); }
      }
      uint32_t hold = 0;
      int lag = 0;
      if ((xo && t < 12) || (cur & F_GATH)) {
        uint32_t v;
        uint32_t v1;
        do asm volatile("ld.relaxed.gpu.global.v2.u32 {%0, %1}, [%2];" : "=r"(v), "=r"(v1) : "l"(pace + npace + (lane & (PG - 1)) * 2) : "memory");
        while (__any_sync(~0u, ((v ^ (epoch * 16 + t - 1)) | (v ^ v1)) & 31));
        v += v1;
        npace ^= PG * 2;
        lag = min((int)(v - __shfl_sync(~0u, v, bid & (PG - 1))), 8000) * LAGM >> 5;
        hold = __reduce_max_sync(~0u, lag);
        asm volatile("st.shared.b32 [%0], %1;" ::"r"(SB + OFF_HOLD + w * 4), "r"(hold) : "memory");
      }
      if (cur & (E_ATTN | E_XPUB0)) {
        const uint32_t s2 = s == NA - 1 ? 0 : s + 1;
        mbar_wait(SB + BAR_STG + w * 8, nst & 1);
        nst++;
        LT(0);
        const uint32_t c1 = clock32();
        e_store(tmA, a0 + sched_k(cur), a1, abase + s * 8192);
        if (xo) {
          mbar_spin(SB + BAR_STG2 + w * 8, ~t & 1);
          e_store(tmA, a0 + sched_k(cur) + 64, a1, abase + s2 * 8192);
          if (t == 12) break;
        } else e_arrive(SB + BAR_OWN + w * 8, 1);
        LT(1);
        spin_until(c1 + hold + (xo ? SDELAY : SDELAYO));
        LT(2);
        LT(5);
      }
      if (cur & E_SIG) {
        e_arrive(SB + BAR_SRV + w * 16, 4);
      }
      if (cur & E_REL) bulk_wait_all();
      if (cur & E_HALO) {
        mbar_spin(SB + BAR_STG + w * 8, nst & 1);
        nst++;
        const uint32_t hs = abase + (slot >= 3 ? slot - 3 : slot + 3) * 8192, ad = hs + lane * 32 + (lane & 4) * 4;
        if (r == 0) {
#pragma unroll
          for (int p = 0; p < 4; p++) sts128(hs + lane * 16 + p * 512, 0, 0, 0, 0);
          asm volatile("st.shared.b32 [%0], %1;" ::"r"(SB + OFF_RSTD + w * 288 + (lane & 7) * 4), "r"(0x3f800000) : "memory");
        } else {
          spin_until(clock32() + HDELAY);
          do {
            halo_fetch(hs, w, hin, SB + BAR_SPEC + 80 + w * 8);
            mbar_spin(SB + BAR_SPEC + 80 + w * 8, hph);
            hph ^= 1;
          } while (__any_sync(~0u, min(min(lds32(ad), lds32(ad + 1024)), lds32(SB + OFF_RSTD + w * 288)) == 0));
        }
        e_arrive(SB + BAR_HALO + w * 8, 1);
      }
      if ((cur & E_REL) && (kind == 1 || kind == 2) && r > 0) {
        uint4* hz = hin + lane;
        hin += 256 * 136;
#pragma unroll
        for (int p = 0; p < 4; p++) hz[p * 32] = make_uint4(0, 0, 0, 0);
        if (lane < 2) hz[128] = make_uint4(0, 0, 0, 0);
      }
      if (cur & E_WAIT) {
        wait_flags(flags + ((cur & E_PART1) ? FG : 0), epoch * 16 + t, lane);
      }
    }
    if (!(cur & (F_AUG | F_NOA))) {
      mbar_wait(ebase + slot * 8, ph);
      e_load(abase + slot * 8192, tmA, a0 + sched_k(cur), a1, fbase + slot * 8, pol);
      adv();
      if (cur & F_STAMP) {
        uint32_t stamp;
        asm volatile("mov.u32 %0, %%globaltimer_lo;" : "=r"(stamp));
        asm volatile("st.relaxed.gpu.global.u32 [%0], %1;" ::"l"(pace + npace + (bid & (PG - 1)) * 2 + w), "r"((stamp & ~31u) | ((epoch * 16 + t) & 31)) : "memory");
      }
    }
  }
  bulk_wait_all();
}

__device__ __forceinline__ void bloader(const Params& P, const Ptrs& Q, bool aux, int j, int lane, uint32_t e, uint32_t epoch) {
  const uint32_t* const sched = c_sched.v[aux ? 8 : j];
  int kind = -1, c2 = 0, c3 = 0, na = 0;
  const CUtensorMap* tmB = nullptr;
  uint32_t sph = 0, efm = aux ? 0 : BEF * 2;
  uint64_t pol = 0;
#pragma unroll 1
  for (int g = aux ? 8 + (j & 1) : NPRO; g < (aux ? NSTEP_AUX : NSTEP); g += 1 + aux) {
    const uint32_t cur = e;
    e = sched[g + 1 + aux];
    if (cur & F_NEW) {
      kind = kind == 5 ? 0 : kind + ((cur >> 29) & 3);
      static_assert(TM_WQKV == 5 && TM_WO == 6 && TM_W1A == 7 && TM_W1B == 8 && TM_W2 == 9, "map order");
      tmB = &P.tm[(0x978655 >> (4 * kind)) & 15];
      efm >>= 1;
      pol = (efm & 1) ? 0x12F0000000000000ull : 0x1000000000000000ull;
      na = (0x243233 >> (4 * kind)) & 15;
      c2 = ((0x277200 >> (4 * kind)) & 15) * j + (kind == 4 ? 3 : 0);
      c3 = kind <= 1 ? kind * 8 + j : 0;
    }
    const int need = g - (int)((cur >> 5) & 15);
    const uint32_t dst = SB + OFF_B + (cur & 31) * 8192, bar = SB + BAR_FULLB + (g & 7) * 8;
    mbar_wait(SB + BAR_EMPTYB + (need & 7) * 8, (need >> 3) & 1);
    if (!(cur & F_AUG)) {
      asm volatile("{\n.reg .pred p;\nelect.sync _|p, 0xffffffff;\n@p mbarrier.arrive.expect_tx.shared::cta.b64 _, [%2], %7;\n"
                   "@p cp.async.bulk.tensor.4d.shared::cluster.global.mbarrier::complete_tx::bytes.L2::cache_hint [%0], [%1, {%3, %4, %5, %6}], [%2], %8;\n}"
                   ::"r"(dst), "l"(tmB), "r"(bar), "r"(0), "r"(sched_k(cur)), "r"(c2), "r"(c3), "r"(na * 8192), "l"(pol) : "memory");
    } else {
      const bool chk = g < NSTEP / 2;
      const uint32_t b2 = chk ? SB + BAR_AUG : bar, ad = dst + lane * 16 + (lane >> 3) * 4;
      while (true) {
        asm volatile("{\n.reg .pred p;\nelect.sync _|p, 0xffffffff;\n@p mbarrier.arrive.expect_tx.shared::cta.b64 _, [%2], 4096;\n"
                     "@p cp.async.bulk.shared::cluster.global.mbarrier::complete_tx::bytes [%0], [%1], 4096, [%2];\n}"
                     ::"r"(dst), "l"(Q.s->aug[epoch & 1][(kind - (kind >= 3)) * 8 + j]), "r"(b2) : "memory");
        if (!chk) break;
        mbar_spin(b2, sph);
        sph ^= 1;
        uint32_t mn = ~0u;
#pragma unroll
        for (int u = 0; u < 8; u++) mn = min(mn, lds32(ad + u * 512));
        if (!__any_sync(~0u, mn == 0)) { e_arrive(bar, 1); break; }
      }
      __syncwarp();
    }
  }
}

constexpr uint32_t job_slots(int layer) {
  const int pos[10] = {11, 26, 63, 73, 77, 81, 92, 96, 100, 104};
  uint32_t v = 0;
  for (int m = 0; m < 10; m++) v |= (uint32_t)((layer * 148 + pos[m]) % NA) << (3 * m);
  return v;
}
constexpr uint32_t JOB_SLOTS0 = job_slots(0), JOB_SLOTS1 = job_slots(1);
__device__ __forceinline__ void server(const Params& P, const Ptrs& Q, int bid, int r, int j, int lane, uint32_t epoch) {
  const uint32_t c0 = clock32();
  if (PFT) {
    spin_until(c0 + PFT);
    if (lane < 16) asm volatile("cp.async.bulk.prefetch.L2.global [%0], 2048;" ::"l"(Q.x + (r * 128 + j * 16 + lane) * 1024) : "memory");
  }
  if (CPF) spin_until(c0 + CPF);
  epoch += __shfl_sync(~0u, c_sched.v[j][lane < 18 ? lane * 16 : 0] >> 31, 0);
  {
    const uint2 b = reinterpret_cast<const uint2*>(Q.b2 + j * 128)[lane];
    sts128(SB + OFF_VEC + lane * 16, b.x << 16, b.x & 0xffff0000u, b.y << 16, b.y & 0xffff0000u);
  }
  int hl = 0;
  uint32_t fph = 0, pend = SB + BAR_DUMMY3;
#pragma unroll 1
  for (int n = 0; n < 20; n++) {
    const int layer = n >= 10, m = n - 10 * layer;
    const bool stat = m == 0 || m == 2;
    const uint32_t slot = ((layer ? JOB_SLOTS1 : JOB_SLOTS0) >> (m * 3)) & 7;
    auto fetch = [&](int w) {
      asm volatile("{\n.reg .pred p;\nelect.sync _|p, 0xffffffff;\n@p mbarrier.arrive.expect_tx.shared::cta.b64 _, [%2], 4096;\n"
                   "@p cp.async.bulk.shared::cluster.global.mbarrier::complete_tx::bytes [%0], [%1], 4096, [%2];\n}"
                   ::"r"(SB + OFF_A + (w * NA + slot) * 8192), "l"(&Q.s->stats[hl][r * 32 + w * 16][0][0]), "r"(SB + BAR_SPEC + 64 + w * 8) : "memory");
    };
#pragma unroll 1
    for (int w = 0; w < 2; w++) {
      mbar_spin(SB + BAR_SRV + w * 16 + (n & 1) * 8, (n >> 1) & 1);
      if (stat) fetch(w);
      else {
        e_store(&P.tm[m == 1 ? TM_O : TM_H], m == 1 ? j * 64 : 448 * j + (m - 3) * 64, r * 128 + w * 64, SB + OFF_A + (w * NA + slot) * 8192);
        bulk_wait_read<1>();
        e_arrive(pend, 4);
        pend = SB + BAR_EMPTYA + (w * NA + slot) * 8;
      }
    }
    if (stat) {
#pragma unroll 1
      for (int w = 0; w < 2; w++) {
        const uint32_t src = SB + OFF_A + (w * NA + slot) * 8192 + (lane >> 1) * 256 + ((lane >> 1) & 7) * 32 + (lane & 1) * 16;
        float ms[2], md[2], mq[2], m0[2];
        while (true) {
          mbar_spin(SB + BAR_SPEC + 64 + w * 8, (fph >> w) & 1);
          fph ^= 1u << w;
          uint32_t bad = 0;
          ms[0] = ms[1] = md[0] = md[1] = mq[0] = mq[1] = m0[0] = m0[1] = 0.f;
#pragma unroll 1
          for (int p = 0; p < 8; p += 2) {
            const float4 v2[2] = {lds128(src ^ (p * 32)), lds128(src ^ (p * 32) ^ 32)};
            if (p == 0) { m0[0] = v2[0].x; m0[1] = v2[0].z; }
#pragma unroll
            for (int z = 0; z < 2; z++) {
              const float4 v = v2[z];
              const float a = v.x - m0[0], b = v.z - m0[1];
              bad |= __float_as_uint(v.y) ^ epoch;
              ms[0] += a; md[0] = fmaf(a, a, md[0]); mq[0] += __uint_as_float(__float_as_uint(v.y) & ~63u);
              ms[1] += b; md[1] = fmaf(b, b, md[1]); mq[1] += v.w;
            }
          }
          if (!__any_sync(~0u, bad & 63)) break;
          fetch(w);
          __syncwarp();
        }
        e_arrive(SB + BAR_EMPTYA + (w * NA + slot) * 8, 4);
        const int row = (lane >> 3) * 16 + (lane & 7);
#pragma unroll
        for (int z = 0; z < 2; z++) {
          const float d = ms[z] * 0.125f;
          asm volatile("st.shared.f32 [%0], %1;" ::"r"(SB + OFF_MEAN + (w * 64 + row + z * 8) * 4), "f"(m0[z] + d) : "memory");
          const float rs = rsq(fmaf(mq[z], 1.f / 1024.f, fmaxf(fmaf(md[z], 0.125f, -d * d), 0.f)) + 1e-5f);
          asm volatile("st.shared.f32 [%0], %1;" ::"r"(SB + OFF_RSTD + (w * 72 + 8 + row + z * 8) * 4), "f"(rs) : "memory");
        }
        e_arrive(SB + BAR_STAT + w * 8, 8);
      }
    }
    if (stat && n != 12) {
#pragma unroll 1
      for (int u = 0; u < (m ? 2 : 3); u++) {
        const uint32_t pitch = u == 2 ? 448 : 128;
        uint4* p = reinterpret_cast<uint4*>(u == 2 ? Q.s->h : (m ? Q.out : Q.s->x)) + (u == 2 ? 64 + j * 8 : j * 16 + u * 8) + ((r * 128 + (lane >> 3)) * pitch + (lane & 7));
#pragma unroll 1
        for (int k = 0; k < 32 / FUN; k++) {
#pragma unroll
          for (int z = 0; z < FUN; z++) {
            *p = make_uint4(~0u, ~0u, ~0u, ~0u);
            p += 4 * pitch;
            asm volatile("" : "+l"(p));
          }
        }
      }
      __syncwarp();
    }
    if ((0x222 >> m) & 1) {
      bulk_wait_all();
      e_arrive(pend, 4);
      pend = SB + BAR_DUMMY3;
      if (lane < 2) st_release8(&Q.s->flags[r / (FG / 8)][lane][(r & (FG / 8 - 1)) * 8 + j + (m == 9 ? FG : 0)], epoch * 16 + layer * 6 + (m == 1 ? 2 : 5));
      __syncwarp();
    }
    hl += stat;
  }
}

__device__ __forceinline__ void aux_math(const Ptrs& Q, int bid, int jj, int warp, int lane) {
  const int g = lane >> 2, q = lane & 3, c0 = (warp & 3) * 2;
  uint32_t st = warp >> 2, bf[16][4] = {};
  const uint32_t ad0 = SB + ((lane >> 4) * 8 + (lane & 7)) * 128 + (((c0 + ((lane >> 3) & 1)) ^ (lane & 7)) << 4);
#pragma unroll 1
  for (int t = 0; t < 4; t++) {
    float acc[4][4] = {};
    uint32_t bias[8];
#pragma unroll
    for (int a = 0; a < 8; a++) bias[a] = t >= 2 ? reinterpret_cast<const uint32_t*>(Q.b1 + 448 * jj + (t - 2) * 192 + c0 * 8)[(a >> 1) * 32 + (a & 1) * 4 + q] : 0u;
#pragma unroll 1
    for (int i = 0; i < 16; i++, st += 2) {
      const uint32_t ad = ad0 + (c_sched.v[8][st] & 31) * 8192;
      mbar_spin(SB + BAR_FULLB + (st & 7) * 8, (st >> 3) & 1);
#pragma unroll
      for (int u = 0; u < 16; u++)
        asm volatile("{\n.reg .pred p;\nsetp.ne.u32 p, %5, 0;\n@p ldmatrix.sync.aligned.m8n8.x4.trans.shared.b16 {%0,%1,%2,%3}, [%4];\n}"
                     : "+r"(bf[u][0]), "+r"(bf[u][1]), "+r"(bf[u][2]), "+r"(bf[u][3])
                     : "r"(ad + (u & 3) * 8192 + (u >> 2) * 2048), "r"((u & 3) != 3 || t == 3 ? 1 : 0) : "memory");
      __syncwarp();
      e_arrive(SB + BAR_EMPTYB + (st & 7) * 8, 2);
#pragma unroll
      for (int u = 0; u < 16; u++) mma16(acc[u & 3], bf[u][0], bf[u][1], bf[u][2], bf[u][3], 0x3F803F80u, 0x3F803F80u);
    }
    const uint32_t epoch = lds32(SB + OFF_HOLD + 8);
    const uint32_t o = (t * 8 + jj) * 1024 + g * 32 + ((c0 ^ g) << 2) + q + (epoch & 1) * 32768;
    uint32_t *const p0 = Q.s->aug[0][0] + o, *const p1 = Q.s->aug[0][0] + (o ^ 4);
#pragma unroll
    for (int a = 0; a < 8; a++) {
      const float u = acc[a >> 1][(a & 1) * 2];
      uint32_t h = movm(pack_bf16(u, u - bf_round(u)));
      if (g >= 6) h = bias[a];
      ((a & 1) ? p1 : p0)[(a >> 1) * 256] = h ? h : 0x8000u;
    }
    uint4* const z = reinterpret_cast<uint4*>(Q.s->aug[~epoch & 1][t * 8 + jj]) + (threadIdx.x & 127);
    z[0] = z[128] = make_uint4(0, 0, 0, 0);
  }
}

template <bool BYSM> __global__ void __launch_bounds__(NTHREADS, 1) mega_kernel(const __grid_constant__ Ptrs Q, const __grid_constant__ Params P) {
  extern __shared__ __align__(1024) uint8_t smem_raw[];
  constexpr uint32_t sb = SB;
  const uint32_t centry = clock32();
  const int warp = __shfl_sync(~0u, threadIdx.x >> 5, 0), lane = threadIdx.x & 31;
  const int bid = BYSM ? work_id() : blockIdx.x;
  const bool aux = bid >= NMAIN;
  const int r = Q44 ? ((bid >> 5) << 2) | (bid & 3) : ((bid >> 4) << 1) | (bid & 1), j = (aux ? bid * 2 : bid >> (1 + Q44)) & 7;
  PRO(0);
  {
    const uint32_t b = sb + OFF_BAR + warp * 48, cnt = warp < 6 ? 1 : (warp < 10 ? 4 : 8);
    asm volatile("{\n.reg .pred p;\nelect.sync _|p, 0xffffffff;\n@p mbarrier.init.shared::cta.b64 [%0], %1;\n@p mbarrier.init.shared::cta.b64 [%0 + 8], %1;\n"
                 "@p mbarrier.init.shared::cta.b64 [%0 + 16], %1;\n@p mbarrier.init.shared::cta.b64 [%0 + 24], %1;\n"
                 "@p mbarrier.init.shared::cta.b64 [%0 + 32], %1;\n@p mbarrier.init.shared::cta.b64 [%0 + 40], %1;\nfence.mbarrier_init.release.cluster;\n}"
                 ::"r"(b), "r"(cnt) : "memory");
  }
  __syncthreads();
  {
    static_assert(NPRO == 4, "prologue stages");
    const int st = ((11 - warp) * (aux ? 32 : 11)) >> 5, op = aux ? (st < 8) * 2 : 11 - warp - 3 * st, sd = aux ? st >> STGX : (op == 2 ? st : st & 2);
    const uint32_t bar0 = sb + OFF_BAR + (op * 6 + st) * 8;
    const int kc = aux ? (st >> 1) * 64 : (((st & 2 ? ROUND1 : ROUND0) >> (4 * j)) & 15) * 128 + (st & 1) * 64;
    spin_until(centry + (sd ? STG0 + sd * STG1 : 0));
    if (op == 2) {
      asm volatile("{\n.reg .pred p;\nelect.sync _|p, 0xffffffff;\n@p mbarrier.arrive.expect_tx.shared::cta.b64 _, [%2], 24576;\n"
                   "@p cp.async.bulk.tensor.4d.shared::cluster.global.mbarrier::complete_tx::bytes [%0], [%1, {%3, %4, %3, %5}], [%2];\n}"
                   ::"r"(sb + OFF_B + (aux ? (st & 1) * 114688 + (st >> 1) * 24576 : (st + pos0(0) / 3 - (st + pos0(0) / 3 >= 5 ? 5 : 0)) * 24576)), "l"(&P.tm[TM_WQKV]), "r"(bar0), "r"(0), "r"(kc), "r"(j + (st & aux)) : "memory");
    } else if (!aux) e_load(sb + OFF_A + (op * 6 + st) * 8192, &P.tm[TM_XIN], op * 1024 + kc, r * 64, bar0);
    PRO(1);
    asm volatile("prefetch.tensormap [%0];" ::"l"(&P.tm[warp]) : "memory");
  }
  if (warp >= 8) {
    asm volatile("setmaxnreg.dec.sync.aligned.u32 24;");
    if (warp == 11) {
      if (smem_u32(smem_raw) != SB) __trap();
      const uint32_t epoch = __shfl_sync(~0u, ld_relaxed(&Q.s->epoch[bid]) + 1, 0);
      Q.s->epoch[bid] = epoch;
      asm volatile("st.shared.b32 [%0], %1;" ::"r"(sb + OFF_HOLD + 8), "r"(epoch) : "memory");
      e_arrive(sb + BAR_EPOCH, 1);
      PRO(2);
      if (!aux) server(P, Q, bid, r, j, lane, epoch);
    } else {
      const uint32_t e = c_sched.v[aux ? 8 : j][aux ? warp : NPRO];
      spin_until(centry + STGL + (aux ? STGLX : (warp > 8 ? STGLW : 0)) + (e >> 31));
      PRO(2);
      const uint32_t epoch = get_epoch();
      PRO(3);
      if (warp <= 8 + aux) bloader(P, Q, aux, j + warp - 8, lane, e, epoch);
      else if (!aux) aloader(P, Q, bid, r, j, lane, warp - 9, e, epoch);
    }
  } else if (aux) aux_math(Q, bid, j + (warp >> 2), warp, lane);
  else {
    asm volatile("setmaxnreg.inc.sync.aligned.u32 240;");
    const int w = warp >> 2, wp = warp & 3;
    {
      uint32_t xr[32];
#pragma unroll
      for (int u = 0; u < 32; u++) if (NOI) asm volatile("" : "=r"(xr[u])); else xr[u] = 0;
      Pipe M;
      M.db = 0; M.g8 = 0; M.a8 = w * NA * 8; M.pa = 0; M.tph = 0; M.aend = (w + 1) * NA * 8;
      M.h0 = gridDim.y * 0x40000040u; M.h1 = gridDim.z * 0x40000040u; M.one = gridDim.z;
      M.curB = M.curA = M.prevB = M.prevA = M.sph = 0; M.nx = make_uint2(0, 0); M.w = w; M.l0 = lane == 0;
      M.bo = (wp * 16 + (lane & 15)) * 128 + (((lane >> 4) ^ (lane & 7)) << 4);
      M.so = __shfl_sync(~0u, SB + OFF_A + wp * 2048 + lane * 32 + (lane >> 2) * 4, lane);
      M.bo = __shfl_sync(~0u, M.bo, lane);
      auto nop = [](int) {};
      const uint32_t zero = gridDim.y - 1;
      PROF_T(w, 0, 3);
      if (STARTC) spin_until(centry + STARTC);
#pragma unroll 1
      for (int hl = 0; hl < 4; hl++) {
        const int t0 = hl * 3;
        const bool ffn = hl & 1;
        float acc[96], acn[64];
        uint32_t au[2] = {0u, 0u};
        {
          const int d = hl ? 0 : ((OWNP * 2u) >> (4 * j)) & 15;
          auto own = [&](auto h, uint32_t dep = 0) {
#pragma unroll
            for (int u = 4 * h.v; u < 4 * h.v + 4; u++)
              asm volatile("ldmatrix.sync.aligned.m8n8.x4.shared.b16 {%0,%1,%2,%3}, [%4];" : "=r"(xr[4 * u]), "=r"(xr[4 * u + 1]), "=r"(xr[4 * u + 2]), "=r"(xr[4 * u + 3])
                           : "r"(box_addr(sb + OFF_A + M.a8 * 1024, M.bo + dep, u & 3)) : "memory");
          };
          M.begin<192>(acc, ffn ? pos0(3) : pos0(0), t0, [&](int) { if (hl + d == 0) own(IC<0>{}); });
          if (hl + d == 0) own(IC<1>{}, (xr[0] | xr[4] | xr[8] | xr[12]) & zero);
          float ss[2] = {0.f, 0.f}, sq[2] = {0.f, 0.f};
          auto part = [&](auto c0, auto n) {
#pragma unroll
            for (int v = 0; v < 4 * n.v; v++) {
              const int u = c0.v + v / n.v * 4 + v % n.v;
              float a, b;
              asm volatile("shl.b32 %0, %2, 16;\nand.b32 %1, %2, 0xffff0000;" : "=f"(a), "=f"(b) : "r"(xr[u]));
              ss[u & 1] += a + b; sq[u & 1] = fmaf(a, a, fmaf(b, b, sq[u & 1]));
            }
          };
          const uint64_t plan = hl ? (ffn ? PLAN1 : PLAN2) : (w ? (d & 4 ? (d & 2 ? PB6 : PB4) : (d ? PB2 : PB0)) : (d & 4 ? (d & 2 ? PA6 : PA4) : (d ? PA2 : PA0)));
          auto todo = [&](int i) { uint64_t v; asm volatile("shr.u64 %0, %1, %2;" : "=l"(v) : "l"(plan), "r"((i + 1 - d) * 8)); return (uint32_t)v; };
          uint32_t m = todo(1);
          M.run<192, false>(acc, 1, 16, 1u << 10, 16 - (ffn ? LEAD3 : LEAD0), [&](int i, uint2 ok) {
           CT(0);
           if (m & 127) {
             if (m & 1) part(IC<0>{}, IC<2>{});
             if (m & 2) part(IC<2>{}, IC<2>{});
             if (m & 4) part(IC<16>{}, IC<1>{});
             if (m & 8) part(IC<17>{}, IC<1>{});
             if (m & 16) part(IC<18>{}, IC<1>{});
             if (m & 32) part(IC<19>{}, IC<1>{});
             if (m & 64) {
               const uint32_t epoch = lds32(sb + OFF_HOLD + 8);
#pragma unroll
               for (int o = 1; o < 4; o *= 2)
#pragma unroll
                 for (int z = 0; z < 2; z++) { ss[z] += __shfl_xor_sync(~0u, ss[z], o); sq[z] += __shfl_xor_sync(~0u, sq[z], o); }
               const float m0 = ss[0] * (1.f / 128.f), m1 = ss[1] * (1.f / 128.f);
               const int rowpair = r * 64 + w * 32 + wp * 8 + (M.lane() >> 2);
               if ((M.lane() & 3) == 0)
                 st_pkt(&Q.s->stats[hl][rowpair >> 1][j][rowpair & 1], __float_as_uint(m0), (__float_as_uint(fmaxf(fmaf(-ss[0], m0, sq[0]), 0.f)) & ~63u) | (epoch & 63),
                        __float_as_uint(m1), __float_as_uint(fmaxf(fmaf(-ss[1], m1, sq[1]), 0.f)));
             }
           }
           CT(1);
           M.ensure(ok);
           CT(3);
           M.validate(hl != 0, &P.tm[ffn ? TM_XA16 : TM_X16], w * 1024, r * 64, wp, j, [&] {
            if (m & 128) { if (m & 1) own(IC<1>{}); else own(IC<0>{}); }
            m = todo(i + 1);
            if (i == STATI) { mbar_spin(sb + BAR_STAT + w * 8, hl & 1); stats_fetch(w, wp, M.lane(), au); }
           });
           CT(4);
          });
          M.end<192, true>(acc, ffn ? 0 : 4, ffn ? posa(3) : posa(0), au[0], au[1], t0);
          PROF_T(w, t0, 2);
        }
        if (!ffn) {
          Attn T;
#pragma unroll 1
          for (int wave = 0; wave < 2; wave++) {
            AP(9);
            uint4* const hp = Q.s->halo[0][0] + (uint32_t)(((hl + wave) * 256 + r * 16 + j * 2 + w) * 136);
            T.A(acc, M, w, wp, r, hp);
            AP(0);
            if (wave == 0) {
              M.begin<192, PACE2 & 1>(acc, pos0(1), t0 + 1);
              M.run<192>(acc, 1, NH1, 4, -1, nop);
              T.B(w, wp, M.lane(), 0);
              M.drain();
            } else {
              M.begin<128, (PACE2 >> 1) & 1>(acn, pos0(2), t0 + 2);
              M.run<128>(acn, 1, NH2, 4, -1, nop);
              T.B(w, wp, M.lane(), 1);
              M.drain();
#pragma unroll
              for (int z = 0; z < 64; z++) asm volatile("mov.b32 %0, %1;" : "=f"(acc[z]) : "f"(acn[z]));
            }
            AP(2);
            T.C(wp, r, M.lane(), zero, [&] { if (EFIRST == 3 || (EFIRST == 2 && wave)) T.E(M, wave); });
            AP(3);
            if (wave == 1) break;
            M.run<192>(acc, NH1, 16, 1u << 7, 16 - LEAD1, [&](int i) { if (EFIRST < 3 && i == NH1) T.E(M, false); });
            M.end<192, true>(acc, 4, posa(1), au[0], au[1], t0 + 1);
            PROF_T(w, t0 + 1, 2);
          }
#pragma unroll
          for (int z = 0; z < 64; z++) asm volatile("mov.b32 %0, %1;" : "=f"(acn[z]) : "f"(acc[z]));
          if (EFIRST == 1) T.E(M, true);
          else if (!EFIRST) {
            M.ensure(M.iss<128, false>(acn, false));
            T.E(M, true);
          }
        } else {
          uint32_t pk[48], pk2[64];
          pack_relu<0, 48>(pk, acc);
          {
            float acc2[128];
            M.begin<256, (PACE2 >> 3) & 1>(acc2, pos0(4), t0 + 1);
            M.run<256>(acc2, 1, 16, 0x248, 16 - LEAD4, [&](int i) { ffn_stage(pk, i, M); });
            M.end<256, true>(acc2, 0, posa(4), au[0], au[1], t0 + 1);
            pack_relu<0, 64>(pk2, acc2);
            PROF_T(w, t0 + 1, 2);
          }
          M.begin<128, (PACE2 >> 4) & 1>(acn, pos0(5), t0 + 2);
          M.run<128>(acn, 1, 13, 0x1248, -1, [&](int i) { ffn_stage(pk2, i, M); });
        }
        {
          const int ks = ffn ? 56 : 16, pause = ks - (ffn ? LEAD5 : LEAD2), vfrom = ffn ? 99 : 7;
          const int imid = w ? pause : (ffn ? 20 : IPRE);
          auto check = [&](int i) {
            if (i >= vfrom) {
              if (i == 7) mbar_spin(sb + BAR_OWN + w * 8, hl >> 1);
              M.validate(true, &P.tm[TM_O16], 0, r * 128 + w * 64, wp, j, [] {});
            }
          };
          M.run<128>(acn, ffn ? 13 : NH2 + !EFIRST, imid, 0, -1, check);
          if (w) M.drain();
          float pre[64], rstd[2];
          presum(pre, xr, M.lane(), ffn ? 1.f : 0.f);
          own_rstd(w, wp, M.lane(), rstd);
          if (w) mbar_spin(SB + BAR_LEAD, M.tph);
          M.run<128>(acn, imid, ks, 0, 0, check);
          M.end<128, false>(acn, 2, 0, 0, 0, t0 + 2);
          epi_res(acn, pre, ffn ? rstd[0] * rstd[0] : 1.f, ffn ? rstd[1] * rstd[1] : 1.f, xr, M, wp);
          PROF_T(w, t0 + 2, 2);
        }
      }
    }
  }
}

typedef CUresult (*EncFn)(CUtensorMap*, CUtensorMapDataType, cuuint32_t, void*, const cuuint64_t*, const cuuint64_t*, const cuuint32_t*,
                          const cuuint32_t*, CUtensorMapInterleave, CUtensorMapSwizzle, CUtensorMapL2promotion, CUtensorMapFloatOOBfill);

void enc2(EncFn enc, CUtensorMap* tm, const void* p, uint64_t cols, uint64_t rows, uint32_t boxrows = 64, CUtensorMapL2promotion promo = APROMO) {
  cuuint64_t gd[2] = {cols, rows}, gs[1] = {cols * 2};
  cuuint32_t box[2] = {64, boxrows}, es[2] = {1, 1};
  enc(tm, CU_TENSOR_MAP_DATA_TYPE_BFLOAT16, 2, const_cast<void*>(p), gd, gs, box, es, CU_TENSOR_MAP_INTERLEAVE_NONE, CU_TENSOR_MAP_SWIZZLE_128B,
      promo, CU_TENSOR_MAP_FLOAT_OOB_FILL_NONE);
}
void enc4(EncFn enc, CUtensorMap* tm, const void* p, uint64_t K, uint64_t N, uint64_t d2, uint64_t s2, uint64_t d3, uint64_t s3, uint32_t na) {
  cuuint64_t gd[4] = {64, K, d2, d3}, gs[3] = {N * 2, s2, s3};
  cuuint32_t box[4] = {64, 64, na, 1}, es[4] = {1, 1, 1, 1};
  enc(tm, CU_TENSOR_MAP_DATA_TYPE_BFLOAT16, 4, const_cast<void*>(p), gd, gs, box, es, CU_TENSOR_MAP_INTERLEAVE_NONE, CU_TENSOR_MAP_SWIZZLE_128B,
      WPROMO, CU_TENSOR_MAP_FLOAT_OOB_FILL_NONE);
}

}

extern "C" void kernel_launch(void* const* d_in, const int* in_sizes, int n_in, void* d_out, int out_size) {
  static EncFn enc = nullptr;
  static Scratch* ps = nullptr;
  static void (*kernel)(Ptrs, Params) = mega_kernel<true>;
  if (!enc) {
    cudaDriverEntryPointQueryResult qr;
    cudaGetDriverEntryPoint("cuTensorMapEncodeTiled", (void**)&enc, cudaEnableDefault, &qr);
    int dev = 0, nsm = 0;
    cudaGetDevice(&dev);
    cudaDeviceGetAttribute(&nsm, cudaDevAttrMultiProcessorCount, dev);
    if (nsm != NMAIN + NAUX) kernel = mega_kernel<false>;
    cudaFuncSetAttribute(kernel, cudaFuncAttributeMaxDynamicSharedMemorySize, SMEM_BYTES);
    cudaGetSymbolAddress((void**)&ps, g_s);
  }
  Params P;
  Ptrs Q;
  Q.s = ps;
  void *p_h = ps->h, *p_x = ps->x;
  enc2(enc, &P.tm[TM_XIN], d_in[0], 2048, 1024, 64, XPROMO);
  enc2(enc, &P.tm[TM_X], d_out, 2048, 1024);
  enc2(enc, &P.tm[TM_XA], p_x, 2048, 1024);
  enc2(enc, &P.tm[TM_O], p_h, 3584, 2048);
  enc2(enc, &P.tm[TM_H], p_h, 3584, 2048);
  enc2(enc, &P.tm[TM_X16], d_out, 2048, 1024, 16);
  enc2(enc, &P.tm[TM_XA16], p_x, 2048, 1024, 16);
  enc2(enc, &P.tm[TM_O16], p_h, 3584, 2048, 16);
  enc4(enc, &P.tm[TM_WQKV], d_in[1], 1024, 3072, 3, 2048, 16, 128, 3);
  enc4(enc, &P.tm[TM_WO], d_in[2], 1024, 1024, 16, 128, 1, 128, 2);
  enc4(enc, &P.tm[TM_W1A], d_in[4], 1024, 3584, 56, 128, 1, 128, 4);
  enc4(enc, &P.tm[TM_W1B], d_in[4], 1024, 3584, 56, 128, 1, 128, 3);
  enc4(enc, &P.tm[TM_W2], d_in[6], 3584, 1024, 16, 128, 1, 128, 2);
  Q.out = (__nv_bfloat16*)d_out;
  Q.b1 = (const __nv_bfloat16*)d_in[5];
  Q.x = (const __nv_bfloat16*)d_in[0];
  Q.b2 = (const __nv_bfloat16*)d_in[7];
  kernel<<<NMAIN + NAUX, NTHREADS, SMEM_BYTES, cudaStreamPerThread>>>(Q, P);
}
```

```cpp
#include <cuda_runtime.h>
#include <cuda_bf16.h>
#include <cuda.h>
#include <stdint.h>

#define LEAD0 2
#define LEAD1 2
#define LEAD2 4
#define LEAD3 2
#define LEAD4 1
#define LEAD5 5
#define WPROMO CU_TENSOR_MAP_L2_PROMOTION_L2_128B
#define PLAN1 0x7f0000ull
#define PLAN2 0x400000003f0000ull
#define P0S 0x640096
#define PAS 0x430ff
#define PA0 0x70000a00050000ull
#define PB0 0x6000120009040000ull
#define PA2 0x600012000c8180ull
#define PB2 0x400030000a048180ull
#define PA4 0x70000e8180ull
#define PB4 0x60001a048180ull
#define PA6 0x7c8380ull
#define PB6 0x7c8380ull
#define LAGM 27
#define APROMO CU_TENSOR_MAP_L2_PROMOTION_L2_128B
#define PFT 500
#define HP0 2
#define LSO 1
#define STATI 13
#define PACE2 0x1a
#define ST2 12
#define STB 3
#define PROBE 4
#define XO 0
#define FORD 0x01234567, 0x01234567, 0x01234567, 0x01234567, 0x04567123, 0x04567123, 0x04567123, 0x04765123
#define SIG0 14
#define STGX 2
#define STGM 3
#define NPRO 4
#define XPROMO CU_TENSOR_MAP_L2_PROMOTION_L2_256B
#define IPRE 7
#define FILLT 1
#define EARLYC 1
#define OWNDLY 0
#define EPW 0
#define CPF 5000
#define STG0 800
#define STG1 400
#define STGL (STG0 + 4 * STG1)
#define STGLW 0
#define STGLX 0
#define STARTC 0
#define FUN 4
#define XEF 0
#define BEF 0xff8
#define AEF 0xdb6
#define SEF 0
#define SDELAYO 1000
#define SDELAY 300
#define Q44 1
#define FG 8
#define NOI 1
#define EFIRST 1
#define STA 1
#define PG (Q44 ? 32 : 16)
#define NH1 6
#define NH2 3
namespace {

constexpr int NMAIN = 128, NAUX = 4, NTHREADS = 384;
constexpr uint32_t OFF_B = 0;
constexpr uint32_t OFF_A = 131072;
constexpr uint32_t OFF_VEC = 229376;
constexpr uint32_t OFF_BAR = 231424;
constexpr uint32_t OFF_RSTD = OFF_VEC + 512, OFF_MEAN = OFF_VEC + 1088, OFF_HOLD = OFF_VEC + 2032;
constexpr uint32_t SMEM_BYTES = OFF_BAR + 960;
constexpr uint32_t BAR_FULLA = OFF_BAR, BAR_FULLB = OFF_BAR + 96, BAR_OWN = OFF_BAR + 160, BAR_EPOCH = OFF_BAR + 176, BAR_AUG = OFF_BAR + 184, BAR_SPEC = OFF_BAR + 192,
                   BAR_EMPTYA = OFF_BAR + 288, BAR_STG = OFF_BAR + 384, BAR_SRV = OFF_BAR + 400, BAR_LEAD = OFF_BAR + 432, BAR_HALO = OFF_BAR + 440, BAR_STG2 = OFF_BAR + 456,
                   BAR_DUMMY3 = OFF_BAR + 472, BAR_EMPTYB = OFF_BAR + 480, BAR_STAT = OFF_BAR + 544, BAR_DUMMY = OFF_BAR + 560;
constexpr int NA = 6;
constexpr uint32_t SB = 1024;
constexpr uint32_t SPIN_LIMIT = 1u << 22;

enum { TM_XIN = 0, TM_X, TM_XA, TM_O, TM_H, TM_WQKV, TM_WO, TM_W1A, TM_W1B, TM_W2, TM_X16, TM_XA16, TM_O16, TM_COUNT };

struct Scratch;
struct Ptrs {
  Scratch* s;
  __nv_bfloat16* out;
  const __nv_bfloat16* b1;
  const __nv_bfloat16* x;
  const __nv_bfloat16* b2;
};
struct Params { CUtensorMap tm[TM_COUNT]; };

constexpr int NSTEP = 280, NSTEP_AUX = 128;
enum : uint32_t { F_STAMP = 1u << 28, F_GATH = 1u << 15, F_NEW = 1u << 16, F_AUG = 1u << 17, F_NOA = 1u << 18, E_HAND = 1u << 19, E_ATTN = 1u << 20, E_XPUB0 = 1u << 21,
                  E_WAIT = 1u << 22, E_REL = 1u << 23, E_KEEP = 1u << 24, E_PART1 = 1u << 25,
                  E_SIG = 1u << 27, E_RARE = F_NEW | E_KEEP | (0xfu << 20) | E_SIG };
constexpr uint32_t first_order(int j) {
  constexpr uint32_t t[8] = {FORD};
  uint32_t v = 0;
  for (int p = 0; p < 8; p++) v |= ((t[j] >> (28 - 4 * p)) & 15) << (4 * p);
  return v;
}
constexpr uint32_t own_rounds() { uint32_t v = 0; for (int j = 0; j < 8; j++) for (int p = 0; p < 8; p++) if (((first_order(j) >> (4 * p)) & 15) == j) v |= p << (4 * j); return v; }
constexpr uint32_t OWNP = own_rounds();
constexpr uint32_t first_round(int p) { uint32_t v = 0; for (int j = 0; j < 8; j++) v |= ((first_order(j) >> (4 * p)) & 15) << (4 * j); return v; }
constexpr uint32_t ROUND0 = first_round(0), ROUND1 = first_round(1);
__host__ __device__ constexpr int pos0(int kind) { return (P0S >> (4 * kind)) & 15; }
__host__ __device__ constexpr int posa(int kind) { return (PAS >> (4 * kind)) & 15; }
struct Sched { uint32_t v[9][NSTEP + 8]; };
constexpr Sched make_sched() {
  Sched T{};
  for (int j = 0; j < 8; j++) {
    int owner[16] = {};
    for (int i = 0; i < 16; i++) owner[i] = -100;
    int p = 0, g = 0;
    for (int t = 0; t < 12; t++) {
      const int kind = t % 6, ks = kind == 5 ? 56 : (kind == 2 ? 16 : 17);
      for (int i = 0; i < ks; i++) {
        const bool augs = ks == 17 && i == 16;
        const int na = (kind == 2 || kind == 5) ? 2 : (augs ? 1 : (kind == 4 ? 4 : 3));
        if (i == 0) p = pos0(kind);
        if (augs) p = posa(kind);
        if (p + na > 16) p = 0;
        int need = g - 8;
        for (int a = p; a < p + na; a++) { if (owner[a] > need) need = owner[a]; owner[a] = g; }
        uint32_t k = i, f = i == (t ? 0 : NPRO) ? F_NEW | (1u << 29) : 0;
        if (augs) { k = 0; f |= F_AUG; }
        else if (kind == 0 || kind == 3) {
          const int o = i - 2;
          if (t == 0) k = ((first_order(j) >> (4 * (i >> 1))) & 15) * 2 + (i & 1);
          else if (i < 2) { k = 2 * j + i; f |= F_NOA | (i == 0 ? E_XPUB0 : 0); }
          else { const int half = o >= 7; int u = o - 7 * half; { const int b = (XO & 3) == 0 ? 0 : ((XO & 3) == 1 ? (j & 4) ^ 4 : j & 4); u += u >= (j ^ b); u ^= b; } k = 2 * u + half; if (i == 6) f |= E_REL; }
          if (i == 11) f |= E_HAND;
          if (i == (t ? 11 : SIG0)) f |= E_SIG;
        } else if (kind == 1 || kind == 4) {
          if (kind == 1) f |= i == 3 ? E_HAND : (i == 8 ? E_HAND | E_KEEP : 0);
          if (kind == 1) f |= i == 13 ? E_REL : 0;
          else if (i == 4 || i == 7 || i == 10) f |= E_HAND;
        } else if (kind == 2) {
          f |= i == 0 ? E_WAIT : (i == 3 ? E_HAND : 0);
          if (i == 8) { k = 8 + j; f |= E_ATTN | E_KEEP | F_NOA; }
          if (i > 8) { const int b = (XO >> 2) == 0 ? 0 : ((XO >> 2) == 1 ? (j & 4) ^ 4 : j & 4); k = 8 + ((i - 9 + (i - 9 >= (j ^ b))) ^ b); }
          if (i == 11) f |= E_REL;
        } else {
          k = i < 24 ? (i / 3) * 7 + i % 3 : ((i - 24) / 4) * 7 + 3 + (i - 24) % 4;
          if (i == 4 || i == 7 || i == 10 || i == 13) f |= E_HAND;
          f |= i == 0 ? E_WAIT : (i == 24 ? E_WAIT | E_PART1 : 0);
        }
        if ((kind == 2 || kind == 5) && t < 11 && i == ks - (kind == 2 ? STA : STB)) f |= F_STAMP;
        if (((PACE2 >> kind) & 1) && i == ST2) f |= F_STAMP;
        if (i == 0 && t && ((PACE2 >> ((t - 1) % 6)) & 1)) f |= F_GATH;
        T.v[j][g] = p | ((g - need) << 5) | (k << 9) | f;
        p += na; g++;
      }
    }
    T.v[j][NSTEP] = F_NEW | F_NOA | E_XPUB0 | (2 * j << 9);
  }
  for (int w = 0; w < 2; w++) {
    int owner[14] = {};
    for (int i = 0; i < 14; i++) owner[i] = -100;
    for (int g = w, p = 0; g < NSTEP_AUX; g += 2) {
      const int na = g < 96 ? 3 : 4;
      if (p + na > 14) p = 0;
      int need = g - 8;
      for (int a = p; a < p + na; a++) { if (owner[a] > need) need = owner[a]; owner[a] = g; }
      T.v[8][g] = (p + 14 * w) | ((g - need) << 5) | ((g & 31) >> 1 << 9) | ((g & 30) && g - w != 8 ? 0 : F_NEW | (g - w == 64 ? 2u : 1u) << 29);
      p += na;
    }
  }
  return T;
}
__constant__ Sched c_sched = make_sched();
__device__ __forceinline__ int sched_k(uint32_t e) { return (e >> 3) & 0xfc0; }

struct Scratch {
  __nv_bfloat16 x[2048 * 1024];
  __nv_bfloat16 h[2048 * 3584];
  uint32_t epoch[160];
  uint8_t flags[16][2][64];
  uint32_t pace[8][64];
  uint32_t aug[2][32][1024];
  uint4 stats[4][512][8][2];
  uint4 halo[4][256][136];
};
__device__ __align__(1024) Scratch g_s;
#define PROF_T(w, t, i)
#define PRO(i)
#define LT(i)
#define CT(n)
#define ST(i)
#define AP(i)

__device__ __forceinline__ int work_id() {
  uint32_t smid;
  asm volatile("mov.u32 %0, %%smid;" : "=r"(smid));
  const int t = smid >> 1, u = t - 32, d = (u * 37) >> 8;
  int id = (t & 7) * 16 + (t >> 3) * 2;
  if (t >= 32) id = (1 + u - 7 * d) * 16 + (4 + d) * 2;
  if (t >= 60) id = t < 62 ? t * 2 + 8 : t * 2 - 116;
  return id + (smid & 1);
}

__device__ __forceinline__ uint32_t smem_u32(const void* p) { return (uint32_t)__cvta_generic_to_shared(p); }
__device__ __forceinline__ void mbar_init(uint32_t bar, int cnt) { asm volatile("mbarrier.init.shared::cta.b64 [%0], %1;" ::"r"(bar), "r"(cnt)); }
__device__ __forceinline__ void mbar_expect_tx(uint32_t bar, uint32_t bytes) { asm volatile("mbarrier.arrive.expect_tx.shared::cta.b64 _, [%0], %1;" ::"r"(bar), "r"(bytes) : "memory"); }
__device__ __forceinline__ void mbar_arrive(uint32_t bar, uint32_t cnt) { asm volatile("mbarrier.arrive.shared::cta.b64 _, [%0], %1;" ::"r"(bar), "r"(cnt) : "memory"); }
__device__ __forceinline__ void arrive_n(uint32_t bar, bool) { asm volatile("{\n.reg .pred p;\nelect.sync _|p, 0xffffffff;\n@p mbarrier.arrive.shared::cta.b64 _, [%0];\n}" ::"r"(bar) : "memory"); }
__device__ __forceinline__ void arrive_2(uint32_t b0, uint32_t b1, bool) {
  asm volatile("{\n.reg .pred p;\nelect.sync _|p, 0xffffffff;\n@p mbarrier.arrive.shared::cta.b64 _, [%0];\n@p mbarrier.arrive.shared::cta.b64 _, [%1];\n}" ::"r"(b0), "r"(b1) : "memory");
}
__device__ __forceinline__ void mbar_wait(uint32_t bar, uint32_t parity) {
  asm volatile(
      "{\n.reg .pred p;\n.reg .u32 c;\nmov.u32 c, 0;\n"
      "LAB_WAIT:\nmbarrier.try_wait.parity.shared::cta.b64 p, [%0], %1;\n@p bra.uni DONE;\n"
      "add.u32 c, c, 1;\nsetp.lt.u32 p, c, 4000000;\n@p bra.uni LAB_WAIT;\ntrap;\nDONE:\n}" ::"r"(bar), "r"(parity) : "memory");
}
__device__ __forceinline__ void mbar_spin(uint32_t bar, uint32_t parity) {
  asm volatile("{\n.reg .pred p;\nLAB_WAIT:\nmbarrier.try_wait.parity.shared::cta.b64 p, [%0], %1;\n@!p pmevent 7;\n@!p bra.uni LAB_WAIT;\n}" ::"r"(bar), "r"(parity) : "memory");
}
__device__ __forceinline__ void mbar_spin31(uint32_t bar, uint32_t ph) {
  asm volatile("{\n.reg .pred p;\n.reg .b64 s;\nmov.b64 s, {%1, %1};\nLAB_WAIT:\nmbarrier.try_wait.shared::cta.b64 p, [%0], s;\n@!p pmevent 7;\n@!p bra.uni LAB_WAIT;\n}" ::"r"(bar), "r"(ph) : "memory");
}
__device__ __forceinline__ bool elect_one() {
  uint32_t p;
  asm volatile("{\n.reg .pred P;\nelect.sync _|P, 0xffffffff;\nselp.u32 %0, 1, 0, P;\n}" : "=r"(p));
  return p != 0;
}
__device__ __forceinline__ bool mbar_test(uint32_t bar, uint32_t parity) {
  uint32_t ok;
  asm volatile("{\n.reg .pred p;\nmbarrier.test_wait.parity.shared::cta.b64 p, [%1], %2;\nselp.u32 %0, 1, 0, p;\n}" : "=r"(ok) : "r"(bar), "r"(parity) : "memory");
  return ok != 0;
}
__device__ __forceinline__ void tma_ld2(uint32_t dst, const CUtensorMap* tm, int c0, int c1, uint32_t bar) {
  asm volatile("cp.async.bulk.tensor.2d.shared::cluster.global.mbarrier::complete_tx::bytes [%0], [%1, {%3, %4}], [%2];" ::"r"(dst), "l"(tm), "r"(bar), "r"(c0), "r"(c1) : "memory");
}
__device__ __forceinline__ void tma_ld4(uint32_t dst, const CUtensorMap* tm, int c1, int c2, int c3, uint32_t bar, uint64_t pol = 0x1000000000000000ull) {
  asm volatile("cp.async.bulk.tensor.4d.shared::cluster.global.mbarrier::complete_tx::bytes.L2::cache_hint [%0], [%1, {%3, %4, %5, %6}], [%2], %7;" ::"r"(dst), "l"(tm), "r"(bar), "r"(0), "r"(c1), "r"(c2), "r"(c3), "l"(pol) : "memory");
}
__device__ __forceinline__ void tma_st2(const CUtensorMap* tm, int c0, int c1, uint32_t src) {
  asm volatile("cp.async.bulk.tensor.2d.global.shared::cta.bulk_group [%0, {%2, %3}], [%1];" ::"l"(tm), "r"(src), "r"(c0), "r"(c1) : "memory");
}
__device__ __forceinline__ void bulk_ld(uint32_t dst, const void* src, uint32_t bytes, uint32_t bar) {
  asm volatile("cp.async.bulk.shared::cluster.global.mbarrier::complete_tx::bytes [%0], [%1], %2, [%3];" ::"r"(dst), "l"(src), "r"(bytes), "r"(bar) : "memory");
}
__device__ __forceinline__ void e_arrive(uint32_t bar, uint32_t cnt) {
  if (cnt == 1) asm volatile("{\n.reg .pred p;\nelect.sync _|p, 0xffffffff;\n@p mbarrier.arrive.shared::cta.b64 _, [%0];\n}" ::"r"(bar) : "memory");
  else asm volatile("{\n.reg .pred p;\nelect.sync _|p, 0xffffffff;\n@p mbarrier.arrive.shared::cta.b64 _, [%0], %1;\n}" ::"r"(bar), "r"(cnt) : "memory");
}
template <int BYTES = 8192> __device__ __forceinline__ void e_load(uint32_t dst, const CUtensorMap* tm, int c0, int c1, uint32_t bar, uint64_t pol = 0x1000000000000000ull) {
  asm volatile("{\n.reg .pred p;\nelect.sync _|p, 0xffffffff;\n@p mbarrier.arrive.expect_tx.shared::cta.b64 _, [%2], %5;\n"
               "@p cp.async.bulk.tensor.2d.shared::cluster.global.mbarrier::complete_tx::bytes.L2::cache_hint [%0], [%1, {%3, %4}], [%2], %6;\n}"
               ::"r"(dst), "l"(tm), "r"(bar), "r"(c0), "r"(c1), "n"(BYTES), "l"(pol) : "memory");
}
__device__ __forceinline__ void e_store(const CUtensorMap* tm, int c0, int c1, uint32_t src) {
  asm volatile("{\n.reg .pred p;\nfence.proxy.async.shared::cta;\nelect.sync _|p, 0xffffffff;\n"
               "@p cp.async.bulk.tensor.2d.global.shared::cta.bulk_group [%0, {%2, %3}], [%1];\ncp.async.bulk.commit_group;\n}"
               ::"l"(tm), "r"(src), "r"(c0), "r"(c1) : "memory");
}
__device__ __forceinline__ void bulk_commit() { asm volatile("cp.async.bulk.commit_group;" ::: "memory"); }
template <int N> __device__ __forceinline__ void bulk_wait_read() { asm volatile("cp.async.bulk.wait_group.read %0;" ::"n"(N) : "memory"); }
__device__ __forceinline__ void bulk_wait_all() { asm volatile("cp.async.bulk.wait_group 0;" ::: "memory"); }
__device__ __forceinline__ void fence_async_smem() { asm volatile("fence.proxy.async.shared::cta;" ::: "memory"); }
__device__ __forceinline__ void wg_fence() { asm volatile("wgmma.fence.sync.aligned;" ::: "memory"); }
__device__ __forceinline__ void wg_commit() { asm volatile("wgmma.commit_group.sync.aligned;" ::: "memory"); }
template <int N> __device__ __forceinline__ void wg_wait() { asm volatile("wgmma.wait_group.sync.aligned %0;" ::"n"(N) : "memory"); }
__device__ __forceinline__ void wg_bar(int w) { asm volatile("bar.sync %0, 128;" ::"r"(w + 1) : "memory"); }
__device__ __forceinline__ uint32_t ld_acquire(const uint32_t* p) { uint32_t v; asm volatile("ld.acquire.gpu.global.u32 %0, [%1];" : "=r"(v) : "l"(p) : "memory"); return v; }
__device__ __forceinline__ uint4 ld_relaxed4(const uint32_t* p) {
  uint4 v; asm volatile("ld.relaxed.gpu.global.v4.u32 {%0,%1,%2,%3}, [%4];" : "=r"(v.x), "=r"(v.y), "=r"(v.z), "=r"(v.w) : "l"(p) : "memory"); return v;
}
__device__ __forceinline__ void st_release8(uint8_t* p, uint32_t v) { asm volatile("st.release.gpu.global.u8 [%0], %1;" ::"l"(p), "r"(v) : "memory"); }
__device__ __forceinline__ uint32_t ld_relaxed(const uint32_t* p) { uint32_t v; asm volatile("ld.relaxed.gpu.global.u32 %0, [%1];" : "=r"(v) : "l"(p) : "memory"); return v; }
__device__ __forceinline__ void st_release(uint32_t* p, uint32_t v) { asm volatile("st.release.gpu.global.u32 [%0], %1;" ::"l"(p), "r"(v) : "memory"); }
__device__ __forceinline__ void st_pkt(uint4* p, uint32_t a, uint32_t b, uint32_t c, uint32_t d) {
  asm volatile("{\n.reg .b64 lo, hi;\n.reg .b128 v;\nmov.b64 lo, {%1, %2};\nmov.b64 hi, {%3, %4};\nmov.b128 v, {lo, hi};\nst.relaxed.gpu.global.b128 [%0], v;\n}" ::"l"(p), "r"(a), "r"(b), "r"(c), "r"(d) : "memory");
}
__device__ __forceinline__ uint4 ld_pkt(const uint4* p) {
  uint4 r;
  asm volatile("{\n.reg .b64 lo, hi;\n.reg .b128 v;\nld.relaxed.gpu.global.b128 v, [%4];\nmov.b128 {lo, hi}, v;\nmov.b64 {%0, %1}, lo;\nmov.b64 {%2, %3}, hi;\n}" : "=r"(r.x), "=r"(r.y), "=r"(r.z), "=r"(r.w) : "l"(p) : "memory");
  return r;
}
__device__ __forceinline__ uint32_t pack_bf16(float lo, float hi) { uint32_t d; asm("cvt.rn.bf16x2.f32 %0, %1, %2;" : "=r"(d) : "f"(hi), "f"(lo)); return d; }
__device__ __forceinline__ float ex2(float x) { float y; asm("ex2.approx.ftz.f32 %0, %1;" : "=f"(y) : "f"(x)); return y; }
__device__ __forceinline__ float rsq(float x) { float y; asm("rsqrt.approx.ftz.f32 %0, %1;" : "=f"(y) : "f"(x)); return y; }
__device__ __forceinline__ float rcp(float x) { float y; asm("rcp.approx.ftz.f32 %0, %1;" : "=f"(y) : "f"(x)); return y; }
__device__ __forceinline__ float bf_lo(uint32_t v) { return __uint_as_float(v << 16); }
__device__ __forceinline__ float bf_hi(uint32_t v) { return __uint_as_float(v & 0xffff0000u); }
__device__ __forceinline__ void stsm4(uint32_t addr, uint32_t a, uint32_t b, uint32_t c, uint32_t d) {
  asm volatile("stmatrix.sync.aligned.m8n8.x4.shared.b16 [%0], {%1, %2, %3, %4};" ::"r"(addr), "r"(a), "r"(b), "r"(c), "r"(d) : "memory");
}
__device__ __forceinline__ uint32_t movm(uint32_t a) { uint32_t d; asm volatile("movmatrix.sync.aligned.m8n8.trans.b16 %0, %1;" : "=r"(d) : "r"(a)); return d; }
__device__ __forceinline__ void mma16(float (&c)[4], uint32_t a0, uint32_t a1, uint32_t a2, uint32_t a3, uint32_t b0, uint32_t b1) {
  asm volatile("mma.sync.aligned.m16n8k16.row.col.f32.bf16.bf16.f32 {%0,%1,%2,%3}, {%4,%5,%6,%7}, {%8,%9}, {%0,%1,%2,%3};"
               : "+f"(c[0]), "+f"(c[1]), "+f"(c[2]), "+f"(c[3]) : "r"(a0), "r"(a1), "r"(a2), "r"(a3), "r"(b0), "r"(b1));
}
__device__ __forceinline__ void mma8(float (&c)[4], uint32_t a0, uint32_t a1, uint32_t b0) {
  asm volatile("mma.sync.aligned.m16n8k8.row.col.f32.bf16.bf16.f32 {%0,%1,%2,%3}, {%4,%5}, {%6}, {%0,%1,%2,%3};"
               : "+f"(c[0]), "+f"(c[1]), "+f"(c[2]), "+f"(c[3]) : "r"(a0), "r"(a1), "r"(b0));
}
__device__ __forceinline__ void sts128(uint32_t a, uint32_t x, uint32_t y, uint32_t z, uint32_t w) {
  asm volatile("st.shared.v4.b32 [%0], {%1,%2,%3,%4};" ::"r"(a), "r"(x), "r"(y), "r"(z), "r"(w) : "memory");
}
__device__ __forceinline__ float2 lds64(uint32_t a) { float2 v; asm volatile("ld.shared.v2.f32 {%0,%1}, [%2];" : "=f"(v.x), "=f"(v.y) : "r"(a)); return v; }
__device__ __forceinline__ float4 lds128(uint32_t a) { float4 v; asm volatile("ld.shared.v4.f32 {%0,%1,%2,%3}, [%4];" : "=f"(v.x), "=f"(v.y), "=f"(v.z), "=f"(v.w) : "r"(a)); return v; }
__device__ __forceinline__ uint32_t lds32(uint32_t a) { uint32_t v; asm volatile("ld.shared.b32 %0, [%1];" : "=r"(v) : "r"(a)); return v; }
constexpr uint32_t PA1 = 0x80000000u / NA + 1, G1 = 8 + (1u << 28);
constexpr uint32_t DA0 = ((SB + OFF_A) >> 4) | (1u << 16), DB0 = ((SB + OFF_B) >> 4) | (512u << 16);
template <int S> __device__ __forceinline__ uint2 wgmma_first128(float (&d)[S], uint32_t da, uint32_t& db, uint32_t h0, uint32_t h1, uint32_t one, uint32_t b0, uint32_t p0, uint32_t b1, uint32_t p1) {
  uint2 ok;
  asm volatile("{\n.reg .b64 a, b, s;\n.reg .b32 t, u;\n.reg .pred p, q;\nwgmma.fence.sync.aligned;\n"
    "mov.b32 t, %67;\n"
    "mov.b64 a, {t, %68};\nmov.b64 b, {%66, %69};\n"
    "wgmma.mma_async.sync.aligned.m64n128k16.f32.bf16.bf16 "
    "{%2, %3, %4, %5, %6, %7, %8, %9, %10, %11, %12, %13, %14, %15, %16, %17, %18, %19, %20, %21, %22, %23, %24, %25, %26, %27, %28, %29, %30, %31, %32, %33, %34, %35, %36, %37, %38, %39, %40, %41, %42, %43, %44, %45, %46, %47, %48, %49, %50, %51, %52, %53, %54, %55, %56, %57, %58, %59, %60, %61, %62, %63, %64, %65}, "
    "a, b, 0, 1, 1, 0, 1;\n"
    "mad.lo.u32 t, %70, 2, t;\nmad.lo.u32 %66, %70, 128, %66;\n"
    "mov.b64 a, {t, %68};\nmov.b64 b, {%66, %69};\n"
    "wgmma.mma_async.sync.aligned.m64n128k16.f32.bf16.bf16 "
    "{%2, %3, %4, %5, %6, %7, %8, %9, %10, %11, %12, %13, %14, %15, %16, %17, %18, %19, %20, %21, %22, %23, %24, %25, %26, %27, %28, %29, %30, %31, %32, %33, %34, %35, %36, %37, %38, %39, %40, %41, %42, %43, %44, %45, %46, %47, %48, %49, %50, %51, %52, %53, %54, %55, %56, %57, %58, %59, %60, %61, %62, %63, %64, %65}, "
    "a, b, 1, 1, 1, 0, 1;\n"
    "mad.lo.u32 t, %70, 2, t;\nmad.lo.u32 %66, %70, 128, %66;\n"
    "mov.b64 a, {t, %68};\nmov.b64 b, {%66, %69};\n"
    "wgmma.mma_async.sync.aligned.m64n128k16.f32.bf16.bf16 "
    "{%2, %3, %4, %5, %6, %7, %8, %9, %10, %11, %12, %13, %14, %15, %16, %17, %18, %19, %20, %21, %22, %23, %24, %25, %26, %27, %28, %29, %30, %31, %32, %33, %34, %35, %36, %37, %38, %39, %40, %41, %42, %43, %44, %45, %46, %47, %48, %49, %50, %51, %52, %53, %54, %55, %56, %57, %58, %59, %60, %61, %62, %63, %64, %65}, "
    "a, b, 1, 1, 1, 0, 1;\n"
    "mov.b64 s, {%72, %72};\nmbarrier.test_wait.shared::cta.b64 p, [%71], s;\nmov.b64 s, {%74, %74};\nmbarrier.test_wait.shared::cta.b64 q, [%73], s;\n"
    "mad.lo.u32 t, %70, 2, t;\nmad.lo.u32 %66, %70, 128, %66;\n"
    "mov.b64 a, {t, %68};\nmov.b64 b, {%66, %69};\n"
    "wgmma.mma_async.sync.aligned.m64n128k16.f32.bf16.bf16 "
    "{%2, %3, %4, %5, %6, %7, %8, %9, %10, %11, %12, %13, %14, %15, %16, %17, %18, %19, %20, %21, %22, %23, %24, %25, %26, %27, %28, %29, %30, %31, %32, %33, %34, %35, %36, %37, %38, %39, %40, %41, %42, %43, %44, %45, %46, %47, %48, %49, %50, %51, %52, %53, %54, %55, %56, %57, %58, %59, %60, %61, %62, %63, %64, %65}, "
    "a, b, 1, 1, 1, 0, 1;\n"
    "wgmma.commit_group.sync.aligned;\nselp.u32 %0, 1, 0, p;\nselp.u32 %1, 1, 0, q;\n}"
    : "=r"(ok.x), "=r"(ok.y), "=f"(d[0]), "=f"(d[1]), "=f"(d[2]), "=f"(d[3]), "=f"(d[4]), "=f"(d[5]), "=f"(d[6]), "=f"(d[7]), "=f"(d[8]), "=f"(d[9]), "=f"(d[10]), "=f"(d[11]), "=f"(d[12]), "=f"(d[13]), "=f"(d[14]), "=f"(d[15]), "=f"(d[16]), "=f"(d[17]), "=f"(d[18]), "=f"(d[19]), "=f"(d[20]), "=f"(d[21]), "=f"(d[22]), "=f"(d[23]), "=f"(d[24]), "=f"(d[25]), "=f"(d[26]), "=f"(d[27]), "=f"(d[28]), "=f"(d[29]), "=f"(d[30]), "=f"(d[31]), "=f"(d[32]), "=f"(d[33]), "=f"(d[34]), "=f"(d[35]), "=f"(d[36]), "=f"(d[37]), "=f"(d[38]), "=f"(d[39]), "=f"(d[40]), "=f"(d[41]), "=f"(d[42]), "=f"(d[43]), "=f"(d[44]), "=f"(d[45]), "=f"(d[46]), "=f"(d[47]), "=f"(d[48]), "=f"(d[49]), "=f"(d[50]), "=f"(d[51]), "=f"(d[52]), "=f"(d[53]), "=f"(d[54]), "=f"(d[55]), "=f"(d[56]), "=f"(d[57]), "=f"(d[58]), "=f"(d[59]), "=f"(d[60]), "=f"(d[61]), "=f"(d[62]), "=f"(d[63]), "+r"(db)
    : "r"(da), "r"(h0), "r"(h1), "r"(one), "r"(b0), "r"(p0), "r"(b1), "r"(p1) : "memory");
  return ok;
}
template <int S> __device__ __forceinline__ uint2 wgmma_step128(float (&d)[S], uint32_t da, uint32_t& db, uint32_t h0, uint32_t h1, uint32_t one, uint32_t b0, uint32_t p0, uint32_t b1, uint32_t p1) {
  uint2 ok;
  asm volatile("{\n.reg .b64 a, b, s;\n.reg .b32 t, u;\n.reg .pred p, q;\nwgmma.fence.sync.aligned;\n"
    "mov.b32 t, %67;\n"
    "mov.b64 a, {t, %68};\nmov.b64 b, {%66, %69};\n"
    "wgmma.mma_async.sync.aligned.m64n128k16.f32.bf16.bf16 "
    "{%2, %3, %4, %5, %6, %7, %8, %9, %10, %11, %12, %13, %14, %15, %16, %17, %18, %19, %20, %21, %22, %23, %24, %25, %26, %27, %28, %29, %30, %31, %32, %33, %34, %35, %36, %37, %38, %39, %40, %41, %42, %43, %44, %45, %46, %47, %48, %49, %50, %51, %52, %53, %54, %55, %56, %57, %58, %59, %60, %61, %62, %63, %64, %65}, "
    "a, b, 1, 1, 1, 0, 1;\n"
    "mad.lo.u32 t, %70, 2, t;\nmad.lo.u32 %66, %70, 128, %66;\n"
    "mov.b64 a, {t, %68};\nmov.b64 b, {%66, %69};\n"
    "wgmma.mma_async.sync.aligned.m64n128k16.f32.bf16.bf16 "
    "{%2, %3, %4, %5, %6, %7, %8, %9, %10, %11, %12, %13, %14, %15, %16, %17, %18, %19, %20, %21, %22, %23, %24, %25, %26, %27, %28, %29, %30, %31, %32, %33, %34, %35, %36, %37, %38, %39, %40, %41, %42, %43, %44, %45, %46, %47, %48, %49, %50, %51, %52, %53, %54, %55, %56, %57, %58, %59, %60, %61, %62, %63, %64, %65}, "
    "a, b, 1, 1, 1, 0, 1;\n"
    "mad.lo.u32 t, %70, 2, t;\nmad.lo.u32 %66, %70, 128, %66;\n"
    "mov.b64 a, {t, %68};\nmov.b64 b, {%66, %69};\n"
    "wgmma.mma_async.sync.aligned.m64n128k16.f32.bf16.bf16 "
    "{%2, %3, %4, %5, %6, %7, %8, %9, %10, %11, %12, %13, %14, %15, %16, %17, %18, %19, %20, %21, %22, %23, %24, %25, %26, %27, %28, %29, %30, %31, %32, %33, %34, %35, %36, %37, %38, %39, %40, %41, %42, %43, %44, %45, %46, %47, %48, %49, %50, %51, %52, %53, %54, %55, %56, %57, %58, %59, %60, %61, %62, %63, %64, %65}, "
    "a, b, 1, 1, 1, 0, 1;\n"
    "mov.b64 s, {%72, %72};\nmbarrier.test_wait.shared::cta.b64 p, [%71], s;\nmov.b64 s, {%74, %74};\nmbarrier.test_wait.shared::cta.b64 q, [%73], s;\n"
    "mad.lo.u32 t, %70, 2, t;\nmad.lo.u32 %66, %70, 128, %66;\n"
    "mov.b64 a, {t, %68};\nmov.b64 b, {%66, %69};\n"
    "wgmma.mma_async.sync.aligned.m64n128k16.f32.bf16.bf16 "
    "{%2, %3, %4, %5, %6, %7, %8, %9, %10, %11, %12, %13, %14, %15, %16, %17, %18, %19, %20, %21, %22, %23, %24, %25, %26, %27, %28, %29, %30, %31, %32, %33, %34, %35, %36, %37, %38, %39, %40, %41, %42, %43, %44, %45, %46, %47, %48, %49, %50, %51, %52, %53, %54, %55, %56, %57, %58, %59, %60, %61, %62, %63, %64, %65}, "
    "a, b, 1, 1, 1, 0, 1;\n"
    "wgmma.commit_group.sync.aligned;\nselp.u32 %0, 1, 0, p;\nselp.u32 %1, 1, 0, q;\n}"
    : "=r"(ok.x), "=r"(ok.y), "+f"(d[0]), "+f"(d[1]), "+f"(d[2]), "+f"(d[3]), "+f"(d[4]), "+f"(d[5]), "+f"(d[6]), "+f"(d[7]), "+f"(d[8]), "+f"(d[9]), "+f"(d[10]), "+f"(d[11]), "+f"(d[12]), "+f"(d[13]), "+f"(d[14]), "+f"(d[15]), "+f"(d[16]), "+f"(d[17]), "+f"(d[18]), "+f"(d[19]), "+f"(d[20]), "+f"(d[21]), "+f"(d[22]), "+f"(d[23]), "+f"(d[24]), "+f"(d[25]), "+f"(d[26]), "+f"(d[27]), "+f"(d[28]), "+f"(d[29]), "+f"(d[30]), "+f"(d[31]), "+f"(d[32]), "+f"(d[33]), "+f"(d[34]), "+f"(d[35]), "+f"(d[36]), "+f"(d[37]), "+f"(d[38]), "+f"(d[39]), "+f"(d[40]), "+f"(d[41]), "+f"(d[42]), "+f"(d[43]), "+f"(d[44]), "+f"(d[45]), "+f"(d[46]), "+f"(d[47]), "+f"(d[48]), "+f"(d[49]), "+f"(d[50]), "+f"(d[51]), "+f"(d[52]), "+f"(d[53]), "+f"(d[54]), "+f"(d[55]), "+f"(d[56]), "+f"(d[57]), "+f"(d[58]), "+f"(d[59]), "+f"(d[60]), "+f"(d[61]), "+f"(d[62]), "+f"(d[63]), "+r"(db)
    : "r"(da), "r"(h0), "r"(h1), "r"(one), "r"(b0), "r"(p0), "r"(b1), "r"(p1) : "memory");
  return ok;
}
template <int S> __device__ __forceinline__ uint2 wgmma_first192(float (&d)[S], uint32_t da, uint32_t& db, uint32_t h0, uint32_t h1, uint32_t one, uint32_t b0, uint32_t p0, uint32_t b1, uint32_t p1) {
  uint2 ok;
  asm volatile("{\n.reg .b64 a, b, s;\n.reg .b32 t, u;\n.reg .pred p, q;\nwgmma.fence.sync.aligned;\n"
    "mov.b32 t, %99;\n"
    "mov.b64 a, {t, %100};\nmov.b64 b, {%98, %101};\n"
    "wgmma.mma_async.sync.aligned.m64n192k16.f32.bf16.bf16 "
    "{%2, %3, %4, %5, %6, %7, %8, %9, %10, %11, %12, %13, %14, %15, %16, %17, %18, %19, %20, %21, %22, %23, %24, %25, %26, %27, %28, %29, %30, %31, %32, %33, %34, %35, %36, %37, %38, %39, %40, %41, %42, %43, %44, %45, %46, %47, %48, %49, %50, %51, %52, %53, %54, %55, %56, %57, %58, %59, %60, %61, %62, %63, %64, %65, %66, %67, %68, %69, %70, %71, %72, %73, %74, %75, %76, %77, %78, %79, %80, %81, %82, %83, %84, %85, %86, %87, %88, %89, %90, %91, %92, %93, %94, %95, %96, %97}, "
    "a, b, 0, 1, 1, 0, 1;\n"
    "mad.lo.u32 t, %102, 2, t;\nmad.lo.u32 %98, %102, 128, %98;\n"
    "mov.b64 a, {t, %100};\nmov.b64 b, {%98, %101};\n"
    "wgmma.mma_async.sync.aligned.m64n192k16.f32.bf16.bf16 "
    "{%2, %3, %4, %5, %6, %7, %8, %9, %10, %11, %12, %13, %14, %15, %16, %17, %18, %19, %20, %21, %22, %23, %24, %25, %26, %27, %28, %29, %30, %31, %32, %33, %34, %35, %36, %37, %38, %39, %40, %41, %42, %43, %44, %45, %46, %47, %48, %49, %50, %51, %52, %53, %54, %55, %56, %57, %58, %59, %60, %61, %62, %63, %64, %65, %66, %67, %68, %69, %70, %71, %72, %73, %74, %75, %76, %77, %78, %79, %80, %81, %82, %83, %84, %85, %86, %87, %88, %89, %90, %91, %92, %93, %94, %95, %96, %97}, "
    "a, b, 1, 1, 1, 0, 1;\n"
    "mad.lo.u32 t, %102, 2, t;\nmad.lo.u32 %98, %102, 128, %98;\n"
    "mov.b64 a, {t, %100};\nmov.b64 b, {%98, %101};\n"
    "wgmma.mma_async.sync.aligned.m64n192k16.f32.bf16.bf16 "
    "{%2, %3, %4, %5, %6, %7, %8, %9, %10, %11, %12, %13, %14, %15, %16, %17, %18, %19, %20, %21, %22, %23, %24, %25, %26, %27, %28, %29, %30, %31, %32, %33, %34, %35, %36, %37, %38, %39, %40, %41, %42, %43, %44, %45, %46, %47, %48, %49, %50, %51, %52, %53, %54, %55, %56, %57, %58, %59, %60, %61, %62, %63, %64, %65, %66, %67, %68, %69, %70, %71, %72, %73, %74, %75, %76, %77, %78, %79, %80, %81, %82, %83, %84, %85, %86, %87, %88, %89, %90, %91, %92, %93, %94, %95, %96, %97}, "
    "a, b, 1, 1, 1, 0, 1;\n"
    "mov.b64 s, {%104, %104};\nmbarrier.test_wait.shared::cta.b64 p, [%103], s;\nmov.b64 s, {%106, %106};\nmbarrier.test_wait.shared::cta.b64 q, [%105], s;\n"
    "mad.lo.u32 t, %102, 2, t;\nmad.lo.u32 %98, %102, 128, %98;\n"
    "mov.b64 a, {t, %100};\nmov.b64 b, {%98, %101};\n"
    "wgmma.mma_async.sync.aligned.m64n192k16.f32.bf16.bf16 "
    "{%2, %3, %4, %5, %6, %7, %8, %9, %10, %11, %12, %13, %14, %15, %16, %17, %18, %19, %20, %21, %22, %23, %24, %25, %26, %27, %28, %29, %30, %31, %32, %33, %34, %35, %36, %37, %38, %39, %40, %41, %42, %43, %44, %45, %46, %47, %48, %49, %50, %51, %52, %53, %54, %55, %56, %57, %58, %59, %60, %61, %62, %63, %64, %65, %66, %67, %68, %69, %70, %71, %72, %73, %74, %75, %76, %77, %78, %79, %80, %81, %82, %83, %84, %85, %86, %87, %88, %89, %90, %91, %92, %93, %94, %95, %96, %97}, "
    "a, b, 1, 1, 1, 0, 1;\n"
    "wgmma.commit_group.sync.aligned;\nselp.u32 %0, 1, 0, p;\nselp.u32 %1, 1, 0, q;\n}"
    : "=r"(ok.x), "=r"(ok.y), "=f"(d[0]), "=f"(d[1]), "=f"(d[2]), "=f"(d[3]), "=f"(d[4]), "=f"(d[5]), "=f"(d[6]), "=f"(d[7]), "=f"(d[8]), "=f"(d[9]), "=f"(d[10]), "=f"(d[11]), "=f"(d[12]), "=f"(d[13]), "=f"(d[14]), "=f"(d[15]), "=f"(d[16]), "=f"(d[17]), "=f"(d[18]), "=f"(d[19]), "=f"(d[20]), "=f"(d[21]), "=f"(d[22]), "=f"(d[23]), "=f"(d[24]), "=f"(d[25]), "=f"(d[26]), "=f"(d[27]), "=f"(d[28]), "=f"(d[29]), "=f"(d[30]), "=f"(d[31]), "=f"(d[32]), "=f"(d[33]), "=f"(d[34]), "=f"(d[35]), "=f"(d[36]), "=f"(d[37]), "=f"(d[38]), "=f"(d[39]), "=f"(d[40]), "=f"(d[41]), "=f"(d[42]), "=f"(d[43]), "=f"(d[44]), "=f"(d[45]), "=f"(d[46]), "=f"(d[47]), "=f"(d[48]), "=f"(d[49]), "=f"(d[50]), "=f"(d[51]), "=f"(d[52]), "=f"(d[53]), "=f"(d[54]), "=f"(d[55]), "=f"(d[56]), "=f"(d[57]), "=f"(d[58]), "=f"(d[59]), "=f"(d[60]), "=f"(d[61]), "=f"(d[62]), "=f"(d[63]), "=f"(d[64]), "=f"(d[65]), "=f"(d[66]), "=f"(d[67]), "=f"(d[68]), "=f"(d[69]), "=f"(d[70]), "=f"(d[71]), "=f"(d[72]), "=f"(d[73]), "=f"(d[74]), "=f"(d[75]), "=f"(d[76]), "=f"(d[77]), "=f"(d[78]), "=f"(d[79]), "=f"(d[80]), "=f"(d[81]), "=f"(d[82]), "=f"(d[83]), "=f"(d[84]), "=f"(d[85]), "=f"(d[86]), "=f"(d[87]), "=f"(d[88]), "=f"(d[89]), "=f"(d[90]), "=f"(d[91]), "=f"(d[92]), "=f"(d[93]), "=f"(d[94]), "=f"(d[95]), "+r"(db)
    : "r"(da), "r"(h0), "r"(h1), "r"(one), "r"(b0), "r"(p0), "r"(b1), "r"(p1) : "memory");
  return ok;
}
template <int S> __device__ __forceinline__ uint2 wgmma_step192(float (&d)[S], uint32_t da, uint32_t& db, uint32_t h0, uint32_t h1, uint32_t one, uint32_t b0, uint32_t p0, uint32_t b1, uint32_t p1) {
  uint2 ok;
  asm volatile("{\n.reg .b64 a, b, s;\n.reg .b32 t, u;\n.reg .pred p, q;\nwgmma.fence.sync.aligned;\n"
    "mov.b32 t, %99;\n"
    "mov.b64 a, {t, %100};\nmov.b64 b, {%98, %101};\n"
    "wgmma.mma_async.sync.aligned.m64n192k16.f32.bf16.bf16 "
    "{%2, %3, %4, %5, %6, %7, %8, %9, %10, %11, %12, %13, %14, %15, %16, %17, %18, %19, %20, %21, %22, %23, %24, %25, %26, %27, %28, %29, %30, %31, %32, %33, %34, %35, %36, %37, %38, %39, %40, %41, %42, %43, %44, %45, %46, %47, %48, %49, %50, %51, %52, %53, %54, %55, %56, %57, %58, %59, %60, %61, %62, %63, %64, %65, %66, %67, %68, %69, %70, %71, %72, %73, %74, %75, %76, %77, %78, %79, %80, %81, %82, %83, %84, %85, %86, %87, %88, %89, %90, %91, %92, %93, %94, %95, %96, %97}, "
    "a, b, 1, 1, 1, 0, 1;\n"
    "mad.lo.u32 t, %102, 2, t;\nmad.lo.u32 %98, %102, 128, %98;\n"
    "mov.b64 a, {t, %100};\nmov.b64 b, {%98, %101};\n"
    "wgmma.mma_async.sync.aligned.m64n192k16.f32.bf16.bf16 "
    "{%2, %3, %4, %5, %6, %7, %8, %9, %10, %11, %12, %13, %14, %15, %16, %17, %18, %19, %20, %21, %22, %23, %24, %25, %26, %27, %28, %29, %30, %31, %32, %33, %34, %35, %36, %37, %38, %39, %40, %41, %42, %43, %44, %45, %46, %47, %48, %49, %50, %51, %52, %53, %54, %55, %56, %57, %58, %59, %60, %61, %62, %63, %64, %65, %66, %67, %68, %69, %70, %71, %72, %73, %74, %75, %76, %77, %78, %79, %80, %81, %82, %83, %84, %85, %86, %87, %88, %89, %90, %91, %92, %93, %94, %95, %96, %97}, "
    "a, b, 1, 1, 1, 0, 1;\n"
    "mad.lo.u32 t, %102, 2, t;\nmad.lo.u32 %98, %102, 128, %98;\n"
    "mov.b64 a, {t, %100};\nmov.b64 b, {%98, %101};\n"
    "wgmma.mma_async.sync.aligned.m64n192k16.f32.bf16.bf16 "
    "{%2, %3, %4, %5, %6, %7, %8, %9, %10, %11, %12, %13, %14, %15, %16, %17, %18, %19, %20, %21, %22, %23, %24, %25, %26, %27, %28, %29, %30, %31, %32, %33, %34, %35, %36, %37, %38, %39, %40, %41, %42, %43, %44, %45, %46, %47, %48, %49, %50, %51, %52, %53, %54, %55, %56, %57, %58, %59, %60, %61, %62, %63, %64, %65, %66, %67, %68, %69, %70, %71, %72, %73, %74, %75, %76, %77, %78, %79, %80, %81, %82, %83, %84, %85, %86, %87, %88, %89, %90, %91, %92, %93, %94, %95, %96, %97}, "
    "a, b, 1, 1, 1, 0, 1;\n"
    "mov.b64 s, {%104, %104};\nmbarrier.test_wait.shared::cta.b64 p, [%103], s;\nmov.b64 s, {%106, %106};\nmbarrier.test_wait.shared::cta.b64 q, [%105], s;\n"
    "mad.lo.u32 t, %102, 2, t;\nmad.lo.u32 %98, %102, 128, %98;\n"
    "mov.b64 a, {t, %100};\nmov.b64 b, {%98, %101};\n"
    "wgmma.mma_async.sync.aligned.m64n192k16.f32.bf16.bf16 "
    "{%2, %3, %4, %5, %6, %7, %8, %9, %10, %11, %12, %13, %14, %15, %16, %17, %18, %19, %20, %21, %22, %23, %24, %25, %26, %27, %28, %29, %30, %31, %32, %33, %34, %35, %36, %37, %38, %39, %40, %41, %42, %43, %44, %45, %46, %47, %48, %49, %50, %51, %52, %53, %54, %55, %56, %57, %58, %59, %60, %61, %62, %63, %64, %65, %66, %67, %68, %69, %70, %71, %72, %73, %74, %75, %76, %77, %78, %79, %80, %81, %82, %83, %84, %85, %86, %87, %88, %89, %90, %91, %92, %93, %94, %95, %96, %97}, "
    "a, b, 1, 1, 1, 0, 1;\n"
    "wgmma.commit_group.sync.aligned;\nselp.u32 %0, 1, 0, p;\nselp.u32 %1, 1, 0, q;\n}"
    : "=r"(ok.x), "=r"(ok.y), "+f"(d[0]), "+f"(d[1]), "+f"(d[2]), "+f"(d[3]), "+f"(d[4]), "+f"(d[5]), "+f"(d[6]), "+f"(d[7]), "+f"(d[8]), "+f"(d[9]), "+f"(d[10]), "+f"(d[11]), "+f"(d[12]), "+f"(d[13]), "+f"(d[14]), "+f"(d[15]), "+f"(d[16]), "+f"(d[17]), "+f"(d[18]), "+f"(d[19]), "+f"(d[20]), "+f"(d[21]), "+f"(d[22]), "+f"(d[23]), "+f"(d[24]), "+f"(d[25]), "+f"(d[26]), "+f"(d[27]), "+f"(d[28]), "+f"(d[29]), "+f"(d[30]), "+f"(d[31]), "+f"(d[32]), "+f"(d[33]), "+f"(d[34]), "+f"(d[35]), "+f"(d[36]), "+f"(d[37]), "+f"(d[38]), "+f"(d[39]), "+f"(d[40]), "+f"(d[41]), "+f"(d[42]), "+f"(d[43]), "+f"(d[44]), "+f"(d[45]), "+f"(d[46]), "+f"(d[47]), "+f"(d[48]), "+f"(d[49]), "+f"(d[50]), "+f"(d[51]), "+f"(d[52]), "+f"(d[53]), "+f"(d[54]), "+f"(d[55]), "+f"(d[56]), "+f"(d[57]), "+f"(d[58]), "+f"(d[59]), "+f"(d[60]), "+f"(d[61]), "+f"(d[62]), "+f"(d[63]), "+f"(d[64]), "+f"(d[65]), "+f"(d[66]), "+f"(d[67]), "+f"(d[68]), "+f"(d[69]), "+f"(d[70]), "+f"(d[71]), "+f"(d[72]), "+f"(d[73]), "+f"(d[74]), "+f"(d[75]), "+f"(d[76]), "+f"(d[77]), "+f"(d[78]), "+f"(d[79]), "+f"(d[80]), "+f"(d[81]), "+f"(d[82]), "+f"(d[83]), "+f"(d[84]), "+f"(d[85]), "+f"(d[86]), "+f"(d[87]), "+f"(d[88]), "+f"(d[89]), "+f"(d[90]), "+f"(d[91]), "+f"(d[92]), "+f"(d[93]), "+f"(d[94]), "+f"(d[95]), "+r"(db)
    : "r"(da), "r"(h0), "r"(h1), "r"(one), "r"(b0), "r"(p0), "r"(b1), "r"(p1) : "memory");
  return ok;
}
template <int S> __device__ __forceinline__ uint2 wgmma_first256(float (&d)[S], uint32_t da, uint32_t& db, uint32_t h0, uint32_t h1, uint32_t one, uint32_t b0, uint32_t p0, uint32_t b1, uint32_t p1) {
  uint2 ok;
  asm volatile("{\n.reg .b64 a, b, s;\n.reg .b32 t, u;\n.reg .pred p, q;\nwgmma.fence.sync.aligned;\n"
    "mov.b32 t, %131;\n"
    "mov.b64 a, {t, %132};\nmov.b64 b, {%130, %133};\n"
    "wgmma.mma_async.sync.aligned.m64n256k16.f32.bf16.bf16 "
    "{%2, %3, %4, %5, %6, %7, %8, %9, %10, %11, %12, %13, %14, %15, %16, %17, %18, %19, %20, %21, %22, %23, %24, %25, %26, %27, %28, %29, %30, %31, %32, %33, %34, %35, %36, %37, %38, %39, %40, %41, %42, %43, %44, %45, %46, %47, %48, %49, %50, %51, %52, %53, %54, %55, %56, %57, %58, %59, %60, %61, %62, %63, %64, %65, %66, %67, %68, %69, %70, %71, %72, %73, %74, %75, %76, %77, %78, %79, %80, %81, %82, %83, %84, %85, %86, %87, %88, %89, %90, %91, %92, %93, %94, %95, %96, %97, %98, %99, %100, %101, %102, %103, %104, %105, %106, %107, %108, %109, %110, %111, %112, %113, %114, %115, %116, %117, %118, %119, %120, %121, %122, %123, %124, %125, %126, %127, %128, %129}, "
    "a, b, 0, 1, 1, 0, 1;\n"
    "mad.lo.u32 t, %134, 2, t;\nmad.lo.u32 %130, %134, 128, %130;\n"
    "mov.b64 a, {t, %132};\nmov.b64 b, {%130, %133};\n"
    "wgmma.mma_async.sync.aligned.m64n256k16.f32.bf16.bf16 "
    "{%2, %3, %4, %5, %6, %7, %8, %9, %10, %11, %12, %13, %14, %15, %16, %17, %18, %19, %20, %21, %22, %23, %24, %25, %26, %27, %28, %29, %30, %31, %32, %33, %34, %35, %36, %37, %38, %39, %40, %41, %42, %43, %44, %45, %46, %47, %48, %49, %50, %51, %52, %53, %54, %55, %56, %57, %58, %59, %60, %61, %62, %63, %64, %65, %66, %67, %68, %69, %70, %71, %72, %73, %74, %75, %76, %77, %78, %79, %80, %81, %82, %83, %84, %85, %86, %87, %88, %89, %90, %91, %92, %93, %94, %95, %96, %97, %98, %99, %100, %101, %102, %103, %104, %105, %106, %107, %108, %109, %110, %111, %112, %113, %114, %115, %116, %117, %118, %119, %120, %121, %122, %123, %124, %125, %126, %127, %128, %129}, "
    "a, b, 1, 1, 1, 0, 1;\n"
    "mov.b64 s, {%136, %136};\nmbarrier.test_wait.shared::cta.b64 p, [%135], s;\nmov.b64 s, {%138, %138};\nmbarrier.test_wait.shared::cta.b64 q, [%137], s;\n"
    "mad.lo.u32 t, %134, 2, t;\nmad.lo.u32 %130, %134, 128, %130;\n"
    "mov.b64 a, {t, %132};\nmov.b64 b, {%130, %133};\n"
    "wgmma.mma_async.sync.aligned.m64n256k16.f32.bf16.bf16 "
    "{%2, %3, %4, %5, %6, %7, %8, %9, %10, %11, %12, %13, %14, %15, %16, %17, %18, %19, %20, %21, %22, %23, %24, %25, %26, %27, %28, %29, %30, %31, %32, %33, %34, %35, %36, %37, %38, %39, %40, %41, %42, %43, %44, %45, %46, %47, %48, %49, %50, %51, %52, %53, %54, %55, %56, %57, %58, %59, %60, %61, %62, %63, %64, %65, %66, %67, %68, %69, %70, %71, %72, %73, %74, %75, %76, %77, %78, %79, %80, %81, %82, %83, %84, %85, %86, %87, %88, %89, %90, %91, %92, %93, %94, %95, %96, %97, %98, %99, %100, %101, %102, %103, %104, %105, %106, %107, %108, %109, %110, %111, %112, %113, %114, %115, %116, %117, %118, %119, %120, %121, %122, %123, %124, %125, %126, %127, %128, %129}, "
    "a, b, 1, 1, 1, 0, 1;\n"
    "mad.lo.u32 t, %134, 2, t;\nmad.lo.u32 %130, %134, 128, %130;\n"
    "mov.b64 a, {t, %132};\nmov.b64 b, {%130, %133};\n"
    "wgmma.mma_async.sync.aligned.m64n256k16.f32.bf16.bf16 "
    "{%2, %3, %4, %5, %6, %7, %8, %9, %10, %11, %12, %13, %14, %15, %16, %17, %18, %19, %20, %21, %22, %23, %24, %25, %26, %27, %28, %29, %30, %31, %32, %33, %34, %35, %36, %37, %38, %39, %40, %41, %42, %43, %44, %45, %46, %47, %48, %49, %50, %51, %52, %53, %54, %55, %56, %57, %58, %59, %60, %61, %62, %63, %64, %65, %66, %67, %68, %69, %70, %71, %72, %73, %74, %75, %76, %77, %78, %79, %80, %81, %82, %83, %84, %85, %86, %87, %88, %89, %90, %91, %92, %93, %94, %95, %96, %97, %98, %99, %100, %101, %102, %103, %104, %105, %106, %107, %108, %109, %110, %111, %112, %113, %114, %115, %116, %117, %118, %119, %120, %121, %122, %123, %124, %125, %126, %127, %128, %129}, "
    "a, b, 1, 1, 1, 0, 1;\n"
    "wgmma.commit_group.sync.aligned;\nselp.u32 %0, 1, 0, p;\nselp.u32 %1, 1, 0, q;\n}"
    : "=r"(ok.x), "=r"(ok.y), "=f"(d[0]), "=f"(d[1]), "=f"(d[2]), "=f"(d[3]), "=f"(d[4]), "=f"(d[5]), "=f"(d[6]), "=f"(d[7]), "=f"(d[8]), "=f"(d[9]), "=f"(d[10]), "=f"(d[11]), "=f"(d[12]), "=f"(d[13]), "=f"(d[14]), "=f"(d[15]), "=f"(d[16]), "=f"(d[17]), "=f"(d[18]), "=f"(d[19]), "=f"(d[20]), "=f"(d[21]), "=f"(d[22]), "=f"(d[23]), "=f"(d[24]), "=f"(d[25]), "=f"(d[26]), "=f"(d[27]), "=f"(d[28]), "=f"(d[29]), "=f"(d[30]), "=f"(d[31]), "=f"(d[32]), "=f"(d[33]), "=f"(d[34]), "=f"(d[35]), "=f"(d[36]), "=f"(d[37]), "=f"(d[38]), "=f"(d[39]), "=f"(d[40]), "=f"(d[41]), "=f"(d[42]), "=f"(d[43]), "=f"(d[44]), "=f"(d[45]), "=f"(d[46]), "=f"(d[47]), "=f"(d[48]), "=f"(d[49]), "=f"(d[50]), "=f"(d[51]), "=f"(d[52]), "=f"(d[53]), "=f"(d[54]), "=f"(d[55]), "=f"(d[56]), "=f"(d[57]), "=f"(d[58]), "=f"(d[59]), "=f"(d[60]), "=f"(d[61]), "=f"(d[62]), "=f"(d[63]), "=f"(d[64]), "=f"(d[65]), "=f"(d[66]), "=f"(d[67]), "=f"(d[68]), "=f"(d[69]), "=f"(d[70]), "=f"(d[71]), "=f"(d[72]), "=f"(d[73]), "=f"(d[74]), "=f"(d[75]), "=f"(d[76]), "=f"(d[77]), "=f"(d[78]), "=f"(d[79]), "=f"(d[80]), "=f"(d[81]), "=f"(d[82]), "=f"(d[83]), "=f"(d[84]), "=f"(d[85]), "=f"(d[86]), "=f"(d[87]), "=f"(d[88]), "=f"(d[89]), "=f"(d[90]), "=f"(d[91]), "=f"(d[92]), "=f"(d[93]), "=f"(d[94]), "=f"(d[95]), "=f"(d[96]), "=f"(d[97]), "=f"(d[98]), "=f"(d[99]), "=f"(d[100]), "=f"(d[101]), "=f"(d[102]), "=f"(d[103]), "=f"(d[104]), "=f"(d[105]), "=f"(d[106]), "=f"(d[107]), "=f"(d[108]), "=f"(d[109]), "=f"(d[110]), "=f"(d[111]), "=f"(d[112]), "=f"(d[113]), "=f"(d[114]), "=f"(d[115]), "=f"(d[116]), "=f"(d[117]), "=f"(d[118]), "=f"(d[119]), "=f"(d[120]), "=f"(d[121]), "=f"(d[122]), "=f"(d[123]), "=f"(d[124]), "=f"(d[125]), "=f"(d[126]), "=f"(d[127]), "+r"(db)
    : "r"(da), "r"(h0), "r"(h1), "r"(one), "r"(b0), "r"(p0), "r"(b1), "r"(p1) : "memory");
  return ok;
}
template <int S> __device__ __forceinline__ uint2 wgmma_step256(float (&d)[S], uint32_t da, uint32_t& db, uint32_t h0, uint32_t h1, uint32_t one, uint32_t b0, uint32_t p0, uint32_t b1, uint32_t p1) {
  uint2 ok;
  asm volatile("{\n.reg .b64 a, b, s;\n.reg .b32 t, u;\n.reg .pred p, q;\nwgmma.fence.sync.aligned;\n"
    "mov.b32 t, %131;\n"
    "mov.b64 a, {t, %132};\nmov.b64 b, {%130, %133};\n"
    "wgmma.mma_async.sync.aligned.m64n256k16.f32.bf16.bf16 "
    "{%2, %3, %4, %5, %6, %7, %8, %9, %10, %11, %12, %13, %14, %15, %16, %17, %18, %19, %20, %21, %22, %23, %24, %25, %26, %27, %28, %29, %30, %31, %32, %33, %34, %35, %36, %37, %38, %39, %40, %41, %42, %43, %44, %45, %46, %47, %48, %49, %50, %51, %52, %53, %54, %55, %56, %57, %58, %59, %60, %61, %62, %63, %64, %65, %66, %67, %68, %69, %70, %71, %72, %73, %74, %75, %76, %77, %78, %79, %80, %81, %82, %83, %84, %85, %86, %87, %88, %89, %90, %91, %92, %93, %94, %95, %96, %97, %98, %99, %100, %101, %102, %103, %104, %105, %106, %107, %108, %109, %110, %111, %112, %113, %114, %115, %116, %117, %118, %119, %120, %121, %122, %123, %124, %125, %126, %127, %128, %129}, "
    "a, b, 1, 1, 1, 0, 1;\n"
    "mad.lo.u32 t, %134, 2, t;\nmad.lo.u32 %130, %134, 128, %130;\n"
    "mov.b64 a, {t, %132};\nmov.b64 b, {%130, %133};\n"
    "wgmma.mma_async.sync.aligned.m64n256k16.f32.bf16.bf16 "
    "{%2, %3, %4, %5, %6, %7, %8, %9, %10, %11, %12, %13, %14, %15, %16, %17, %18, %19, %20, %21, %22, %23, %24, %25, %26, %27, %28, %29, %30, %31, %32, %33, %34, %35, %36, %37, %38, %39, %40, %41, %42, %43, %44, %45, %46, %47, %48, %49, %50, %51, %52, %53, %54, %55, %56, %57, %58, %59, %60, %61, %62, %63, %64, %65, %66, %67, %68, %69, %70, %71, %72, %73, %74, %75, %76, %77, %78, %79, %80, %81, %82, %83, %84, %85, %86, %87, %88, %89, %90, %91, %92, %93, %94, %95, %96, %97, %98, %99, %100, %101, %102, %103, %104, %105, %106, %107, %108, %109, %110, %111, %112, %113, %114, %115, %116, %117, %118, %119, %120, %121, %122, %123, %124, %125, %126, %127, %128, %129}, "
    "a, b, 1, 1, 1, 0, 1;\n"
    "mov.b64 s, {%136, %136};\nmbarrier.test_wait.shared::cta.b64 p, [%135], s;\nmov.b64 s, {%138, %138};\nmbarrier.test_wait.shared::cta.b64 q, [%137], s;\n"
    "mad.lo.u32 t, %134, 2, t;\nmad.lo.u32 %130, %134, 128, %130;\n"
    "mov.b64 a, {t, %132};\nmov.b64 b, {%130, %133};\n"
    "wgmma.mma_async.sync.aligned.m64n256k16.f32.bf16.bf16 "
    "{%2, %3, %4, %5, %6, %7, %8, %9, %10, %11, %12, %13, %14, %15, %16, %17, %18, %19, %20, %21, %22, %23, %24, %25, %26, %27, %28, %29, %30, %31, %32, %33, %34, %35, %36, %37, %38, %39, %40, %41, %42, %43, %44, %45, %46, %47, %48, %49, %50, %51, %52, %53, %54, %55, %56, %57, %58, %59, %60, %61, %62, %63, %64, %65, %66, %67, %68, %69, %70, %71, %72, %73, %74, %75, %76, %77, %78, %79, %80, %81, %82, %83, %84, %85, %86, %87, %88, %89, %90, %91, %92, %93, %94, %95, %96, %97, %98, %99, %100, %101, %102, %103, %104, %105, %106, %107, %108, %109, %110, %111, %112, %113, %114, %115, %116, %117, %118, %119, %120, %121, %122, %123, %124, %125, %126, %127, %128, %129}, "
    "a, b, 1, 1, 1, 0, 1;\n"
    "mad.lo.u32 t, %134, 2, t;\nmad.lo.u32 %130, %134, 128, %130;\n"
    "mov.b64 a, {t, %132};\nmov.b64 b, {%130, %133};\n"
    "wgmma.mma_async.sync.aligned.m64n256k16.f32.bf16.bf16 "
    "{%2, %3, %4, %5, %6, %7, %8, %9, %10, %11, %12, %13, %14, %15, %16, %17, %18, %19, %20, %21, %22, %23, %24, %25, %26, %27, %28, %29, %30, %31, %32, %33, %34, %35, %36, %37, %38, %39, %40, %41, %42, %43, %44, %45, %46, %47, %48, %49, %50, %51, %52, %53, %54, %55, %56, %57, %58, %59, %60, %61, %62, %63, %64, %65, %66, %67, %68, %69, %70, %71, %72, %73, %74, %75, %76, %77, %78, %79, %80, %81, %82, %83, %84, %85, %86, %87, %88, %89, %90, %91, %92, %93, %94, %95, %96, %97, %98, %99, %100, %101, %102, %103, %104, %105, %106, %107, %108, %109, %110, %111, %112, %113, %114, %115, %116, %117, %118, %119, %120, %121, %122, %123, %124, %125, %126, %127, %128, %129}, "
    "a, b, 1, 1, 1, 0, 1;\n"
    "wgmma.commit_group.sync.aligned;\nselp.u32 %0, 1, 0, p;\nselp.u32 %1, 1, 0, q;\n}"
    : "=r"(ok.x), "=r"(ok.y), "+f"(d[0]), "+f"(d[1]), "+f"(d[2]), "+f"(d[3]), "+f"(d[4]), "+f"(d[5]), "+f"(d[6]), "+f"(d[7]), "+f"(d[8]), "+f"(d[9]), "+f"(d[10]), "+f"(d[11]), "+f"(d[12]), "+f"(d[13]), "+f"(d[14]), "+f"(d[15]), "+f"(d[16]), "+f"(d[17]), "+f"(d[18]), "+f"(d[19]), "+f"(d[20]), "+f"(d[21]), "+f"(d[22]), "+f"(d[23]), "+f"(d[24]), "+f"(d[25]), "+f"(d[26]), "+f"(d[27]), "+f"(d[28]), "+f"(d[29]), "+f"(d[30]), "+f"(d[31]), "+f"(d[32]), "+f"(d[33]), "+f"(d[34]), "+f"(d[35]), "+f"(d[36]), "+f"(d[37]), "+f"(d[38]), "+f"(d[39]), "+f"(d[40]), "+f"(d[41]), "+f"(d[42]), "+f"(d[43]), "+f"(d[44]), "+f"(d[45]), "+f"(d[46]), "+f"(d[47]), "+f"(d[48]), "+f"(d[49]), "+f"(d[50]), "+f"(d[51]), "+f"(d[52]), "+f"(d[53]), "+f"(d[54]), "+f"(d[55]), "+f"(d[56]), "+f"(d[57]), "+f"(d[58]), "+f"(d[59]), "+f"(d[60]), "+f"(d[61]), "+f"(d[62]), "+f"(d[63]), "+f"(d[64]), "+f"(d[65]), "+f"(d[66]), "+f"(d[67]), "+f"(d[68]), "+f"(d[69]), "+f"(d[70]), "+f"(d[71]), "+f"(d[72]), "+f"(d[73]), "+f"(d[74]), "+f"(d[75]), "+f"(d[76]), "+f"(d[77]), "+f"(d[78]), "+f"(d[79]), "+f"(d[80]), "+f"(d[81]), "+f"(d[82]), "+f"(d[83]), "+f"(d[84]), "+f"(d[85]), "+f"(d[86]), "+f"(d[87]), "+f"(d[88]), "+f"(d[89]), "+f"(d[90]), "+f"(d[91]), "+f"(d[92]), "+f"(d[93]), "+f"(d[94]), "+f"(d[95]), "+f"(d[96]), "+f"(d[97]), "+f"(d[98]), "+f"(d[99]), "+f"(d[100]), "+f"(d[101]), "+f"(d[102]), "+f"(d[103]), "+f"(d[104]), "+f"(d[105]), "+f"(d[106]), "+f"(d[107]), "+f"(d[108]), "+f"(d[109]), "+f"(d[110]), "+f"(d[111]), "+f"(d[112]), "+f"(d[113]), "+f"(d[114]), "+f"(d[115]), "+f"(d[116]), "+f"(d[117]), "+f"(d[118]), "+f"(d[119]), "+f"(d[120]), "+f"(d[121]), "+f"(d[122]), "+f"(d[123]), "+f"(d[124]), "+f"(d[125]), "+f"(d[126]), "+f"(d[127]), "+r"(db)
    : "r"(da), "r"(h0), "r"(h1), "r"(one), "r"(b0), "r"(p0), "r"(b1), "r"(p1) : "memory");
  return ok;
}
template <int S> __device__ __forceinline__ void wgmma_aug192(float (&d)[S], uint32_t a0, uint32_t a1, uint32_t db, uint32_t h1) {
  asm volatile("{\n.reg .b64 b;\n.reg .b32 z;\nmov.b32 z, 0;\n"
    "mov.b64 b, {%98, %99};\nwgmma.fence.sync.aligned;\n"
    "wgmma.mma_async.sync.aligned.m64n192k16.f32.bf16.bf16 "
    "{%0, %1, %2, %3, %4, %5, %6, %7, %8, %9, %10, %11, %12, %13, %14, %15, %16, %17, %18, %19, %20, %21, %22, %23, %24, %25, %26, %27, %28, %29, %30, %31, %32, %33, %34, %35, %36, %37, %38, %39, %40, %41, %42, %43, %44, %45, %46, %47, %48, %49, %50, %51, %52, %53, %54, %55, %56, %57, %58, %59, %60, %61, %62, %63, %64, %65, %66, %67, %68, %69, %70, %71, %72, %73, %74, %75, %76, %77, %78, %79, %80, %81, %82, %83, %84, %85, %86, %87, %88, %89, %90, %91, %92, %93, %94, %95}, "
    "{%96, %97, z, z}, b, 1, 1, 1, 1;\n"
    "wgmma.commit_group.sync.aligned;\n}"
    : "+f"(d[0]), "+f"(d[1]), "+f"(d[2]), "+f"(d[3]), "+f"(d[4]), "+f"(d[5]), "+f"(d[6]), "+f"(d[7]), "+f"(d[8]), "+f"(d[9]), "+f"(d[10]), "+f"(d[11]), "+f"(d[12]), "+f"(d[13]), "+f"(d[14]), "+f"(d[15]), "+f"(d[16]), "+f"(d[17]), "+f"(d[18]), "+f"(d[19]), "+f"(d[20]), "+f"(d[21]), "+f"(d[22]), "+f"(d[23]), "+f"(d[24]), "+f"(d[25]), "+f"(d[26]), "+f"(d[27]), "+f"(d[28]), "+f"(d[29]), "+f"(d[30]), "+f"(d[31]), "+f"(d[32]), "+f"(d[33]), "+f"(d[34]), "+f"(d[35]), "+f"(d[36]), "+f"(d[37]), "+f"(d[38]), "+f"(d[39]), "+f"(d[40]), "+f"(d[41]), "+f"(d[42]), "+f"(d[43]), "+f"(d[44]), "+f"(d[45]), "+f"(d[46]), "+f"(d[47]), "+f"(d[48]), "+f"(d[49]), "+f"(d[50]), "+f"(d[51]), "+f"(d[52]), "+f"(d[53]), "+f"(d[54]), "+f"(d[55]), "+f"(d[56]), "+f"(d[57]), "+f"(d[58]), "+f"(d[59]), "+f"(d[60]), "+f"(d[61]), "+f"(d[62]), "+f"(d[63]), "+f"(d[64]), "+f"(d[65]), "+f"(d[66]), "+f"(d[67]), "+f"(d[68]), "+f"(d[69]), "+f"(d[70]), "+f"(d[71]), "+f"(d[72]), "+f"(d[73]), "+f"(d[74]), "+f"(d[75]), "+f"(d[76]), "+f"(d[77]), "+f"(d[78]), "+f"(d[79]), "+f"(d[80]), "+f"(d[81]), "+f"(d[82]), "+f"(d[83]), "+f"(d[84]), "+f"(d[85]), "+f"(d[86]), "+f"(d[87]), "+f"(d[88]), "+f"(d[89]), "+f"(d[90]), "+f"(d[91]), "+f"(d[92]), "+f"(d[93]), "+f"(d[94]), "+f"(d[95])
    : "r"(a0), "r"(a1), "r"(db), "r"(h1) : "memory");
}
template <int S> __device__ __forceinline__ void wgmma_aug256(float (&d)[S], uint32_t a0, uint32_t a1, uint32_t db, uint32_t h1) {
  asm volatile("{\n.reg .b64 b;\n.reg .b32 z;\nmov.b32 z, 0;\n"
    "mov.b64 b, {%130, %131};\nwgmma.fence.sync.aligned;\n"
    "wgmma.mma_async.sync.aligned.m64n256k16.f32.bf16.bf16 "
    "{%0, %1, %2, %3, %4, %5, %6, %7, %8, %9, %10, %11, %12, %13, %14, %15, %16, %17, %18, %19, %20, %21, %22, %23, %24, %25, %26, %27, %28, %29, %30, %31, %32, %33, %34, %35, %36, %37, %38, %39, %40, %41, %42, %43, %44, %45, %46, %47, %48, %49, %50, %51, %52, %53, %54, %55, %56, %57, %58, %59, %60, %61, %62, %63, %64, %65, %66, %67, %68, %69, %70, %71, %72, %73, %74, %75, %76, %77, %78, %79, %80, %81, %82, %83, %84, %85, %86, %87, %88, %89, %90, %91, %92, %93, %94, %95, %96, %97, %98, %99, %100, %101, %102, %103, %104, %105, %106, %107, %108, %109, %110, %111, %112, %113, %114, %115, %116, %117, %118, %119, %120, %121, %122, %123, %124, %125, %126, %127}, "
    "{%128, %129, z, z}, b, 1, 1, 1, 1;\n"
    "wgmma.commit_group.sync.aligned;\n}"
    : "+f"(d[0]), "+f"(d[1]), "+f"(d[2]), "+f"(d[3]), "+f"(d[4]), "+f"(d[5]), "+f"(d[6]), "+f"(d[7]), "+f"(d[8]), "+f"(d[9]), "+f"(d[10]), "+f"(d[11]), "+f"(d[12]), "+f"(d[13]), "+f"(d[14]), "+f"(d[15]), "+f"(d[16]), "+f"(d[17]), "+f"(d[18]), "+f"(d[19]), "+f"(d[20]), "+f"(d[21]), "+f"(d[22]), "+f"(d[23]), "+f"(d[24]), "+f"(d[25]), "+f"(d[26]), "+f"(d[27]), "+f"(d[28]), "+f"(d[29]), "+f"(d[30]), "+f"(d[31]), "+f"(d[32]), "+f"(d[33]), "+f"(d[34]), "+f"(d[35]), "+f"(d[36]), "+f"(d[37]), "+f"(d[38]), "+f"(d[39]), "+f"(d[40]), "+f"(d[41]), "+f"(d[42]), "+f"(d[43]), "+f"(d[44]), "+f"(d[45]), "+f"(d[46]), "+f"(d[47]), "+f"(d[48]), "+f"(d[49]), "+f"(d[50]), "+f"(d[51]), "+f"(d[52]), "+f"(d[53]), "+f"(d[54]), "+f"(d[55]), "+f"(d[56]), "+f"(d[57]), "+f"(d[58]), "+f"(d[59]), "+f"(d[60]), "+f"(d[61]), "+f"(d[62]), "+f"(d[63]), "+f"(d[64]), "+f"(d[65]), "+f"(d[66]), "+f"(d[67]), "+f"(d[68]), "+f"(d[69]), "+f"(d[70]), "+f"(d[71]), "+f"(d[72]), "+f"(d[73]), "+f"(d[74]), "+f"(d[75]), "+f"(d[76]), "+f"(d[77]), "+f"(d[78]), "+f"(d[79]), "+f"(d[80]), "+f"(d[81]), "+f"(d[82]), "+f"(d[83]), "+f"(d[84]), "+f"(d[85]), "+f"(d[86]), "+f"(d[87]), "+f"(d[88]), "+f"(d[89]), "+f"(d[90]), "+f"(d[91]), "+f"(d[92]), "+f"(d[93]), "+f"(d[94]), "+f"(d[95]), "+f"(d[96]), "+f"(d[97]), "+f"(d[98]), "+f"(d[99]), "+f"(d[100]), "+f"(d[101]), "+f"(d[102]), "+f"(d[103]), "+f"(d[104]), "+f"(d[105]), "+f"(d[106]), "+f"(d[107]), "+f"(d[108]), "+f"(d[109]), "+f"(d[110]), "+f"(d[111]), "+f"(d[112]), "+f"(d[113]), "+f"(d[114]), "+f"(d[115]), "+f"(d[116]), "+f"(d[117]), "+f"(d[118]), "+f"(d[119]), "+f"(d[120]), "+f"(d[121]), "+f"(d[122]), "+f"(d[123]), "+f"(d[124]), "+f"(d[125]), "+f"(d[126]), "+f"(d[127])
    : "r"(a0), "r"(a1), "r"(db), "r"(h1) : "memory");
}

__device__ __forceinline__ uint32_t clock32() { uint32_t c; asm volatile("mov.u32 %0, %%clock;" : "=r"(c)); return c; }
__device__ __forceinline__ void spin_until(uint32_t c) {
  asm volatile("{\n.reg .pred p;\n.reg .s32 t;\nLAB_WAIT:\nmov.u32 t, %%clock;\nsub.s32 t, t, %0;\nsetp.lt.s32 p, t, 0;\n@p bra.uni LAB_WAIT;\n}" ::"r"(c) : "memory");
}
struct Nop { __device__ __forceinline__ void operator()(int) const {} };
template <int V> struct IC { static constexpr int v = V; };
struct Pipe {
  uint32_t db, g8, a8, pa, tph, aend, curB, curA, prevB, prevA, bo, so, sph, h0, h1, one;
  uint2 nx;
  int w; bool l0;
  __device__ __forceinline__ int lane() const { return LSO ? (so >> 5) & 31 : threadIdx.x & 31; }
  __device__ __forceinline__ void adv_a() { a8 += 8; pa += PA1; if (a8 == aend) a8 -= NA * 8; }
  __device__ __forceinline__ uint32_t take() { const uint32_t a = SB + OFF_A + a8 * 1024; adv_a(); return a; }
  __device__ __forceinline__ uint32_t ahead(int d) const { uint32_t ls = a8 + d * 8; if (ls >= aend) ls -= NA * 8; return SB + OFF_A + ls * 1024; }
  __device__ __forceinline__ uint32_t wait_ahead(int d) {
    uint32_t ls = a8 + d * 8;
    if (ls >= aend) ls -= NA * 8;
    mbar_spin31(SB + BAR_FULLA + ls, pa + d * PA1);
    return SB + OFF_A + ls * 1024;
  }
  template <int N, bool FIRST, int S> __device__ __forceinline__ uint2 iss(float (&acc)[S], bool skip) {
    const uint32_t da = DA0 + a8 * 64;
    if (!FIRST) { if (N != 192) db &= ~0x2000u; else if (db == DB0 + 15 * 512) db = DB0; }
    prevB = curB; prevA = curA;
    curB = g8 & 56; curA = a8;
    g8 += G1;
    a8 += skip ? 16 : 8; pa += skip ? 2 * PA1 : PA1;
    if (a8 >= aend) a8 -= NA * 8;
    const uint32_t fb = SB + BAR_FULLB + (g8 & 56), fa = SB + BAR_FULLA + a8;
    uint2 ok;
    if constexpr (N == 128) ok = FIRST ? wgmma_first128(acc, da, db, h0, h1, one, fb, g8, fa, pa) : wgmma_step128(acc, da, db, h0, h1, one, fb, g8, fa, pa);
    if constexpr (N == 192) ok = FIRST ? wgmma_first192(acc, da, db, h0, h1, one, fb, g8, fa, pa) : wgmma_step192(acc, da, db, h0, h1, one, fb, g8, fa, pa);
    if constexpr (N == 256) ok = FIRST ? wgmma_first256(acc, da, db, h0, h1, one, fb, g8, fa, pa) : wgmma_step256(acc, da, db, h0, h1, one, fb, g8, fa, pa);
    db += N * 8 - 384;
    return ok;
  }
  __device__ __forceinline__ void ensure(uint2 ok) {
    asm volatile(
        "{\n.reg .pred p, q;\n.reg .b64 s, t;\nmov.b64 s, {%1, %1};\nmov.b64 t, {%3, %3};\nsetp.ne.u32 p, %4, 0;\nsetp.ne.u32 q, %5, 0;\n@!p bra.uni LAB_WAIT;\n@q bra.uni DONE;\n"
        "LAB_WAIT:\nmbarrier.try_wait.shared::cta.b64 p, [%0], s;\nmbarrier.try_wait.shared::cta.b64 q, [%2], t;\n"
        "and.pred p, p, q;\n@!p bra.uni LAB_WAIT;\nDONE:\n}" ::"r"(SB + BAR_FULLB + (g8 & 56)), "r"(g8), "r"(SB + BAR_FULLA + a8), "r"(pa), "r"(ok.x), "r"(ok.y) : "memory");
  }
  template <class Hook> __device__ __forceinline__ void validate(bool check, const CUtensorMap* tm16, int c0, int c1, int wp, int j, Hook hook) {
    const uint32_t rows = SB + OFF_A + a8 * 1024 + wp * 2048, ad = a8 * 1024 + so;
    uint32_t v0 = 0, v1 = 0;
    asm volatile("{\n.reg .pred p;\nsetp.ne.u32 p, %3, 0;\n@p ld.shared.b32 %0, [%2];\n@p ld.shared.b32 %1, [%2 + 1024];\n}" : "+r"(v0), "+r"(v1) : "r"(ad), "r"((uint32_t)check));
    hook();
    while (__any_sync(~0u, max(v0, v1) == 0xffffffffu)) {
      const uint32_t bar = SB + BAR_SPEC + (w * 4 + wp) * 8;
      e_load<2048>(rows, tm16, c0 + sched_k(c_sched.v[j][(g8 >> 3) & 511]), c1 + wp * 16, bar);
      mbar_spin(bar, sph);
      sph ^= 1;
      v0 = lds32(ad); v1 = lds32(ad + 1024);
    }
  }
  __device__ __forceinline__ void fence() const { asm volatile("{\n.reg .pred p;\nsetp.eq.u32 p, %0, 2;\nLAB:\n@p pmevent 6;\n@p bra.uni LAB;\n}" ::"r"(one) : "memory"); }
  __device__ __forceinline__ void drain() {
    wg_wait<0>();
    arrive_2(SB + BAR_EMPTYB + curB, SB + BAR_EMPTYA + curA, l0);
    curB = BAR_DUMMY - BAR_EMPTYB; curA = BAR_DUMMY - BAR_EMPTYA;
  }
  __device__ __forceinline__ void signal_server(uint32_t odd) { __syncwarp(); arrive_n(SB + BAR_SRV + w * 16 + odd * 8, l0); }
  __device__ __forceinline__ void signal_loader() { __syncwarp(); arrive_n(SB + BAR_STG + w * 8, l0); }
  template <int N, bool HOLD = false, int S, class Pre = Nop> __device__ __forceinline__ void begin(float (&acc)[S], uint32_t p0, int proft, Pre pre = Pre()) {
    db = DB0 + p0 * 512;
    const uint32_t c1 = HOLD ? clock32() : 0;
    ensure(nx);
    if (HOLD) spin_until(c1 + lds32(SB + OFF_HOLD + w * 4));
    pre(0);
    PROF_T(w, proft, 0);
    ensure(iss<N, true>(acc, false));
  }
  template <int N, bool ENSURE = true, int S, class Hook> __device__ __forceinline__ void run(float (&acc)[S], int i0, int i1, uint32_t skips, int pause, Hook hook) {
    int i = i0;
    const int ev = w ? pause : -1;
#pragma unroll 1
    while (true) {
      const uint2 ok = iss<N, false>(acc, (skips >> i) & 1);
      wg_wait<1>();
      arrive_2(SB + BAR_EMPTYB + prevB, SB + BAR_EMPTYA + prevA, l0);
      if (pause >= 0 && i + 1 == i1) { nx = ok; break; }
      if constexpr (ENSURE) { ensure(ok); hook(i); } else hook(i, ok);
      i++;
      if (pause < 0 && i == i1) break;
      if (pause > 0 && i == ev) { drain(); mbar_spin(SB + BAR_LEAD, tph); }
    }
  }
  template <int N, bool AUG, int S> __device__ __forceinline__ void end(float (&acc)[S], int ns, uint32_t pos, uint32_t au0, uint32_t au1, int proft) {
    uint32_t augB = 0;
    arrive_n(SB + BAR_LEAD + w * (BAR_DUMMY - BAR_LEAD), l0);
    if constexpr (AUG) {
      asm volatile("{\n.reg .pred p;\n.reg .b64 s;\nmov.b64 s, {%1, %1};\nsetp.ne.u32 p, %2, 0;\n@p bra.uni DONE;\nLAB_WAIT:\nmbarrier.try_wait.shared::cta.b64 p, [%0], s;\n@!p bra.uni LAB_WAIT;\nDONE:\n}"
                     ::"r"(SB + BAR_FULLB + (g8 & 56)), "r"(g8), "r"(nx.x) : "memory");
      const uint32_t dc = (((SB + OFF_B) >> 4) | (64u << 16)) + pos * 512;
      if constexpr (N == 192) wgmma_aug192(acc, au0, au1, dc, h1); else wgmma_aug256(acc, au0, au1, dc, h1);
      augB = g8 & 56; g8 += G1;
    }
    tph ^= 1;
    if (ns > 0) wait_ahead(ns - 1);
    nx = make_uint2(mbar_test(SB + BAR_FULLB + (g8 & 56), g8 >> 31), AUG ? mbar_test(SB + BAR_FULLA + a8, pa >> 31) : 1);
    wg_wait<0>();
    arrive_2(SB + BAR_EMPTYB + curB, SB + BAR_EMPTYA + curA, l0);
    if (AUG) arrive_n(SB + BAR_EMPTYB + augB, l0);
    PROF_T(w, proft, 1);
  }
};

__device__ __forceinline__ uint32_t box_addr(uint32_t buf, uint32_t bo, int u) { return (buf + bo) ^ (u * 32); }

__device__ __forceinline__ float bf_round(float x) { return __bfloat162float(__float2bfloat16_rn(x)); }
__device__ __forceinline__ void own_rstd(int w, int wp, int lane, float (&rstd)[2]) {
#pragma unroll
  for (int hh = 0; hh < 2; hh++) rstd[hh] = __uint_as_float(lds32(SB + OFF_RSTD + (w * 72 + 8 + wp * 16 + (lane >> 2) + hh * 8) * 4));
}
__device__ __forceinline__ void stats_fetch(int w, int wp, int lane, uint32_t (&au)[2]) {
  const int g = lane >> 2, q4 = lane & 3;
  float rstd[2];
  own_rstd(w, wp, lane, rstd);
#pragma unroll
  for (int hh = 0; hh < 2; hh++) {
    const float m = __uint_as_float(lds32(SB + OFF_MEAN + (w * 64 + wp * 16 + g + hh * 8) * 4));
    const float v = q4 == 3 ? rcp(rstd[hh]) : -m;
    const float v1 = bf_round(v), v2 = bf_round(v - v1);
    const float p = q4 == 1 ? v2 : (q4 == 2 ? v - v1 - v2 : v1);
    au[hh] = pack_bf16(p, q4 == 3 ? v2 : p);
  }
}

struct Attn {
  uint32_t lo[24], hi[24], ha[16], hslot;
  float c[8][4], rstd[2];
  float2 rk[3];
  const uint4* hsrc;
  __device__ __forceinline__ void pull(int lane) {
    asm volatile("{\n.reg .b64 a;\n.reg .b32 t;\nand.b32 t, %19, 3;\nmad.wide.u32 a, t, 8, %18;\nld.relaxed.gpu.global.v2.f32 {%16,%17}, [a + 2048];\nmad.wide.u32 a, %19, 16, %18;\n"
                 "ld.relaxed.gpu.global.v4.b32 {%0,%1,%2,%3}, [a];\nld.relaxed.gpu.global.v4.b32 {%4,%5,%6,%7}, [a + 512];\n"
                 "ld.relaxed.gpu.global.v4.b32 {%8,%9,%10,%11}, [a + 1024];\nld.relaxed.gpu.global.v4.b32 {%12,%13,%14,%15}, [a + 1536];\n}"
                 : "=&r"(ha[0]), "=&r"(ha[1]), "=&r"(ha[2]), "=&r"(ha[3]), "=&r"(ha[4]), "=&r"(ha[5]), "=&r"(ha[6]), "=&r"(ha[7]), "=&r"(ha[8]), "=&r"(ha[9]), "=&r"(ha[10]),
                   "=&r"(ha[11]), "=&r"(ha[12]), "=&r"(ha[13]), "=&r"(ha[14]), "=&r"(ha[15]), "=&f"(rk[0].x), "=&f"(rk[0].y) : "l"(hsrc), "r"(lane) : "memory");
  }
  __device__ __forceinline__ void A(const float (&acc)[96], Pipe& M, int w, int wp, int r, uint4* halo_out) {
    const int lane = M.lane();
    auto cvt = [&](uint32_t& d, int u) { asm volatile("cvt.rn.bf16x2.f32 %0, %1, %2;" : "=r"(d) : "f"(acc[u + 1]), "f"(acc[u])); };
    auto rest = [&] {
#pragma unroll
      for (int nb = 23; nb >= 0; nb--) {
        cvt(lo[nb], 4 * nb);
        if (nb < 8) cvt(hi[nb], 4 * nb + 2);
        if (nb >= 16) lo[nb] = movm(lo[nb]);
      }
    };
#pragma unroll
    for (int nb = 8; nb < 24; nb++) hi[nb] = pack_bf16(acc[4 * nb + 2], acc[4 * nb + 3]);
    hslot = M.ahead(3);
    const uint32_t hbuf = hslot + wp * 2048 + lane * 16;
#pragma unroll
    for (int nb = 16; nb < 24; nb++) hi[nb] = movm(hi[nb]);
    if (wp == 3) {
      if (r < 15) {
#pragma unroll
        for (int p = 0; p < 4; p++) halo_out[p * 32 + lane] = make_uint4(hi[8 + 4 * p] ? hi[8 + 4 * p] : 0x8000u, hi[9 + 4 * p], hi[10 + 4 * p], hi[11 + 4 * p]);
        const uint32_t rh = lds32(SB + OFF_RSTD + (w * 72 + 64 + (lane & 7)) * 4);
        if (lane < 8) reinterpret_cast<uint32_t*>(halo_out + 128)[lane] = rh ? rh : 0x80000000u;
      }
    } else {
#pragma unroll
      for (int p = 0; p < 4; p++)
        asm volatile("st.shared.v4.b32 [%0], {%1,%2,%3,%4};" ::"r"(hbuf + 2048 + p * 512), "r"(hi[8 + 4 * p]), "r"(hi[9 + 4 * p]), "r"(hi[10 + 4 * p]), "r"(hi[11 + 4 * p]) : "memory");
    }
    __syncwarp();
    arrive_n(SB + BAR_HALO + w * 8, M.l0);
    rest();
    hsrc = halo_out - 16 * 136;
#pragma unroll
    for (int u = 0; u < 16; u++) ha[u] = 0;
    rk[0] = make_float2(1.f, 1.f);
  }
  __device__ __forceinline__ void B(int w, int wp, int r, int lane, uint32_t hph) {
    own_rstd(w, wp, lane, rstd);
    if (wp == 0) {
#pragma unroll
      for (int u = 1; u < 3; u++) rk[u] = lds64(SB + OFF_RSTD + (w * 72 + u * 8 + 2 * (lane & 3)) * 4);
      while (r > 0 && __any_sync(~0u, min(min(min(ha[0], ha[4]), min(ha[8], ha[12])), min(__float_as_uint(rk[0].x), __float_as_uint(rk[0].y))) == 0)) {
        pull(lane);
      }
      return;
    }
    mbar_spin(SB + BAR_HALO + w * 8, hph);
#pragma unroll
    for (int p = 0; p < 4; p++)
      asm volatile("ld.shared.v4.b32 {%0,%1,%2,%3}, [%4];" : "=r"(ha[4 * p]), "=r"(ha[4 * p + 1]), "=r"(ha[4 * p + 2]), "=r"(ha[4 * p + 3]) : "r"(hslot + wp * 2048 + lane * 16 + p * 512) : "memory");
#pragma unroll
    for (int u = 0; u < 3; u++) rk[u] = lds64(SB + OFF_RSTD + (w * 72 + wp * 16 + u * 8 + 2 * (lane & 3)) * 4);
  }
  template <class F> __device__ __forceinline__ void C(int wp, int r, int lane, uint32_t zero, F last) {
    const int g = lane >> 2, q = lane & 3;
    const bool nohalo = (wp == 0) && (r == 0);
    const bool up0 = 2 * q > g, up1 = 2 * q + 1 > g;
    const float sc = 0.17677669529663687f * 1.4426950408889634f;
    const float kx0 = up0 ? rk[0].x : rk[1].x, kx1 = up1 ? rk[0].y : rk[1].y;
    const float ky0 = up0 ? rk[1].x : rk[2].x, ky1 = up1 ? rk[1].y : rk[2].y;
    const float fx = rstd[0] * sc, fy = rstd[1] * sc;
    float sm[2][4] = {}, s0[2][4] = {}, s1[2][4] = {};
#pragma unroll
    for (int ks = 0; ks < 2; ks++)
#pragma unroll
      for (int h = 0; h < 2; h++) {
        const int a = 4 * h + 2 * ks;
        mma16(s0[h], lo[a], hi[a], lo[a + 1], hi[a + 1], lo[8 + a], lo[9 + a]);
        mma16(s1[h], lo[a], hi[a], lo[a + 1], hi[a + 1], hi[8 + a], hi[9 + a]);
      }
#pragma unroll
    for (int u = 0; u < 4; u++) { const int a = 4 * (u & 1) + (u & 2); mma16(sm[u & 1], lo[a], hi[a], lo[a + 1], hi[a + 1], ha[a], ha[a + 1]); }
    uint32_t pf[2][4];
    const uint32_t um = (up0 ? 0xffffu : 0u) | (up1 ? 0xffff0000u : 0u);
#pragma unroll
    for (int h = 0; h < 2; h++) {
      if (nohalo) { sm[h][0] = -INFINITY; sm[h][1] = -INFINITY; }
      float x0 = (up0 ? sm[h][0] : s0[h][0]) * (kx0 * fx), x1 = (up1 ? sm[h][1] : s0[h][1]) * (kx1 * fx);
      float y0 = (up0 ? s0[h][2] : s1[h][2]) * (ky0 * fy), y1 = (up1 ? s0[h][3] : s1[h][3]) * (ky1 * fy);
      float mx = fmaxf(x0, x1), my = fmaxf(y0, y1);
      mx = fmaxf(mx, __shfl_xor_sync(~0u, mx, 1)); my = fmaxf(my, __shfl_xor_sync(~0u, my, 1));
      mx = fmaxf(mx, __shfl_xor_sync(~0u, mx, 2)); my = fmaxf(my, __shfl_xor_sync(~0u, my, 2));
      x0 = ex2(x0 - mx); x1 = ex2(x1 - mx); y0 = ex2(y0 - my); y1 = ex2(y1 - my);
      float sx = x0 + x1, sy = y0 + y1;
      x0 *= kx0; x1 *= kx1; y0 *= ky0; y1 *= ky1;
      sx += __shfl_xor_sync(~0u, sx, 1); sy += __shfl_xor_sync(~0u, sy, 1);
      sx += __shfl_xor_sync(~0u, sx, 2); sy += __shfl_xor_sync(~0u, sy, 2);
      sx = rcp(sx); sy = rcp(sy);
      x0 *= sx; x1 *= sx; y0 *= sy; y1 *= sy;
      const uint32_t px = pack_bf16(x0, x1), py = pack_bf16(y0, y1);
      pf[h][0] = px & um; pf[h][1] = px & ~um; pf[h][2] = py & um; pf[h][3] = py & ~um;
    }
#pragma unroll
    for (int u = 0; u < 4; u++) {
#pragma unroll
      for (int e = 0; e < 4; e++) { c[2 * u][e] = 0.f; c[2 * u + 1][e] = 0.f; }
      mma8(c[2 * u], ha[8 + 2 * u], ha[9 + 2 * u], pf[u >> 1][0]);
      mma8(c[2 * u + 1], lo[16 + 2 * u], lo[17 + 2 * u], pf[u >> 1][2]);
    }
#pragma unroll
    for (int u = 0; u < 4; u++) {
      mma8(c[2 * u], lo[16 + 2 * u], lo[17 + 2 * u], pf[u >> 1][1]);
      mma8(c[2 * u + 1], hi[16 + 2 * u], hi[17 + 2 * u], pf[u >> 1][3]);
    }
    uint32_t dep = 0;
    last();
#pragma unroll
    for (int u = 0; u < (EFIRST == 3 ? 0 : 8); u++) dep |= __float_as_uint(c[u][0]);
    asm volatile("bar.sync %0, 256;" ::"r"(3 + (dep & zero)) : "memory");
  }
  __device__ __forceinline__ void E(Pipe& M, bool urgent) {
#pragma unroll
    for (int u = 0; u < 4; u++)
      asm volatile("stmatrix.sync.aligned.m8n8.x4.trans.shared.b16 [%0], {%1, %2, %3, %4};" ::"r"(box_addr(hslot, M.bo, u)),
                   "r"(pack_bf16(c[2 * u][0], c[2 * u][1])), "r"(pack_bf16(c[2 * u + 1][0], c[2 * u + 1][1])),
                   "r"(pack_bf16(c[2 * u][2], c[2 * u][3])), "r"(pack_bf16(c[2 * u + 1][2], c[2 * u + 1][3])) : "memory");
    __syncwarp();
    arrive_n(SB + (urgent ? BAR_STG + M.w * 8 : BAR_SRV + M.w * 16 + 8), M.l0);
  }
};

__device__ __forceinline__ void epi_res(const float (&acc)[64], const float (&pre)[64], float sc0, float sc1, uint32_t (&xr)[32], Pipe& M, int wp) {
  Pipe T = M;
  const uint32_t buf0 = T.take(), buf1 = T.take();
#pragma unroll
  for (int u = 0; u < 8; u++) {
#pragma unroll
    for (int nb = 2 * u; nb < 2 * u + 2; nb++) {
      xr[2 * nb] = pack_bf16(fmaf(acc[4 * nb], sc0, pre[2 * nb]), fmaf(acc[4 * nb + 1], sc0, pre[32 + 2 * nb]));
      xr[2 * nb + 1] = pack_bf16(fmaf(acc[4 * nb + 2], sc1, pre[2 * nb + 1]), fmaf(acc[4 * nb + 3], sc1, pre[33 + 2 * nb]));
    }
    stsm4(box_addr(u < 4 ? buf0 : buf1, M.bo, u & 3), xr[4 * u], xr[4 * u + 1], xr[4 * u + 2], xr[4 * u + 3]);
    if (u == 3) { M.signal_loader(); M.fence(); }
  }
  __syncwarp();
  arrive_n(SB + BAR_STG2 + M.w * 8, M.l0);
  fence_async_smem();
  wg_bar(M.w);
}
__device__ __forceinline__ void presum(float (&pre)[64], const uint32_t (&xr)[32], int lane, float usebias) {
  const uint32_t bias = SB + OFF_VEC + (lane & 3) * 8;
#pragma unroll
  for (int nb = 0; nb < 16; nb++) {
    const float2 b = lds64(bias + nb * 32);
#pragma unroll
    for (int u = 2 * nb; u < 2 * nb + 2; u++) {
      pre[32 + u] = fmaf(b.y, usebias, bf_hi(xr[u])); pre[u] = fmaf(b.x, usebias, bf_lo(xr[u]));
      asm volatile("" : "+f"(pre[u]), "+f"(pre[32 + u]));
    }
  }
}
template <int U0, int U1, int S, int Q> __device__ __forceinline__ void pack_relu(uint32_t (&o)[Q], const float (&acc)[S]) {
#pragma unroll
  for (int u = U0; u < U1; u++) asm volatile("cvt.rn.relu.bf16x2.f32 %0, %1, %2;" : "=r"(o[u]) : "f"(acc[2 * u + 1]), "f"(acc[2 * u]));
}
__device__ __forceinline__ uint32_t sq_bf16x2(uint32_t a) { uint32_t d; asm("mul.rn.bf16x2 %0, %1, %1;" : "=r"(d) : "r"(a)); return d; }
template <int Q> __device__ __forceinline__ void ffn_stage(const uint32_t (&o)[Q], int i, Pipe& M) {
  i -= M.w;
  if (i == 1 || i == 4 || i == 7 || (Q == 64 && i == 10)) {
    const uint32_t buf = M.wait_ahead(2 - M.w);
#pragma unroll
    for (int b = 0; b < Q / 16; b++)
      if (i == 3 * b + 1) {
#pragma unroll
        for (int u = 4 * b; u < 4 * b + 4; u++)
          stsm4(box_addr(buf, M.bo, u & 3), sq_bf16x2(o[4 * u]), sq_bf16x2(o[4 * u + 1]), sq_bf16x2(o[4 * u + 2]), sq_bf16x2(o[4 * u + 3]));
      }
    M.signal_server((i & 1) ^ (Q == 64));
  }
}

__device__ __forceinline__ void wait_flags(const uint8_t* f, uint32_t tag, int lane) {
  const uint32_t t4 = (tag & 0xff) * 0x01010101u;
  const uint32_t* fp = reinterpret_cast<const uint32_t*>(f) + (lane & (FG / 4 - 1));
  while (__any_sync(~0u, __vsub4(ld_relaxed(fp), t4) & 0x80808080u)) {}
  asm volatile("fence.acquire.gpu;\nfence.proxy.async.global;" ::: "memory");
}
__device__ __forceinline__ uint32_t get_epoch() { mbar_spin(SB + BAR_EPOCH, 0); return __shfl_sync(~0u, lds32(SB + OFF_HOLD + 8), 0); }
__device__ __forceinline__ void aloader(const Params& P, const Ptrs& Q, int bid, int r, int j, int lane, int w, uint32_t e, uint32_t epoch) {
  const uint32_t abase = SB + OFF_A + w * NA * 8192, fbase = SB + BAR_FULLA + w * NA * 8, ebase = SB + BAR_EMPTYA + w * NA * 8;
  uint32_t slot = NPRO, ph = 1, nst = 0, npace = 0;
  int t = -1, kind = -1, a0 = 0, a1 = 0;
  const CUtensorMap* tmA = nullptr;
  uint64_t pol = 0;
  uint4* hin = Q.s->halo[0][0] + (r * 16 + j * 2 + w - 16) * 136;
  uint32_t* const pace = Q.s->pace[0] + (bid & -PG) * 4;
  const uint8_t* const flags = Q.s->flags[r / (FG / 8)][w];
  auto adv = [&] { if (++slot == NA) { slot = 0; ph ^= 1; } };
#pragma unroll 1
  for (int g = NPRO; g <= NSTEP; g++) {
    const uint32_t cur = e;
    e = c_sched.v[j][g + 1];
    if (!(cur & E_RARE)) {
      if (cur & E_HAND) { mbar_spin(ebase + slot * 8, ph); e_arrive(fbase + slot * 8, 1); adv(); }
    } else {
      if (cur & F_NEW) {
        t++; kind = kind == 5 ? 0 : kind + 1;
        const bool narrow = kind == 2 || kind == 5;
        static_assert(TM_XIN == 0 && TM_X == 1 && TM_XA == 2 && TM_O == 3 && TM_H == 4, "map order");
        tmA = &P.tm[t < 2 ? 0 : (0x422311 >> (4 * kind)) & 15];
        pol = ((AEF >> t) & 1) ? 0x12F0000000000000ull : 0x1000000000000000ull;
        a0 = narrow ? 0 : w * 1024; a1 = narrow ? r * 128 + w * 64 : r * 64;
      }
      const bool xo = cur & E_XPUB0;
      uint32_t s = slot;
      if (cur & (E_HAND | E_ATTN | E_XPUB0)) {
        if (cur & E_KEEP) e_arrive(ebase + slot * 8, 4);
#pragma unroll 1
        for (int u = xo ? 0 : 1; u < 2; u++) { mbar_wait(ebase + slot * 8, ph); e_arrive(fbase + slot * 8, 1); adv(); }
      }
      uint32_t hold = 0;
      int lag = 0;
      if ((xo && t < 12) || (cur & F_GATH)) {
        uint32_t v;
        uint32_t v1;
        do asm volatile("ld.relaxed.gpu.global.v2.u32 {%0, %1}, [%2];" : "=r"(v), "=r"(v1) : "l"(pace + npace + (lane & (PG - 1)) * 2) : "memory");
        while (__any_sync(~0u, ((v ^ (epoch * 16 + t - 1)) | (v ^ v1)) & 31));
        v += v1;
        npace ^= PG * 2;
        lag = min((int)(v - __shfl_sync(~0u, v, bid & (PG - 1))), 8000) * LAGM >> 5;
        hold = __reduce_max_sync(~0u, lag);
        asm volatile("st.shared.b32 [%0], %1;" ::"r"(SB + OFF_HOLD + w * 4), "r"(hold) : "memory");
      }
      if (cur & (E_ATTN | E_XPUB0)) {
        const uint32_t s2 = s == NA - 1 ? 0 : s + 1;
        mbar_wait(SB + BAR_STG + w * 8, nst & 1);
        nst++;
        LT(0);
        const uint32_t c1 = clock32();
        e_store(tmA, a0 + sched_k(cur), a1, abase + s * 8192);
        if (xo) {
          mbar_spin(SB + BAR_STG2 + w * 8, ~t & 1);
          e_store(tmA, a0 + sched_k(cur) + 64, a1, abase + s2 * 8192);
          if (t == 12) break;
        } else e_arrive(SB + BAR_OWN + w * 8, 1);
        LT(1);
        spin_until(c1 + hold + (xo ? SDELAY : SDELAYO));
        LT(2);
        LT(5);
      }
      if (cur & E_SIG) {
        e_arrive(SB + BAR_SRV + w * 16, 4);
      }
      if (cur & E_REL) bulk_wait_all();
      if ((cur & E_REL) && (kind == 1 || kind == 2) && r > 0) {
        uint4* hz = hin + lane;
        hin += 256 * 136;
#pragma unroll
        for (int p = 0; p < 4; p++) hz[p * 32] = make_uint4(0, 0, 0, 0);
        if (lane < 2) hz[128] = make_uint4(0, 0, 0, 0);
      }
      if (cur & E_WAIT) {
        wait_flags(flags + ((cur & E_PART1) ? FG : 0), epoch * 16 + t, lane);
      }
    }
    if (!(cur & (F_AUG | F_NOA))) {
      mbar_wait(ebase + slot * 8, ph);
      e_load(abase + slot * 8192, tmA, a0 + sched_k(cur), a1, fbase + slot * 8, pol);
      adv();
      if (cur & F_STAMP) {
        uint32_t stamp;
        asm volatile("mov.u32 %0, %%globaltimer_lo;" : "=r"(stamp));
        asm volatile("st.relaxed.gpu.global.u32 [%0], %1;" ::"l"(pace + npace + (bid & (PG - 1)) * 2 + w), "r"((stamp & ~31u) | ((epoch * 16 + t) & 31)) : "memory");
      }
    }
  }
  bulk_wait_all();
}

__device__ __forceinline__ void bloader(const Params& P, const Ptrs& Q, bool aux, int j, int lane, uint32_t e, uint32_t epoch) {
  const uint32_t* const sched = c_sched.v[aux ? 8 : j];
  int kind = -1, c2 = 0, c3 = 0, na = 0;
  const CUtensorMap* tmB = nullptr;
  uint32_t sph = 0, efm = aux ? 0 : BEF * 2;
  uint64_t pol = 0;
#pragma unroll 1
  for (int g = aux ? 8 + (j & 1) : NPRO; g < (aux ? NSTEP_AUX : NSTEP); g += 1 + aux) {
    const uint32_t cur = e;
    e = sched[g + 1 + aux];
    if (cur & F_NEW) {
      kind = kind == 5 ? 0 : kind + ((cur >> 29) & 3);
      static_assert(TM_WQKV == 5 && TM_WO == 6 && TM_W1A == 7 && TM_W1B == 8 && TM_W2 == 9, "map order");
      tmB = &P.tm[(0x978655 >> (4 * kind)) & 15];
      efm >>= 1;
      pol = (efm & 1) ? 0x12F0000000000000ull : 0x1000000000000000ull;
      na = (0x243233 >> (4 * kind)) & 15;
      c2 = ((0x277200 >> (4 * kind)) & 15) * j + (kind == 4 ? 3 : 0);
      c3 = kind <= 1 ? kind * 8 + j : 0;
    }
    const int need = g - (int)((cur >> 5) & 15);
    const uint32_t dst = SB + OFF_B + (cur & 31) * 8192, bar = SB + BAR_FULLB + (g & 7) * 8;
    mbar_wait(SB + BAR_EMPTYB + (need & 7) * 8, (need >> 3) & 1);
    if (!(cur & F_AUG)) {
      asm volatile("{\n.reg .pred p;\nelect.sync _|p, 0xffffffff;\n@p mbarrier.arrive.expect_tx.shared::cta.b64 _, [%2], %7;\n"
                   "@p cp.async.bulk.tensor.4d.shared::cluster.global.mbarrier::complete_tx::bytes.L2::cache_hint [%0], [%1, {%3, %4, %5, %6}], [%2], %8;\n}"
                   ::"r"(dst), "l"(tmB), "r"(bar), "r"(0), "r"(sched_k(cur)), "r"(c2), "r"(c3), "r"(na * 8192), "l"(pol) : "memory");
    } else {
      const bool chk = g < NSTEP / 2;
      const uint32_t b2 = chk ? SB + BAR_AUG : bar, ad = dst + lane * 16 + (lane >> 3) * 4;
      while (true) {
        asm volatile("{\n.reg .pred p;\nelect.sync _|p, 0xffffffff;\n@p mbarrier.arrive.expect_tx.shared::cta.b64 _, [%2], 4096;\n"
                     "@p cp.async.bulk.shared::cluster.global.mbarrier::complete_tx::bytes [%0], [%1], 4096, [%2];\n}"
                     ::"r"(dst), "l"(Q.s->aug[epoch & 1][(kind - (kind >= 3)) * 8 + j]), "r"(b2) : "memory");
        if (!chk) break;
        mbar_spin(b2, sph);
        sph ^= 1;
        uint32_t mn = ~0u;
#pragma unroll
        for (int u = 0; u < 8; u++) mn = min(mn, lds32(ad + u * 512));
        if (!__any_sync(~0u, mn == 0)) { e_arrive(bar, 1); break; }
      }
      __syncwarp();
    }
  }
}

constexpr uint32_t job_slots(int layer) {
  const int pos[10] = {11, 26, 63, 73, 77, 81, 92, 96, 100, 104};
  uint32_t v = 0;
  for (int m = 0; m < 10; m++) v |= (uint32_t)((layer * 148 + pos[m]) % NA) << (3 * m);
  return v;
}
constexpr uint32_t JOB_SLOTS0 = job_slots(0), JOB_SLOTS1 = job_slots(1);
__device__ __forceinline__ void server(const Params& P, const Ptrs& Q, int bid, int r, int j, int lane, uint32_t epoch) {
  const uint32_t c0 = clock32();
  if (PFT) {
    spin_until(c0 + PFT);
    if (lane < 16) asm volatile("cp.async.bulk.prefetch.L2.global [%0], 2048;" ::"l"(Q.x + (r * 128 + j * 16 + lane) * 1024) : "memory");
  }
  if (CPF) spin_until(c0 + CPF);
  epoch += __shfl_sync(~0u, c_sched.v[j][lane < 18 ? lane * 16 : 0] >> 31, 0);
  {
    const uint2 b = reinterpret_cast<const uint2*>(Q.b2 + j * 128)[lane];
    sts128(SB + OFF_VEC + lane * 16, b.x << 16, b.x & 0xffff0000u, b.y << 16, b.y & 0xffff0000u);
  }
  int hl = 0;
  uint32_t fph = 0, pend = SB + BAR_DUMMY3;
#pragma unroll 1
  for (int n = 0; n < 20; n++) {
    const int layer = n >= 10, m = n - 10 * layer;
    const bool stat = m == 0 || m == 2;
    const uint32_t slot = ((layer ? JOB_SLOTS1 : JOB_SLOTS0) >> (m * 3)) & 7;
    auto fetch = [&](int w) {
      asm volatile("{\n.reg .pred p;\nelect.sync _|p, 0xffffffff;\n@p mbarrier.arrive.expect_tx.shared::cta.b64 _, [%2], 4096;\n"
                   "@p cp.async.bulk.shared::cluster.global.mbarrier::complete_tx::bytes [%0], [%1], 4096, [%2];\n}"
                   ::"r"(SB + OFF_A + (w * NA + slot) * 8192), "l"(&Q.s->stats[hl][r * 32 + w * 16][0][0]), "r"(SB + BAR_SPEC + 64 + w * 8) : "memory");
    };
#pragma unroll 1
    for (int w = 0; w < 2; w++) {
      mbar_spin(SB + BAR_SRV + w * 16 + (n & 1) * 8, (n >> 1) & 1);
      if (stat) fetch(w);
      else {
        e_store(&P.tm[m == 1 ? TM_O : TM_H], m == 1 ? j * 64 : 448 * j + (m - 3) * 64, r * 128 + w * 64, SB + OFF_A + (w * NA + slot) * 8192);
        bulk_wait_read<1>();
        e_arrive(pend, 4);
        pend = SB + BAR_EMPTYA + (w * NA + slot) * 8;
      }
    }
    if (stat) {
#pragma unroll 1
      for (int w = 0; w < 2; w++) {
        const uint32_t src = SB + OFF_A + (w * NA + slot) * 8192 + (lane >> 1) * 256 + ((lane >> 1) & 7) * 32 + (lane & 1) * 16;
        float ms[2], md[2], mq[2], m0[2];
        while (true) {
          mbar_spin(SB + BAR_SPEC + 64 + w * 8, (fph >> w) & 1);
          fph ^= 1u << w;
          uint32_t bad = 0;
          ms[0] = ms[1] = md[0] = md[1] = mq[0] = mq[1] = m0[0] = m0[1] = 0.f;
#pragma unroll 1
          for (int p = 0; p < 8; p += 2) {
            const float4 v2[2] = {lds128(src ^ (p * 32)), lds128(src ^ (p * 32) ^ 32)};
            if (p == 0) { m0[0] = v2[0].x; m0[1] = v2[0].z; }
#pragma unroll
            for (int z = 0; z < 2; z++) {
              const float4 v = v2[z];
              const float a = v.x - m0[0], b = v.z - m0[1];
              bad |= __float_as_uint(v.y) ^ epoch;
              ms[0] += a; md[0] = fmaf(a, a, md[0]); mq[0] += __uint_as_float(__float_as_uint(v.y) & ~63u);
              ms[1] += b; md[1] = fmaf(b, b, md[1]); mq[1] += v.w;
            }
          }
          if (!__any_sync(~0u, bad & 63)) break;
          fetch(w);
          __syncwarp();
        }
        e_arrive(SB + BAR_EMPTYA + (w * NA + slot) * 8, 4);
        const int row = (lane >> 3) * 16 + (lane & 7);
#pragma unroll
        for (int z = 0; z < 2; z++) {
          const float d = ms[z] * 0.125f;
          asm volatile("st.shared.f32 [%0], %1;" ::"r"(SB + OFF_MEAN + (w * 64 + row + z * 8) * 4), "f"(m0[z] + d) : "memory");
          const float rs = rsq(fmaf(mq[z], 1.f / 1024.f, fmaxf(fmaf(md[z], 0.125f, -d * d), 0.f)) + 1e-5f);
          asm volatile("st.shared.f32 [%0], %1;" ::"r"(SB + OFF_RSTD + (w * 72 + 8 + row + z * 8) * 4), "f"(rs) : "memory");
        }
        e_arrive(SB + BAR_STAT + w * 8, 8);
      }
    }
    if (stat && n != 12) {
#pragma unroll 1
      for (int u = 0; u < (m ? 2 : 3); u++) {
        const uint32_t pitch = u == 2 ? 448 : 128;
        uint4* p = reinterpret_cast<uint4*>(u == 2 ? Q.s->h : (m ? Q.out : Q.s->x)) + (u == 2 ? 64 + j * 8 : j * 16 + u * 8) + ((r * 128 + (lane >> 3)) * pitch + (lane & 7));
#pragma unroll 1
        for (int k = 0; k < 32 / FUN; k++) {
#pragma unroll
          for (int z = 0; z < FUN; z++) {
            *p = make_uint4(~0u, ~0u, ~0u, ~0u);
            p += 4 * pitch;
            asm volatile("" : "+l"(p));
          }
        }
      }
      __syncwarp();
    }
    if ((0x222 >> m) & 1) {
      bulk_wait_all();
      e_arrive(pend, 4);
      pend = SB + BAR_DUMMY3;
      if (lane < 2) st_release8(&Q.s->flags[r / (FG / 8)][lane][(r & (FG / 8 - 1)) * 8 + j + (m == 9 ? FG : 0)], epoch * 16 + layer * 6 + (m == 1 ? 2 : 5));
      __syncwarp();
    }
    hl += stat;
  }
}

__device__ __forceinline__ void aux_math(const Ptrs& Q, int bid, int jj, int warp, int lane) {
  const int g = lane >> 2, q = lane & 3, c0 = (warp & 3) * 2;
  uint32_t st = warp >> 2, bf[16][4] = {};
  const uint32_t ad0 = SB + ((lane >> 4) * 8 + (lane & 7)) * 128 + (((c0 + ((lane >> 3) & 1)) ^ (lane & 7)) << 4);
#pragma unroll 1
  for (int t = 0; t < 4; t++) {
    float acc[4][4] = {};
    uint32_t bias[8];
#pragma unroll
    for (int a = 0; a < 8; a++) bias[a] = t >= 2 ? reinterpret_cast<const uint32_t*>(Q.b1 + 448 * jj + (t - 2) * 192 + c0 * 8)[(a >> 1) * 32 + (a & 1) * 4 + q] : 0u;
#pragma unroll 1
    for (int i = 0; i < 16; i++, st += 2) {
      const uint32_t ad = ad0 + (c_sched.v[8][st] & 31) * 8192;
      mbar_spin(SB + BAR_FULLB + (st & 7) * 8, (st >> 3) & 1);
#pragma unroll
      for (int u = 0; u < 16; u++)
        asm volatile("{\n.reg .pred p;\nsetp.ne.u32 p, %5, 0;\n@p ldmatrix.sync.aligned.m8n8.x4.trans.shared.b16 {%0,%1,%2,%3}, [%4];\n}"
                     : "+r"(bf[u][0]), "+r"(bf[u][1]), "+r"(bf[u][2]), "+r"(bf[u][3])
                     : "r"(ad + (u & 3) * 8192 + (u >> 2) * 2048), "r"((u & 3) != 3 || t == 3 ? 1 : 0) : "memory");
      __syncwarp();
      e_arrive(SB + BAR_EMPTYB + (st & 7) * 8, 2);
#pragma unroll
      for (int u = 0; u < 16; u++) mma16(acc[u & 3], bf[u][0], bf[u][1], bf[u][2], bf[u][3], 0x3F803F80u, 0x3F803F80u);
    }
    const uint32_t epoch = lds32(SB + OFF_HOLD + 8);
    const uint32_t o = (t * 8 + jj) * 1024 + g * 32 + ((c0 ^ g) << 2) + q + (epoch & 1) * 32768;
    uint32_t *const p0 = Q.s->aug[0][0] + o, *const p1 = Q.s->aug[0][0] + (o ^ 4);
#pragma unroll
    for (int a = 0; a < 8; a++) {
      const float u = acc[a >> 1][(a & 1) * 2];
      uint32_t h = movm(pack_bf16(u, u - bf_round(u)));
      if (g >= 6) h = bias[a];
      ((a & 1) ? p1 : p0)[(a >> 1) * 256] = h ? h : 0x8000u;
    }
    uint4* const z = reinterpret_cast<uint4*>(Q.s->aug[~epoch & 1][t * 8 + jj]) + (threadIdx.x & 127);
    z[0] = z[128] = make_uint4(0, 0, 0, 0);
  }
}

template <bool BYSM> __global__ void __launch_bounds__(NTHREADS, 1) mega_kernel(const __grid_constant__ Ptrs Q, const __grid_constant__ Params P) {
  extern __shared__ __align__(1024) uint8_t smem_raw[];
  constexpr uint32_t sb = SB;
  const uint32_t centry = clock32();
  const int warp = __shfl_sync(~0u, threadIdx.x >> 5, 0), lane = threadIdx.x & 31;
  const int bid = BYSM ? work_id() : blockIdx.x;
  const bool aux = bid >= NMAIN;
  const int r = Q44 ? ((bid >> 5) << 2) | (bid & 3) : ((bid >> 4) << 1) | (bid & 1), j = (aux ? bid * 2 : bid >> (1 + Q44)) & 7;
  PRO(0);
  {
    const uint32_t b = sb + OFF_BAR + warp * 48, cnt = warp < 6 ? 1 : (warp < 10 ? 4 : 8);
    asm volatile("{\n.reg .pred p;\nelect.sync _|p, 0xffffffff;\n@p mbarrier.init.shared::cta.b64 [%0], %1;\n@p mbarrier.init.shared::cta.b64 [%0 + 8], %1;\n"
                 "@p mbarrier.init.shared::cta.b64 [%0 + 16], %1;\n@p mbarrier.init.shared::cta.b64 [%0 + 24], %1;\n"
                 "@p mbarrier.init.shared::cta.b64 [%0 + 32], %1;\n@p mbarrier.init.shared::cta.b64 [%0 + 40], %1;\nfence.mbarrier_init.release.cluster;\n}"
                 ::"r"(b), "r"(cnt) : "memory");
  }
  __syncthreads();
  {
    static_assert(NPRO == 4, "prologue stages");
    const int st = ((11 - warp) * (aux ? 32 : 11)) >> 5, op = aux ? (st < 8) * 2 : 11 - warp - 3 * st, sd = aux ? st >> STGX : (op == 2 ? st : st & 2);
    const uint32_t bar0 = sb + OFF_BAR + (op * 6 + st) * 8;
    const int kc = aux ? (st >> 1) * 64 : (((st & 2 ? ROUND1 : ROUND0) >> (4 * j)) & 15) * 128 + (st & 1) * 64;
    spin_until(centry + (sd ? STG0 + sd * STG1 : 0));
    if (op == 2) {
      asm volatile("{\n.reg .pred p;\nelect.sync _|p, 0xffffffff;\n@p mbarrier.arrive.expect_tx.shared::cta.b64 _, [%2], 24576;\n"
                   "@p cp.async.bulk.tensor.4d.shared::cluster.global.mbarrier::complete_tx::bytes [%0], [%1, {%3, %4, %3, %5}], [%2];\n}"
                   ::"r"(sb + OFF_B + (aux ? (st & 1) * 114688 + (st >> 1) * 24576 : (st + pos0(0) / 3 - (st + pos0(0) / 3 >= 5 ? 5 : 0)) * 24576)), "l"(&P.tm[TM_WQKV]), "r"(bar0), "r"(0), "r"(kc), "r"(j + (st & aux)) : "memory");
    } else if (!aux) e_load(sb + OFF_A + (op * 6 + st) * 8192, &P.tm[TM_XIN], op * 1024 + kc, r * 64, bar0);
    PRO(1);
    asm volatile("prefetch.tensormap [%0];" ::"l"(&P.tm[warp]) : "memory");
  }
  if (warp >= 8) {
    asm volatile("setmaxnreg.dec.sync.aligned.u32 24;");
    if (warp == 11) {
      if (smem_u32(smem_raw) != SB) __trap();
      const uint32_t epoch = __shfl_sync(~0u, ld_relaxed(&Q.s->epoch[bid]) + 1, 0);
      Q.s->epoch[bid] = epoch;
      asm volatile("st.shared.b32 [%0], %1;" ::"r"(sb + OFF_HOLD + 8), "r"(epoch) : "memory");
      e_arrive(sb + BAR_EPOCH, 1);
      PRO(2);
      if (!aux) server(P, Q, bid, r, j, lane, epoch);
    } else {
      const uint32_t e = c_sched.v[aux ? 8 : j][aux ? warp : NPRO];
      spin_until(centry + STGL + (aux ? STGLX : (warp > 8 ? STGLW : 0)) + (e >> 31));
      PRO(2);
      const uint32_t epoch = get_epoch();
      PRO(3);
      if (warp <= 8 + aux) bloader(P, Q, aux, j + warp - 8, lane, e, epoch);
      else if (!aux) aloader(P, Q, bid, r, j, lane, warp - 9, e, epoch);
    }
  } else if (aux) aux_math(Q, bid, j + (warp >> 2), warp, lane);
  else {
    asm volatile("setmaxnreg.inc.sync.aligned.u32 240;");
    const int w = warp >> 2, wp = warp & 3;
    {
      uint32_t xr[32];
#pragma unroll
      for (int u = 0; u < 32; u++) if (NOI) asm volatile("" : "=r"(xr[u])); else xr[u] = 0;
      Pipe M;
      M.db = 0; M.g8 = 0; M.a8 = w * NA * 8; M.pa = 0; M.tph = 0; M.aend = (w + 1) * NA * 8;
      M.h0 = gridDim.y * 0x40000040u; M.h1 = gridDim.z * 0x40000040u; M.one = gridDim.z;
      M.curB = M.curA = M.prevB = M.prevA = M.sph = 0; M.nx = make_uint2(0, 0); M.w = w; M.l0 = lane == 0;
      M.bo = (wp * 16 + (lane & 15)) * 128 + (((lane >> 4) ^ (lane & 7)) << 4);
      M.so = __shfl_sync(~0u, SB + OFF_A + wp * 2048 + lane * 32 + (lane >> 2) * 4, lane);
      M.bo = __shfl_sync(~0u, M.bo, lane);
      auto nop = [](int) {};
      const uint32_t zero = gridDim.y - 1;
      PROF_T(w, 0, 3);
      if (STARTC) spin_until(centry + STARTC);
#pragma unroll 1
      for (int hl = 0; hl < 4; hl++) {
        const int t0 = hl * 3;
        const bool ffn = hl & 1;
        float acc[96], acn[64];
        uint32_t au[2] = {0u, 0u};
        {
          const int d = hl ? 0 : ((OWNP * 2u) >> (4 * j)) & 15;
          auto own = [&](auto h, uint32_t dep = 0) {
#pragma unroll
            for (int u = 4 * h.v; u < 4 * h.v + 4; u++)
              asm volatile("ldmatrix.sync.aligned.m8n8.x4.shared.b16 {%0,%1,%2,%3}, [%4];" : "=r"(xr[4 * u]), "=r"(xr[4 * u + 1]), "=r"(xr[4 * u + 2]), "=r"(xr[4 * u + 3])
                           : "r"(box_addr(sb + OFF_A + M.a8 * 1024, M.bo + dep, u & 3)) : "memory");
          };
          M.begin<192>(acc, ffn ? pos0(3) : pos0(0), t0, [&](int) { if (hl + d == 0) own(IC<0>{}); });
          if (hl + d == 0) own(IC<1>{}, (xr[0] | xr[4] | xr[8] | xr[12]) & zero);
          float ss[2] = {0.f, 0.f}, sq[2] = {0.f, 0.f};
          auto part = [&](auto c0, auto n) {
#pragma unroll
            for (int v = 0; v < 4 * n.v; v++) {
              const int u = c0.v + v / n.v * 4 + v % n.v;
              float a, b;
              asm volatile("shl.b32 %0, %2, 16;\nand.b32 %1, %2, 0xffff0000;" : "=f"(a), "=f"(b) : "r"(xr[u]));
              ss[u & 1] += a + b; sq[u & 1] = fmaf(a, a, fmaf(b, b, sq[u & 1]));
            }
          };
          const uint64_t plan = hl ? (ffn ? PLAN1 : PLAN2) : (w ? (d & 4 ? (d & 2 ? PB6 : PB4) : (d ? PB2 : PB0)) : (d & 4 ? (d & 2 ? PA6 : PA4) : (d ? PA2 : PA0)));
          auto todo = [&](int i) { uint64_t v; asm volatile("shr.u64 %0, %1, %2;" : "=l"(v) : "l"(plan), "r"((i + 1 - d) * 8)); return (uint32_t)v; };
          uint32_t m = todo(1);
          M.run<192, false>(acc, 1, 16, 1u << 10, 16 - (ffn ? LEAD3 : LEAD0), [&](int i, uint2 ok) {
           CT(0);
           if (m & 127) {
             if (m & 1) part(IC<0>{}, IC<2>{});
             if (m & 2) part(IC<2>{}, IC<2>{});
             if (m & 4) part(IC<16>{}, IC<1>{});
             if (m & 8) part(IC<17>{}, IC<1>{});
             if (m & 16) part(IC<18>{}, IC<1>{});
             if (m & 32) part(IC<19>{}, IC<1>{});
             if (m & 64) {
               const uint32_t epoch = lds32(sb + OFF_HOLD + 8);
#pragma unroll
               for (int o = 1; o < 4; o *= 2)
#pragma unroll
                 for (int z = 0; z < 2; z++) { ss[z] += __shfl_xor_sync(~0u, ss[z], o); sq[z] += __shfl_xor_sync(~0u, sq[z], o); }
               const float m0 = ss[0] * (1.f / 128.f), m1 = ss[1] * (1.f / 128.f);
               const int rowpair = r * 64 + w * 32 + wp * 8 + (M.lane() >> 2);
               if ((M.lane() & 3) == 0)
                 st_pkt(&Q.s->stats[hl][rowpair >> 1][j][rowpair & 1], __float_as_uint(m0), (__float_as_uint(fmaxf(fmaf(-ss[0], m0, sq[0]), 0.f)) & ~63u) | (epoch & 63),
                        __float_as_uint(m1), __float_as_uint(fmaxf(fmaf(-ss[1], m1, sq[1]), 0.f)));
             }
           }
           CT(1);
           M.ensure(ok);
           CT(3);
           M.validate(hl != 0, &P.tm[ffn ? TM_XA16 : TM_X16], w * 1024, r * 64, wp, j, [&] {
            if (m & 128) { if (m & 1) own(IC<1>{}); else own(IC<0>{}); }
            m = todo(i + 1);
            if (i == STATI) { mbar_spin(sb + BAR_STAT + w * 8, hl & 1); stats_fetch(w, wp, M.lane(), au); }
           });
           CT(4);
          });
          M.end<192, true>(acc, ffn ? 0 : 4, ffn ? posa(3) : posa(0), au[0], au[1], t0);
          PROF_T(w, t0, 2);
        }
        if (!ffn) {
          Attn T;
#pragma unroll 1
          for (int wave = 0; wave < 2; wave++) {
            AP(9);
            uint4* const hp = Q.s->halo[0][0] + (uint32_t)(((hl + wave) * 256 + r * 16 + j * 2 + w) * 136);
            T.A(acc, M, w, wp, r, hp);
            AP(0);
            if (wave == 0) {
              M.begin<192, PACE2 & 1>(acc, pos0(1), t0 + 1);
              M.run<192>(acc, 1, NH1, 4, -1, [&](int i) { if (i == HP0 && wp == 0 && r > 0) T.pull(M.lane()); });
              T.B(w, wp, r, M.lane(), 0);
              M.drain();
            } else {
              M.begin<128, (PACE2 >> 1) & 1>(acn, pos0(2), t0 + 2);
              if (wp == 0 && r > 0) T.pull(M.lane());
              M.run<128>(acn, 1, NH2, 4, -1, nop);
              T.B(w, wp, r, M.lane(), 1);
              M.drain();
#pragma unroll
              for (int z = 0; z < 64; z++) asm volatile("mov.b32 %0, %1;" : "=f"(acc[z]) : "f"(acn[z]));
            }
            AP(2);
            T.C(wp, r, M.lane(), zero, [&] { if (EFIRST == 3 || (EFIRST == 2 && wave)) T.E(M, wave); });
            AP(3);
            if (wave == 1) break;
            M.run<192>(acc, NH1, 16, 1u << 7, 16 - LEAD1, [&](int i) { if (EFIRST < 3 && i == NH1) T.E(M, false); });
            M.end<192, true>(acc, 4, posa(1), au[0], au[1], t0 + 1);
            PROF_T(w, t0 + 1, 2);
          }
#pragma unroll
          for (int z = 0; z < 64; z++) asm volatile("mov.b32 %0, %1;" : "=f"(acn[z]) : "f"(acc[z]));
          if (EFIRST == 1) T.E(M, true);
          else if (!EFIRST) {
            M.ensure(M.iss<128, false>(acn, false));
            T.E(M, true);
          }
        } else {
          uint32_t pk[48], pk2[64];
          pack_relu<0, 48>(pk, acc);
          {
            float acc2[128];
            M.begin<256, (PACE2 >> 3) & 1>(acc2, pos0(4), t0 + 1);
            M.run<256>(acc2, 1, 16, 0x248, 16 - LEAD4, [&](int i) { ffn_stage(pk, i, M); });
            M.end<256, true>(acc2, 0, posa(4), au[0], au[1], t0 + 1);
            pack_relu<0, 64>(pk2, acc2);
            PROF_T(w, t0 + 1, 2);
          }
          M.begin<128, (PACE2 >> 4) & 1>(acn, pos0(5), t0 + 2);
          M.run<128>(acn, 1, 13, 0x1248, -1, [&](int i) { ffn_stage(pk2, i, M); });
        }
        {
          const int ks = ffn ? 56 : 16, pause = ks - (ffn ? LEAD5 : LEAD2), vfrom = ffn ? 99 : 7;
          const int imid = w ? pause : (ffn ? 20 : IPRE);
          auto check = [&](int i) {
            if (i >= vfrom) {
              if (i == 7) mbar_spin(sb + BAR_OWN + w * 8, hl >> 1);
              M.validate(true, &P.tm[TM_O16], 0, r * 128 + w * 64, wp, j, [] {});
            }
          };
          M.run<128>(acn, ffn ? 13 : NH2 + !EFIRST, imid, 0, -1, check);
          if (w) M.drain();
          float pre[64], rstd[2];
          presum(pre, xr, M.lane(), ffn ? 1.f : 0.f);
          own_rstd(w, wp, M.lane(), rstd);
          if (w) mbar_spin(SB + BAR_LEAD, M.tph);
          M.run<128>(acn, imid, ks, 0, 0, check);
          M.end<128, false>(acn, 2, 0, 0, 0, t0 + 2);
          epi_res(acn, pre, ffn ? rstd[0] * rstd[0] : 1.f, ffn ? rstd[1] * rstd[1] : 1.f, xr, M, wp);
          PROF_T(w, t0 + 2, 2);
        }
      }
    }
  }
}

typedef CUresult (*EncFn)(CUtensorMap*, CUtensorMapDataType, cuuint32_t, void*, const cuuint64_t*, const cuuint64_t*, const cuuint32_t*,
                          const cuuint32_t*, CUtensorMapInterleave, CUtensorMapSwizzle, CUtensorMapL2promotion, CUtensorMapFloatOOBfill);

void enc2(EncFn enc, CUtensorMap* tm, const void* p, uint64_t cols, uint64_t rows, uint32_t boxrows = 64, CUtensorMapL2promotion promo = APROMO) {
  cuuint64_t gd[2] = {cols, rows}, gs[1] = {cols * 2};
  cuuint32_t box[2] = {64, boxrows}, es[2] = {1, 1};
  enc(tm, CU_TENSOR_MAP_DATA_TYPE_BFLOAT16, 2, const_cast<void*>(p), gd, gs, box, es, CU_TENSOR_MAP_INTERLEAVE_NONE, CU_TENSOR_MAP_SWIZZLE_128B,
      promo, CU_TENSOR_MAP_FLOAT_OOB_FILL_NONE);
}
void enc4(EncFn enc, CUtensorMap* tm, const void* p, uint64_t K, uint64_t N, uint64_t d2, uint64_t s2, uint64_t d3, uint64_t s3, uint32_t na) {
  cuuint64_t gd[4] = {64, K, d2, d3}, gs[3] = {N * 2, s2, s3};
  cuuint32_t box[4] = {64, 64, na, 1}, es[4] = {1, 1, 1, 1};
  enc(tm, CU_TENSOR_MAP_DATA_TYPE_BFLOAT16, 4, const_cast<void*>(p), gd, gs, box, es, CU_TENSOR_MAP_INTERLEAVE_NONE, CU_TENSOR_MAP_SWIZZLE_128B,
      WPROMO, CU_TENSOR_MAP_FLOAT_OOB_FILL_NONE);
}

}

extern "C" void kernel_launch(void* const* d_in, const int* in_sizes, int n_in, void* d_out, int out_size) {
  static EncFn enc = nullptr;
  static Scratch* ps = nullptr;
  static void (*kernel)(Ptrs, Params) = mega_kernel<true>;
  if (!enc) {
    cudaDriverEntryPointQueryResult qr;
    cudaGetDriverEntryPoint("cuTensorMapEncodeTiled", (void**)&enc, cudaEnableDefault, &qr);
    int dev = 0, nsm = 0;
    cudaGetDevice(&dev);
    cudaDeviceGetAttribute(&nsm, cudaDevAttrMultiProcessorCount, dev);
    if (nsm != NMAIN + NAUX) kernel = mega_kernel<false>;
    cudaFuncSetAttribute(kernel, cudaFuncAttributeMaxDynamicSharedMemorySize, SMEM_BYTES);
    cudaGetSymbolAddress((void**)&ps, g_s);
  }
  Params P;
  Ptrs Q;
  Q.s = ps;
  void *p_h = ps->h, *p_x = ps->x;
  enc2(enc, &P.tm[TM_XIN], d_in[0], 2048, 1024, 64, XPROMO);
  enc2(enc, &P.tm[TM_X], d_out, 2048, 1024);
  enc2(enc, &P.tm[TM_XA], p_x, 2048, 1024);
  enc2(enc, &P.tm[TM_O], p_h, 3584, 2048);
  enc2(enc, &P.tm[TM_H], p_h, 3584, 2048);
  enc2(enc, &P.tm[TM_X16], d_out, 2048, 1024, 16);
  enc2(enc, &P.tm[TM_XA16], p_x, 2048, 1024, 16);
  enc2(enc, &P.tm[TM_O16], p_h, 3584, 2048, 16);
  enc4(enc, &P.tm[TM_WQKV], d_in[1], 1024, 3072, 3, 2048, 16, 128, 3);
  enc4(enc, &P.tm[TM_WO], d_in[2], 1024, 1024, 16, 128, 1, 128, 2);
  enc4(enc, &P.tm[TM_W1A], d_in[4], 1024, 3584, 56, 128, 1, 128, 4);
  enc4(enc, &P.tm[TM_W1B], d_in[4], 1024, 3584, 56, 128, 1, 128, 3);
  enc4(enc, &P.tm[TM_W2], d_in[6], 3584, 1024, 16, 128, 1, 128, 2);
  Q.out = (__nv_bfloat16*)d_out;
  Q.b1 = (const __nv_bfloat16*)d_in[5];
  Q.x = (const __nv_bfloat16*)d_in[0];
  Q.b2 = (const __nv_bfloat16*)d_in[7];
  kernel<<<NMAIN + NAUX, NTHREADS, SMEM_BYTES, cudaStreamPerThread>>>(Q, P);
}
```

```cpp
#include <cuda_runtime.h>
#include <cuda_bf16.h>
#include <cuda.h>
#include <stdint.h>

#define LEAD0 2
#define LEAD1 2
#define LEAD2 3
#define LEAD3 2
#define LEAD4 1
#define LEAD5 5
#define WPROMO CU_TENSOR_MAP_L2_PROMOTION_L2_128B
#define PLAN1 0x7f0000ull
#define PLAN2 0x400000003f0000ull
#define P0S 0x640096
#define PAS 0x430ff
#define PA0 0x70000a00050000ull
#define PB0 0x6000120009040000ull
#define PA2 0x600012000c8180ull
#define PB2 0x400030000a048180ull
#define PA4 0x70000e8180ull
#define PB4 0x60001a048180ull
#define PA6 0x7c8380ull
#define PB6 0x7c8380ull
#define LAGM 27
#define APROMO CU_TENSOR_MAP_L2_PROMOTION_L2_128B
#define PFT 500
#define HPM 0x3c
#define LSO 1
#define STATI 13
#define PACE2 0x1a
#define ST2 12
#define STB 3
#define PROBE 4
#define XO 0
#define FORD 0x01234567, 0x01234567, 0x01234567, 0x01234567, 0x04567123, 0x04567123, 0x04567123, 0x04765123
#define SIG0 14
#define STGX 2
#define STGM 3
#define NPRO 4
#define XPROMO CU_TENSOR_MAP_L2_PROMOTION_L2_256B
#define IPRE 7
#define FILLT 1
#define EARLYC 1
#define OWNDLY 0
#define EPW 0
#define CPF 5000
#define STG0 800
#define STG1 400
#define STGL (STG0 + 4 * STG1)
#define STGLW 0
#define STGLX 0
#define STARTC 0
#define FUN 4
#define XEF 0
#define BEF 0xff8
#define AEF 0xdb6
#define SEF 0
#define SDELAYO 1000
#define SDELAY 300
#define Q44 1
#define FG 8
#define NOI 1
#define EFIRST 0
#define STA 1
#define PG (Q44 ? 32 : 16)
#define NH1 6
#define NH2 3
namespace {

constexpr int NMAIN = 128, NAUX = 4, NTHREADS = 384;
constexpr uint32_t OFF_B = 0;
constexpr uint32_t OFF_A = 131072;
constexpr uint32_t OFF_VEC = 229376;
constexpr uint32_t OFF_BAR = 231424;
constexpr uint32_t OFF_RSTD = OFF_VEC + 512, OFF_MEAN = OFF_VEC + 1088, OFF_HOLD = OFF_VEC + 2032;
constexpr uint32_t SMEM_BYTES = OFF_BAR + 960;
constexpr uint32_t BAR_FULLA = OFF_BAR, BAR_FULLB = OFF_BAR + 96, BAR_OWN = OFF_BAR + 160, BAR_EPOCH = OFF_BAR + 176, BAR_AUG = OFF_BAR + 184, BAR_SPEC = OFF_BAR + 192,
                   BAR_EMPTYA = OFF_BAR + 288, BAR_STG = OFF_BAR + 384, BAR_SRV = OFF_BAR + 400, BAR_LEAD = OFF_BAR + 432, BAR_HALO = OFF_BAR + 440, BAR_STG2 = OFF_BAR + 456,
                   BAR_DUMMY3 = OFF_BAR + 472, BAR_EMPTYB = OFF_BAR + 480, BAR_STAT = OFF_BAR + 544, BAR_DUMMY = OFF_BAR + 560;
constexpr int NA = 6;
constexpr uint32_t SB = 1024;
constexpr uint32_t SPIN_LIMIT = 1u << 22;

enum { TM_XIN = 0, TM_X, TM_XA, TM_O, TM_H, TM_WQKV, TM_WO, TM_W1A, TM_W1B, TM_W2, TM_X16, TM_XA16, TM_O16, TM_COUNT };

struct Scratch;
struct Ptrs {
  Scratch* s;
  __nv_bfloat16* out;
  const __nv_bfloat16* b1;
  const __nv_bfloat16* x;
  const __nv_bfloat16* b2;
};
struct Params { CUtensorMap tm[TM_COUNT]; };

constexpr int NSTEP = 280, NSTEP_AUX = 128;
enum : uint32_t { F_STAMP = 1u << 28, F_GATH = 1u << 15, F_NEW = 1u << 16, F_AUG = 1u << 17, F_NOA = 1u << 18, E_HAND = 1u << 19, E_ATTN = 1u << 20, E_XPUB0 = 1u << 21,
                  E_WAIT = 1u << 22, E_REL = 1u << 23, E_KEEP = 1u << 24, E_PART1 = 1u << 25,
                  E_SIG = 1u << 27, E_RARE = F_NEW | E_KEEP | (0xfu << 20) | E_SIG };
constexpr uint32_t first_order(int j) {
  constexpr uint32_t t[8] = {FORD};
  uint32_t v = 0;
  for (int p = 0; p < 8; p++) v |= ((t[j] >> (28 - 4 * p)) & 15) << (4 * p);
  return v;
}
constexpr uint32_t own_rounds() { uint32_t v = 0; for (int j = 0; j < 8; j++) for (int p = 0; p < 8; p++) if (((first_order(j) >> (4 * p)) & 15) == j) v |= p << (4 * j); return v; }
constexpr uint32_t OWNP = own_rounds();
constexpr uint32_t first_round(int p) { uint32_t v = 0; for (int j = 0; j < 8; j++) v |= ((first_order(j) >> (4 * p)) & 15) << (4 * j); return v; }
constexpr uint32_t ROUND0 = first_round(0), ROUND1 = first_round(1);
__host__ __device__ constexpr int pos0(int kind) { return (P0S >> (4 * kind)) & 15; }
__host__ __device__ constexpr int posa(int kind) { return (PAS >> (4 * kind)) & 15; }
struct Sched { uint32_t v[9][NSTEP + 8]; };
constexpr Sched make_sched() {
  Sched T{};
  for (int j = 0; j < 8; j++) {
    int owner[16] = {};
    for (int i = 0; i < 16; i++) owner[i] = -100;
    int p = 0, g = 0;
    for (int t = 0; t < 12; t++) {
      const int kind = t % 6, ks = kind == 5 ? 56 : (kind == 2 ? 16 : 17);
      for (int i = 0; i < ks; i++) {
        const bool augs = ks == 17 && i == 16;
        const int na = (kind == 2 || kind == 5) ? 2 : (augs ? 1 : (kind == 4 ? 4 : 3));
        if (i == 0) p = pos0(kind);
        if (augs) p = posa(kind);
        if (p + na > 16) p = 0;
        int need = g - 8;
        for (int a = p; a < p + na; a++) { if (owner[a] > need) need = owner[a]; owner[a] = g; }
        uint32_t k = i, f = i == (t ? 0 : NPRO) ? F_NEW | (1u << 29) : 0;
        if (augs) { k = 0; f |= F_AUG; }
        else if (kind == 0 || kind == 3) {
          const int o = i - 2;
          if (t == 0) k = ((first_order(j) >> (4 * (i >> 1))) & 15) * 2 + (i & 1);
          else if (i < 2) { k = 2 * j + i; f |= F_NOA | (i == 0 ? E_XPUB0 : 0); }
          else { const int half = o >= 7; int u = o - 7 * half; { const int b = (XO & 3) == 0 ? 0 : ((XO & 3) == 1 ? (j & 4) ^ 4 : j & 4); u += u >= (j ^ b); u ^= b; } k = 2 * u + half; if (i == 6) f |= E_REL; }
          if (i == 11) f |= E_HAND;
          if (i == (t ? 11 : SIG0)) f |= E_SIG;
        } else if (kind == 1 || kind == 4) {
          if (kind == 1) f |= i == 3 ? E_HAND : (i == 8 ? E_HAND | E_KEEP : 0);
          if (kind == 1) f |= i == 13 ? E_REL : 0;
          else if (i == 4 || i == 7 || i == 10) f |= E_HAND;
        } else if (kind == 2) {
          f |= i == 0 ? E_WAIT : (i == 3 ? E_HAND : 0);
          if (i == 8) { k = 8 + j; f |= E_ATTN | E_KEEP | F_NOA; }
          if (i > 8) { const int b = (XO >> 2) == 0 ? 0 : ((XO >> 2) == 1 ? (j & 4) ^ 4 : j & 4); k = 8 + ((i - 9 + (i - 9 >= (j ^ b))) ^ b); }
          if (i == 11) f |= E_REL;
        } else {
          k = i < 24 ? (i / 3) * 7 + i % 3 : ((i - 24) / 4) * 7 + 3 + (i - 24) % 4;
          if (i == 4 || i == 7 || i == 10 || i == 13) f |= E_HAND;
          f |= i == 0 ? E_WAIT : (i == 24 ? E_WAIT | E_PART1 : 0);
        }
        if ((kind == 2 || kind == 5) && t < 11 && i == ks - (kind == 2 ? STA : STB)) f |= F_STAMP;
        if (((PACE2 >> kind) & 1) && i == ST2) f |= F_STAMP;
        if (i == 0 && t && ((PACE2 >> ((t - 1) % 6)) & 1)) f |= F_GATH;
        T.v[j][g] = p | ((g - need) << 5) | (k << 9) | f;
        p += na; g++;
      }
    }
    T.v[j][NSTEP] = F_NEW | F_NOA | E_XPUB0 | (2 * j << 9);
  }
  for (int w = 0; w < 2; w++) {
    int owner[14] = {};
    for (int i = 0; i < 14; i++) owner[i] = -100;
    for (int g = w, p = 0; g < NSTEP_AUX; g += 2) {
      const int na = g < 96 ? 3 : 4;
      if (p + na > 14) p = 0;
      int need = g - 8;
      for (int a = p; a < p + na; a++) { if (owner[a] > need) need = owner[a]; owner[a] = g; }
      T.v[8][g] = (p + 14 * w) | ((g - need) << 5) | ((g & 31) >> 1 << 9) | ((g & 30) && g - w != 8 ? 0 : F_NEW | (g - w == 64 ? 2u : 1u) << 29);
      p += na;
    }
  }
  return T;
}
__constant__ Sched c_sched = make_sched();
__device__ __forceinline__ int sched_k(uint32_t e) { return (e >> 3) & 0xfc0; }

struct Scratch {
  __nv_bfloat16 x[2048 * 1024];
  __nv_bfloat16 h[2048 * 3584];
  uint32_t epoch[160];
  uint8_t flags[16][2][64];
  uint32_t pace[8][64];
  uint32_t aug[2][32][1024];
  uint4 stats[4][512][8][2];
  uint4 halo[4][256][136];
};
__device__ __align__(1024) Scratch g_s;
#define PROF_T(w, t, i)
#define PRO(i)
#define LT(i)
#define CT(n)
#define ST(i)
#define AP(i)

__device__ __forceinline__ int work_id() {
  uint32_t smid;
  asm volatile("mov.u32 %0, %%smid;" : "=r"(smid));
  const int t = smid >> 1, u = t - 32, d = (u * 37) >> 8;
  int id = (t & 7) * 16 + (t >> 3) * 2;
  if (t >= 32) id = (1 + u - 7 * d) * 16 + (4 + d) * 2;
  if (t >= 60) id = t < 62 ? t * 2 + 8 : t * 2 - 116;
  return id + (smid & 1);
}

__device__ __forceinline__ uint32_t smem_u32(const void* p) { return (uint32_t)__cvta_generic_to_shared(p); }
__device__ __forceinline__ void mbar_init(uint32_t bar, int cnt) { asm volatile("mbarrier.init.shared::cta.b64 [%0], %1;" ::"r"(bar), "r"(cnt)); }
__device__ __forceinline__ void mbar_expect_tx(uint32_t bar, uint32_t bytes) { asm volatile("mbarrier.arrive.expect_tx.shared::cta.b64 _, [%0], %1;" ::"r"(bar), "r"(bytes) : "memory"); }
__device__ __forceinline__ void mbar_arrive(uint32_t bar, uint32_t cnt) { asm volatile("mbarrier.arrive.shared::cta.b64 _, [%0], %1;" ::"r"(bar), "r"(cnt) : "memory"); }
__device__ __forceinline__ void arrive_n(uint32_t bar, bool) { asm volatile("{\n.reg .pred p;\nelect.sync _|p, 0xffffffff;\n@p mbarrier.arrive.shared::cta.b64 _, [%0];\n}" ::"r"(bar) : "memory"); }
__device__ __forceinline__ void arrive_2(uint32_t b0, uint32_t b1, bool) {
  asm volatile("{\n.reg .pred p;\nelect.sync _|p, 0xffffffff;\n@p mbarrier.arrive.shared::cta.b64 _, [%0];\n@p mbarrier.arrive.shared::cta.b64 _, [%1];\n}" ::"r"(b0), "r"(b1) : "memory");
}
__device__ __forceinline__ void mbar_wait(uint32_t bar, uint32_t parity) {
  asm volatile(
      "{\n.reg .pred p;\n.reg .u32 c;\nmov.u32 c, 0;\n"
      "LAB_WAIT:\nmbarrier.try_wait.parity.shared::cta.b64 p, [%0], %1;\n@p bra.uni DONE;\n"
      "add.u32 c, c, 1;\nsetp.lt.u32 p, c, 4000000;\n@p bra.uni LAB_WAIT;\ntrap;\nDONE:\n}" ::"r"(bar), "r"(parity) : "memory");
}
__device__ __forceinline__ void mbar_spin(uint32_t bar, uint32_t parity) {
  asm volatile("{\n.reg .pred p;\nLAB_WAIT:\nmbarrier.try_wait.parity.shared::cta.b64 p, [%0], %1;\n@!p pmevent 7;\n@!p bra.uni LAB_WAIT;\n}" ::"r"(bar), "r"(parity) : "memory");
}
__device__ __forceinline__ void mbar_spin31(uint32_t bar, uint32_t ph) {
  asm volatile("{\n.reg .pred p;\n.reg .b64 s;\nmov.b64 s, {%1, %1};\nLAB_WAIT:\nmbarrier.try_wait.shared::cta.b64 p, [%0], s;\n@!p pmevent 7;\n@!p bra.uni LAB_WAIT;\n}" ::"r"(bar), "r"(ph) : "memory");
}
__device__ __forceinline__ bool elect_one() {
  uint32_t p;
  asm volatile("{\n.reg .pred P;\nelect.sync _|P, 0xffffffff;\nselp.u32 %0, 1, 0, P;\n}" : "=r"(p));
  return p != 0;
}
__device__ __forceinline__ bool mbar_test(uint32_t bar, uint32_t parity) {
  uint32_t ok;
  asm volatile("{\n.reg .pred p;\nmbarrier.test_wait.parity.shared::cta.b64 p, [%1], %2;\nselp.u32 %0, 1, 0, p;\n}" : "=r"(ok) : "r"(bar), "r"(parity) : "memory");
  return ok != 0;
}
__device__ __forceinline__ void tma_ld2(uint32_t dst, const CUtensorMap* tm, int c0, int c1, uint32_t bar) {
  asm volatile("cp.async.bulk.tensor.2d.shared::cluster.global.mbarrier::complete_tx::bytes [%0], [%1, {%3, %4}], [%2];" ::"r"(dst), "l"(tm), "r"(bar), "r"(c0), "r"(c1) : "memory");
}
__device__ __forceinline__ void tma_ld4(uint32_t dst, const CUtensorMap* tm, int c1, int c2, int c3, uint32_t bar, uint64_t pol = 0x1000000000000000ull) {
  asm volatile("cp.async.bulk.tensor.4d.shared::cluster.global.mbarrier::complete_tx::bytes.L2::cache_hint [%0], [%1, {%3, %4, %5, %6}], [%2], %7;" ::"r"(dst), "l"(tm), "r"(bar), "r"(0), "r"(c1), "r"(c2), "r"(c3), "l"(pol) : "memory");
}
__device__ __forceinline__ void tma_st2(const CUtensorMap* tm, int c0, int c1, uint32_t src) {
  asm volatile("cp.async.bulk.tensor.2d.global.shared::cta.bulk_group [%0, {%2, %3}], [%1];" ::"l"(tm), "r"(src), "r"(c0), "r"(c1) : "memory");
}
__device__ __forceinline__ void bulk_ld(uint32_t dst, const void* src, uint32_t bytes, uint32_t bar) {
  asm volatile("cp.async.bulk.shared::cluster.global.mbarrier::complete_tx::bytes [%0], [%1], %2, [%3];" ::"r"(dst), "l"(src), "r"(bytes), "r"(bar) : "memory");
}
__device__ __forceinline__ void e_arrive(uint32_t bar, uint32_t cnt) {
  if (cnt == 1) asm volatile("{\n.reg .pred p;\nelect.sync _|p, 0xffffffff;\n@p mbarrier.arrive.shared::cta.b64 _, [%0];\n}" ::"r"(bar) : "memory");
  else asm volatile("{\n.reg .pred p;\nelect.sync _|p, 0xffffffff;\n@p mbarrier.arrive.shared::cta.b64 _, [%0], %1;\n}" ::"r"(bar), "r"(cnt) : "memory");
}
template <int BYTES = 8192> __device__ __forceinline__ void e_load(uint32_t dst, const CUtensorMap* tm, int c0, int c1, uint32_t bar, uint64_t pol = 0x1000000000000000ull) {
  asm volatile("{\n.reg .pred p;\nelect.sync _|p, 0xffffffff;\n@p mbarrier.arrive.expect_tx.shared::cta.b64 _, [%2], %5;\n"
               "@p cp.async.bulk.tensor.2d.shared::cluster.global.mbarrier::complete_tx::bytes.L2::cache_hint [%0], [%1, {%3, %4}], [%2], %6;\n}"
               ::"r"(dst), "l"(tm), "r"(bar), "r"(c0), "r"(c1), "n"(BYTES), "l"(pol) : "memory");
}
__device__ __forceinline__ void e_store(const CUtensorMap* tm, int c0, int c1, uint32_t src) {
  asm volatile("{\n.reg .pred p;\nfence.proxy.async.shared::cta;\nelect.sync _|p, 0xffffffff;\n"
               "@p cp.async.bulk.tensor.2d.global.shared::cta.bulk_group [%0, {%2, %3}], [%1];\ncp.async.bulk.commit_group;\n}"
               ::"l"(tm), "r"(src), "r"(c0), "r"(c1) : "memory");
}
__device__ __forceinline__ void bulk_commit() { asm volatile("cp.async.bulk.commit_group;" ::: "memory"); }
template <int N> __device__ __forceinline__ void bulk_wait_read() { asm volatile("cp.async.bulk.wait_group.read %0;" ::"n"(N) : "memory"); }
__device__ __forceinline__ void bulk_wait_all() { asm volatile("cp.async.bulk.wait_group 0;" ::: "memory"); }
__device__ __forceinline__ void fence_async_smem() { asm volatile("fence.proxy.async.shared::cta;" ::: "memory"); }
__device__ __forceinline__ void wg_fence() { asm volatile("wgmma.fence.sync.aligned;" ::: "memory"); }
__device__ __forceinline__ void wg_commit() { asm volatile("wgmma.commit_group.sync.aligned;" ::: "memory"); }
template <int N> __device__ __forceinline__ void wg_wait() { asm volatile("wgmma.wait_group.sync.aligned %0;" ::"n"(N) : "memory"); }
__device__ __forceinline__ void wg_bar(int w) { asm volatile("bar.sync %0, 128;" ::"r"(w + 1) : "memory"); }
__device__ __forceinline__ uint32_t ld_acquire(const uint32_t* p) { uint32_t v; asm volatile("ld.acquire.gpu.global.u32 %0, [%1];" : "=r"(v) : "l"(p) : "memory"); return v; }
__device__ __forceinline__ uint4 ld_relaxed4(const uint32_t* p) {
  uint4 v; asm volatile("ld.relaxed.gpu.global.v4.u32 {%0,%1,%2,%3}, [%4];" : "=r"(v.x), "=r"(v.y), "=r"(v.z), "=r"(v.w) : "l"(p) : "memory"); return v;
}
__device__ __forceinline__ void st_release8(uint8_t* p, uint32_t v) { asm volatile("st.release.gpu.global.u8 [%0], %1;" ::"l"(p), "r"(v) : "memory"); }
__device__ __forceinline__ uint32_t ld_relaxed(const uint32_t* p) { uint32_t v; asm volatile("ld.relaxed.gpu.global.u32 %0, [%1];" : "=r"(v) : "l"(p) : "memory"); return v; }
__device__ __forceinline__ void st_release(uint32_t* p, uint32_t v) { asm volatile("st.release.gpu.global.u32 [%0], %1;" ::"l"(p), "r"(v) : "memory"); }
__device__ __forceinline__ void st_pkt(uint4* p, uint32_t a, uint32_t b, uint32_t c, uint32_t d) {
  asm volatile("{\n.reg .b64 lo, hi;\n.reg .b128 v;\nmov.b64 lo, {%1, %2};\nmov.b64 hi, {%3, %4};\nmov.b128 v, {lo, hi};\nst.relaxed.gpu.global.b128 [%0], v;\n}" ::"l"(p), "r"(a), "r"(b), "r"(c), "r"(d) : "memory");
}
__device__ __forceinline__ uint4 ld_pkt(const uint4* p) {
  uint4 r;
  asm volatile("{\n.reg .b64 lo, hi;\n.reg .b128 v;\nld.relaxed.gpu.global.b128 v, [%4];\nmov.b128 {lo, hi}, v;\nmov.b64 {%0, %1}, lo;\nmov.b64 {%2, %3}, hi;\n}" : "=r"(r.x), "=r"(r.y), "=r"(r.z), "=r"(r.w) : "l"(p) : "memory");
  return r;
}
__device__ __forceinline__ uint32_t pack_bf16(float lo, float hi) { uint32_t d; asm("cvt.rn.bf16x2.f32 %0, %1, %2;" : "=r"(d) : "f"(hi), "f"(lo)); return d; }
__device__ __forceinline__ float ex2(float x) { float y; asm("ex2.approx.ftz.f32 %0, %1;" : "=f"(y) : "f"(x)); return y; }
__device__ __forceinline__ float rsq(float x) { float y; asm("rsqrt.approx.ftz.f32 %0, %1;" : "=f"(y) : "f"(x)); return y; }
__device__ __forceinline__ float rcp(float x) { float y; asm("rcp.approx.ftz.f32 %0, %1;" : "=f"(y) : "f"(x)); return y; }
__device__ __forceinline__ float bf_lo(uint32_t v) { return __uint_as_float(v << 16); }
__device__ __forceinline__ float bf_hi(uint32_t v) { return __uint_as_float(v & 0xffff0000u); }
__device__ __forceinline__ void stsm4(uint32_t addr, uint32_t a, uint32_t b, uint32_t c, uint32_t d) {
  asm volatile("stmatrix.sync.aligned.m8n8.x4.shared.b16 [%0], {%1, %2, %3, %4};" ::"r"(addr), "r"(a), "r"(b), "r"(c), "r"(d) : "memory");
}
__device__ __forceinline__ uint32_t movm(uint32_t a) { uint32_t d; asm volatile("movmatrix.sync.aligned.m8n8.trans.b16 %0, %1;" : "=r"(d) : "r"(a)); return d; }
__device__ __forceinline__ void mma16(float (&c)[4], uint32_t a0, uint32_t a1, uint32_t a2, uint32_t a3, uint32_t b0, uint32_t b1) {
  asm volatile("mma.sync.aligned.m16n8k16.row.col.f32.bf16.bf16.f32 {%0,%1,%2,%3}, {%4,%5,%6,%7}, {%8,%9}, {%0,%1,%2,%3};"
               : "+f"(c[0]), "+f"(c[1]), "+f"(c[2]), "+f"(c[3]) : "r"(a0), "r"(a1), "r"(a2), "r"(a3), "r"(b0), "r"(b1));
}
__device__ __forceinline__ void mma8(float (&c)[4], uint32_t a0, uint32_t a1, uint32_t b0) {
  asm volatile("mma.sync.aligned.m16n8k8.row.col.f32.bf16.bf16.f32 {%0,%1,%2,%3}, {%4,%5}, {%6}, {%0,%1,%2,%3};"
               : "+f"(c[0]), "+f"(c[1]), "+f"(c[2]), "+f"(c[3]) : "r"(a0), "r"(a1), "r"(b0));
}
__device__ __forceinline__ void sts128(uint32_t a, uint32_t x, uint32_t y, uint32_t z, uint32_t w) {
  asm volatile("st.shared.v4.b32 [%0], {%1,%2,%3,%4};" ::"r"(a), "r"(x), "r"(y), "r"(z), "r"(w) : "memory");
}
__device__ __forceinline__ float2 lds64(uint32_t a) { float2 v; asm volatile("ld.shared.v2.f32 {%0,%1}, [%2];" : "=f"(v.x), "=f"(v.y) : "r"(a)); return v; }
__device__ __forceinline__ float4 lds128(uint32_t a) { float4 v; asm volatile("ld.shared.v4.f32 {%0,%1,%2,%3}, [%4];" : "=f"(v.x), "=f"(v.y), "=f"(v.z), "=f"(v.w) : "r"(a)); return v; }
__device__ __forceinline__ uint32_t lds32(uint32_t a) { uint32_t v; asm volatile("ld.shared.b32 %0, [%1];" : "=r"(v) : "r"(a)); return v; }
constexpr uint32_t PA1 = 0x80000000u / NA + 1, G1 = 8 + (1u << 28);
constexpr uint32_t DA0 = ((SB + OFF_A) >> 4) | (1u << 16), DB0 = ((SB + OFF_B) >> 4) | (512u << 16);
template <int S> __device__ __forceinline__ uint2 wgmma_first128(float (&d)[S], uint32_t da, uint32_t& db, uint32_t h0, uint32_t h1, uint32_t one, uint32_t b0, uint32_t p0, uint32_t b1, uint32_t p1) {
  uint2 ok;
  asm volatile("{\n.reg .b64 a, b, s;\n.reg .b32 t, u;\n.reg .pred p, q;\nwgmma.fence.sync.aligned;\n"
    "mov.b32 t, %67;\n"
    "mov.b64 a, {t, %68};\nmov.b64 b, {%66, %69};\n"
    "wgmma.mma_async.sync.aligned.m64n128k16.f32.bf16.bf16 "
    "{%2, %3, %4, %5, %6, %7, %8, %9, %10, %11, %12, %13, %14, %15, %16, %17, %18, %19, %20, %21, %22, %23, %24, %25, %26, %27, %28, %29, %30, %31, %32, %33, %34, %35, %36, %37, %38, %39, %40, %41, %42, %43, %44, %45, %46, %47, %48, %49, %50, %51, %52, %53, %54, %55, %56, %57, %58, %59, %60, %61, %62, %63, %64, %65}, "
    "a, b, 0, 1, 1, 0, 1;\n"
    "mad.lo.u32 t, %70, 2, t;\nmad.lo.u32 %66, %70, 128, %66;\n"
    "mov.b64 a, {t, %68};\nmov.b64 b, {%66, %69};\n"
    "wgmma.mma_async.sync.aligned.m64n128k16.f32.bf16.bf16 "
    "{%2, %3, %4, %5, %6, %7, %8, %9, %10, %11, %12, %13, %14, %15, %16, %17, %18, %19, %20, %21, %22, %23, %24, %25, %26, %27, %28, %29, %30, %31, %32, %33, %34, %35, %36, %37, %38, %39, %40, %41, %42, %43, %44, %45, %46, %47, %48, %49, %50, %51, %52, %53, %54, %55, %56, %57, %58, %59, %60, %61, %62, %63, %64, %65}, "
    "a, b, 1, 1, 1, 0, 1;\n"
    "mad.lo.u32 t, %70, 2, t;\nmad.lo.u32 %66, %70, 128, %66;\n"
    "mov.b64 a, {t, %68};\nmov.b64 b, {%66, %69};\n"
    "wgmma.mma_async.sync.aligned.m64n128k16.f32.bf16.bf16 "
    "{%2, %3, %4, %5, %6, %7, %8, %9, %10, %11, %12, %13, %14, %15, %16, %17, %18, %19, %20, %21, %22, %23, %24, %25, %26, %27, %28, %29, %30, %31, %32, %33, %34, %35, %36, %37, %38, %39, %40, %41, %42, %43, %44, %45, %46, %47, %48, %49, %50, %51, %52, %53, %54, %55, %56, %57, %58, %59, %60, %61, %62, %63, %64, %65}, "
    "a, b, 1, 1, 1, 0, 1;\n"
    "mov.b64 s, {%72, %72};\nmbarrier.test_wait.shared::cta.b64 p, [%71], s;\nmov.b64 s, {%74, %74};\nmbarrier.test_wait.shared::cta.b64 q, [%73], s;\n"
    "mad.lo.u32 t, %70, 2, t;\nmad.lo.u32 %66, %70, 128, %66;\n"
    "mov.b64 a, {t, %68};\nmov.b64 b, {%66, %69};\n"
    "wgmma.mma_async.sync.aligned.m64n128k16.f32.bf16.bf16 "
    "{%2, %3, %4, %5, %6, %7, %8, %9, %10, %11, %12, %13, %14, %15, %16, %17, %18, %19, %20, %21, %22, %23, %24, %25, %26, %27, %28, %29, %30, %31, %32, %33, %34, %35, %36, %37, %38, %39, %40, %41, %42, %43, %44, %45, %46, %47, %48, %49, %50, %51, %52, %53, %54, %55, %56, %57, %58, %59, %60, %61, %62, %63, %64, %65}, "
    "a, b, 1, 1, 1, 0, 1;\n"
    "wgmma.commit_group.sync.aligned;\nselp.u32 %0, 1, 0, p;\nselp.u32 %1, 1, 0, q;\n}"
    : "=r"(ok.x), "=r"(ok.y), "=f"(d[0]), "=f"(d[1]), "=f"(d[2]), "=f"(d[3]), "=f"(d[4]), "=f"(d[5]), "=f"(d[6]), "=f"(d[7]), "=f"(d[8]), "=f"(d[9]), "=f"(d[10]), "=f"(d[11]), "=f"(d[12]), "=f"(d[13]), "=f"(d[14]), "=f"(d[15]), "=f"(d[16]), "=f"(d[17]), "=f"(d[18]), "=f"(d[19]), "=f"(d[20]), "=f"(d[21]), "=f"(d[22]), "=f"(d[23]), "=f"(d[24]), "=f"(d[25]), "=f"(d[26]), "=f"(d[27]), "=f"(d[28]), "=f"(d[29]), "=f"(d[30]), "=f"(d[31]), "=f"(d[32]), "=f"(d[33]), "=f"(d[34]), "=f"(d[35]), "=f"(d[36]), "=f"(d[37]), "=f"(d[38]), "=f"(d[39]), "=f"(d[40]), "=f"(d[41]), "=f"(d[42]), "=f"(d[43]), "=f"(d[44]), "=f"(d[45]), "=f"(d[46]), "=f"(d[47]), "=f"(d[48]), "=f"(d[49]), "=f"(d[50]), "=f"(d[51]), "=f"(d[52]), "=f"(d[53]), "=f"(d[54]), "=f"(d[55]), "=f"(d[56]), "=f"(d[57]), "=f"(d[58]), "=f"(d[59]), "=f"(d[60]), "=f"(d[61]), "=f"(d[62]), "=f"(d[63]), "+r"(db)
    : "r"(da), "r"(h0), "r"(h1), "r"(one), "r"(b0), "r"(p0), "r"(b1), "r"(p1) : "memory");
  return ok;
}
template <int S> __device__ __forceinline__ uint2 wgmma_step128(float (&d)[S], uint32_t da, uint32_t& db, uint32_t h0, uint32_t h1, uint32_t one, uint32_t b0, uint32_t p0, uint32_t b1, uint32_t p1) {
  uint2 ok;
  asm volatile("{\n.reg .b64 a, b, s;\n.reg .b32 t, u;\n.reg .pred p, q;\nwgmma.fence.sync.aligned;\n"
    "mov.b32 t, %67;\n"
    "mov.b64 a, {t, %68};\nmov.b64 b, {%66, %69};\n"
    "wgmma.mma_async.sync.aligned.m64n128k16.f32.bf16.bf16 "
    "{%2, %3, %4, %5, %6, %7, %8, %9, %10, %11, %12, %13, %14, %15, %16, %17, %18, %19, %20, %21, %22, %23, %24, %25, %26, %27, %28, %29, %30, %31, %32, %33, %34, %35, %36, %37, %38, %39, %40, %41, %42, %43, %44, %45, %46, %47, %48, %49, %50, %51, %52, %53, %54, %55, %56, %57, %58, %59, %60, %61, %62, %63, %64, %65}, "
    "a, b, 1, 1, 1, 0, 1;\n"
    "mad.lo.u32 t, %70, 2, t;\nmad.lo.u32 %66, %70, 128, %66;\n"
    "mov.b64 a, {t, %68};\nmov.b64 b, {%66, %69};\n"
    "wgmma.mma_async.sync.aligned.m64n128k16.f32.bf16.bf16 "
    "{%2, %3, %4, %5, %6, %7, %8, %9, %10, %11, %12, %13, %14, %15, %16, %17, %18, %19, %20, %21, %22, %23, %24, %25, %26, %27, %28, %29, %30, %31, %32, %33, %34, %35, %36, %37, %38, %39, %40, %41, %42, %43, %44, %45, %46, %47, %48, %49, %50, %51, %52, %53, %54, %55, %56, %57, %58, %59, %60, %61, %62, %63, %64, %65}, "
    "a, b, 1, 1, 1, 0, 1;\n"
    "mad.lo.u32 t, %70, 2, t;\nmad.lo.u32 %66, %70, 128, %66;\n"
    "mov.b64 a, {t, %68};\nmov.b64 b, {%66, %69};\n"
    "wgmma.mma_async.sync.aligned.m64n128k16.f32.bf16.bf16 "
    "{%2, %3, %4, %5, %6, %7, %8, %9, %10, %11, %12, %13, %14, %15, %16, %17, %18, %19, %20, %21, %22, %23, %24, %25, %26, %27, %28, %29, %30, %31, %32, %33, %34, %35, %36, %37, %38, %39, %40, %41, %42, %43, %44, %45, %46, %47, %48, %49, %50, %51, %52, %53, %54, %55, %56, %57, %58, %59, %60, %61, %62, %63, %64, %65}, "
    "a, b, 1, 1, 1, 0, 1;\n"
    "mov.b64 s, {%72, %72};\nmbarrier.test_wait.shared::cta.b64 p, [%71], s;\nmov.b64 s, {%74, %74};\nmbarrier.test_wait.shared::cta.b64 q, [%73], s;\n"
    "mad.lo.u32 t, %70, 2, t;\nmad.lo.u32 %66, %70, 128, %66;\n"
    "mov.b64 a, {t, %68};\nmov.b64 b, {%66, %69};\n"
    "wgmma.mma_async.sync.aligned.m64n128k16.f32.bf16.bf16 "
    "{%2, %3, %4, %5, %6, %7, %8, %9, %10, %11, %12, %13, %14, %15, %16, %17, %18, %19, %20, %21, %22, %23, %24, %25, %26, %27, %28, %29, %30, %31, %32, %33, %34, %35, %36, %37, %38, %39, %40, %41, %42, %43, %44, %45, %46, %47, %48, %49, %50, %51, %52, %53, %54, %55, %56, %57, %58, %59, %60, %61, %62, %63, %64, %65}, "
    "a, b, 1, 1, 1, 0, 1;\n"
    "wgmma.commit_group.sync.aligned;\nselp.u32 %0, 1, 0, p;\nselp.u32 %1, 1, 0, q;\n}"
    : "=r"(ok.x), "=r"(ok.y), "+f"(d[0]), "+f"(d[1]), "+f"(d[2]), "+f"(d[3]), "+f"(d[4]), "+f"(d[5]), "+f"(d[6]), "+f"(d[7]), "+f"(d[8]), "+f"(d[9]), "+f"(d[10]), "+f"(d[11]), "+f"(d[12]), "+f"(d[13]), "+f"(d[14]), "+f"(d[15]), "+f"(d[16]), "+f"(d[17]), "+f"(d[18]), "+f"(d[19]), "+f"(d[20]), "+f"(d[21]), "+f"(d[22]), "+f"(d[23]), "+f"(d[24]), "+f"(d[25]), "+f"(d[26]), "+f"(d[27]), "+f"(d[28]), "+f"(d[29]), "+f"(d[30]), "+f"(d[31]), "+f"(d[32]), "+f"(d[33]), "+f"(d[34]), "+f"(d[35]), "+f"(d[36]), "+f"(d[37]), "+f"(d[38]), "+f"(d[39]), "+f"(d[40]), "+f"(d[41]), "+f"(d[42]), "+f"(d[43]), "+f"(d[44]), "+f"(d[45]), "+f"(d[46]), "+f"(d[47]), "+f"(d[48]), "+f"(d[49]), "+f"(d[50]), "+f"(d[51]), "+f"(d[52]), "+f"(d[53]), "+f"(d[54]), "+f"(d[55]), "+f"(d[56]), "+f"(d[57]), "+f"(d[58]), "+f"(d[59]), "+f"(d[60]), "+f"(d[61]), "+f"(d[62]), "+f"(d[63]), "+r"(db)
    : "r"(da), "r"(h0), "r"(h1), "r"(one), "r"(b0), "r"(p0), "r"(b1), "r"(p1) : "memory");
  return ok;
}
template <int S> __device__ __forceinline__ uint2 wgmma_first192(float (&d)[S], uint32_t da, uint32_t& db, uint32_t h0, uint32_t h1, uint32_t one, uint32_t b0, uint32_t p0, uint32_t b1, uint32_t p1) {
  uint2 ok;
  asm volatile("{\n.reg .b64 a, b, s;\n.reg .b32 t, u;\n.reg .pred p, q;\nwgmma.fence.sync.aligned;\n"
    "mov.b32 t, %99;\n"
    "mov.b64 a, {t, %100};\nmov.b64 b, {%98, %101};\n"
    "wgmma.mma_async.sync.aligned.m64n192k16.f32.bf16.bf16 "
    "{%2, %3, %4, %5, %6, %7, %8, %9, %10, %11, %12, %13, %14, %15, %16, %17, %18, %19, %20, %21, %22, %23, %24, %25, %26, %27, %28, %29, %30, %31, %32, %33, %34, %35, %36, %37, %38, %39, %40, %41, %42, %43, %44, %45, %46, %47, %48, %49, %50, %51, %52, %53, %54, %55, %56, %57, %58, %59, %60, %61, %62, %63, %64, %65, %66, %67, %68, %69, %70, %71, %72, %73, %74, %75, %76, %77, %78, %79, %80, %81, %82, %83, %84, %85, %86, %87, %88, %89, %90, %91, %92, %93, %94, %95, %96, %97}, "
    "a, b, 0, 1, 1, 0, 1;\n"
    "mad.lo.u32 t, %102, 2, t;\nmad.lo.u32 %98, %102, 128, %98;\n"
    "mov.b64 a, {t, %100};\nmov.b64 b, {%98, %101};\n"
    "wgmma.mma_async.sync.aligned.m64n192k16.f32.bf16.bf16 "
    "{%2, %3, %4, %5, %6, %7, %8, %9, %10, %11, %12, %13, %14, %15, %16, %17, %18, %19, %20, %21, %22, %23, %24, %25, %26, %27, %28, %29, %30, %31, %32, %33, %34, %35, %36, %37, %38, %39, %40, %41, %42, %43, %44, %45, %46, %47, %48, %49, %50, %51, %52, %53, %54, %55, %56, %57, %58, %59, %60, %61, %62, %63, %64, %65, %66, %67, %68, %69, %70, %71, %72, %73, %74, %75, %76, %77, %78, %79, %80, %81, %82, %83, %84, %85, %86, %87, %88, %89, %90, %91, %92, %93, %94, %95, %96, %97}, "
    "a, b, 1, 1, 1, 0, 1;\n"
    "mad.lo.u32 t, %102, 2, t;\nmad.lo.u32 %98, %102, 128, %98;\n"
    "mov.b64 a, {t, %100};\nmov.b64 b, {%98, %101};\n"
    "wgmma.mma_async.sync.aligned.m64n192k16.f32.bf16.bf16 "
    "{%2, %3, %4, %5, %6, %7, %8, %9, %10, %11, %12, %13, %14, %15, %16, %17, %18, %19, %20, %21, %22, %23, %24, %25, %26, %27, %28, %29, %30, %31, %32, %33, %34, %35, %36, %37, %38, %39, %40, %41, %42, %43, %44, %45, %46, %47, %48, %49, %50, %51, %52, %53, %54, %55, %56, %57, %58, %59, %60, %61, %62, %63, %64, %65, %66, %67, %68, %69, %70, %71, %72, %73, %74, %75, %76, %77, %78, %79, %80, %81, %82, %83, %84, %85, %86, %87, %88, %89, %90, %91, %92, %93, %94, %95, %96, %97}, "
    "a, b, 1, 1, 1, 0, 1;\n"
    "mov.b64 s, {%104, %104};\nmbarrier.test_wait.shared::cta.b64 p, [%103], s;\nmov.b64 s, {%106, %106};\nmbarrier.test_wait.shared::cta.b64 q, [%105], s;\n"
    "mad.lo.u32 t, %102, 2, t;\nmad.lo.u32 %98, %102, 128, %98;\n"
    "mov.b64 a, {t, %100};\nmov.b64 b, {%98, %101};\n"
    "wgmma.mma_async.sync.aligned.m64n192k16.f32.bf16.bf16 "
    "{%2, %3, %4, %5, %6, %7, %8, %9, %10, %11, %12, %13, %14, %15, %16, %17, %18, %19, %20, %21, %22, %23, %24, %25, %26, %27, %28, %29, %30, %31, %32, %33, %34, %35, %36, %37, %38, %39, %40, %41, %42, %43, %44, %45, %46, %47, %48, %49, %50, %51, %52, %53, %54, %55, %56, %57, %58, %59, %60, %61, %62, %63, %64, %65, %66, %67, %68, %69, %70, %71, %72, %73, %74, %75, %76, %77, %78, %79, %80, %81, %82, %83, %84, %85, %86, %87, %88, %89, %90, %91, %92, %93, %94, %95, %96, %97}, "
    "a, b, 1, 1, 1, 0, 1;\n"
    "wgmma.commit_group.sync.aligned;\nselp.u32 %0, 1, 0, p;\nselp.u32 %1, 1, 0, q;\n}"
    : "=r"(ok.x), "=r"(ok.y), "=f"(d[0]), "=f"(d[1]), "=f"(d[2]), "=f"(d[3]), "=f"(d[4]), "=f"(d[5]), "=f"(d[6]), "=f"(d[7]), "=f"(d[8]), "=f"(d[9]), "=f"(d[10]), "=f"(d[11]), "=f"(d[12]), "=f"(d[13]), "=f"(d[14]), "=f"(d[15]), "=f"(d[16]), "=f"(d[17]), "=f"(d[18]), "=f"(d[19]), "=f"(d[20]), "=f"(d[21]), "=f"(d[22]), "=f"(d[23]), "=f"(d[24]), "=f"(d[25]), "=f"(d[26]), "=f"(d[27]), "=f"(d[28]), "=f"(d[29]), "=f"(d[30]), "=f"(d[31]), "=f"(d[32]), "=f"(d[33]), "=f"(d[34]), "=f"(d[35]), "=f"(d[36]), "=f"(d[37]), "=f"(d[38]), "=f"(d[39]), "=f"(d[40]), "=f"(d[41]), "=f"(d[42]), "=f"(d[43]), "=f"(d[44]), "=f"(d[45]), "=f"(d[46]), "=f"(d[47]), "=f"(d[48]), "=f"(d[49]), "=f"(d[50]), "=f"(d[51]), "=f"(d[52]), "=f"(d[53]), "=f"(d[54]), "=f"(d[55]), "=f"(d[56]), "=f"(d[57]), "=f"(d[58]), "=f"(d[59]), "=f"(d[60]), "=f"(d[61]), "=f"(d[62]), "=f"(d[63]), "=f"(d[64]), "=f"(d[65]), "=f"(d[66]), "=f"(d[67]), "=f"(d[68]), "=f"(d[69]), "=f"(d[70]), "=f"(d[71]), "=f"(d[72]), "=f"(d[73]), "=f"(d[74]), "=f"(d[75]), "=f"(d[76]), "=f"(d[77]), "=f"(d[78]), "=f"(d[79]), "=f"(d[80]), "=f"(d[81]), "=f"(d[82]), "=f"(d[83]), "=f"(d[84]), "=f"(d[85]), "=f"(d[86]), "=f"(d[87]), "=f"(d[88]), "=f"(d[89]), "=f"(d[90]), "=f"(d[91]), "=f"(d[92]), "=f"(d[93]), "=f"(d[94]), "=f"(d[95]), "+r"(db)
    : "r"(da), "r"(h0), "r"(h1), "r"(one), "r"(b0), "r"(p0), "r"(b1), "r"(p1) : "memory");
  return ok;
}
template <int S> __device__ __forceinline__ uint2 wgmma_step192(float (&d)[S], uint32_t da, uint32_t& db, uint32_t h0, uint32_t h1, uint32_t one, uint32_t b0, uint32_t p0, uint32_t b1, uint32_t p1) {
  uint2 ok;
  asm volatile("{\n.reg .b64 a, b, s;\n.reg .b32 t, u;\n.reg .pred p, q;\nwgmma.fence.sync.aligned;\n"
    "mov.b32 t, %99;\n"
    "mov.b64 a, {t, %100};\nmov.b64 b, {%98, %101};\n"
    "wgmma.mma_async.sync.aligned.m64n192k16.f32.bf16.bf16 "
    "{%2, %3, %4, %5, %6, %7, %8, %9, %10, %11, %12, %13, %14, %15, %16, %17, %18, %19, %20, %21, %22, %23, %24, %25, %26, %27, %28, %29, %30, %31, %32, %33, %34, %35, %36, %37, %38, %39, %40, %41, %42, %43, %44, %45, %46, %47, %48, %49, %50, %51, %52, %53, %54, %55, %56, %57, %58, %59, %60, %61, %62, %63, %64, %65, %66, %67, %68, %69, %70, %71, %72, %73, %74, %75, %76, %77, %78, %79, %80, %81, %82, %83, %84, %85, %86, %87, %88, %89, %90, %91, %92, %93, %94, %95, %96, %97}, "
    "a, b, 1, 1, 1, 0, 1;\n"
    "mad.lo.u32 t, %102, 2, t;\nmad.lo.u32 %98, %102, 128, %98;\n"
    "mov.b64 a, {t, %100};\nmov.b64 b, {%98, %101};\n"
    "wgmma.mma_async.sync.aligned.m64n192k16.f32.bf16.bf16 "
    "{%2, %3, %4, %5, %6, %7, %8, %9, %10, %11, %12, %13, %14, %15, %16, %17, %18, %19, %20, %21, %22, %23, %24, %25, %26, %27, %28, %29, %30, %31, %32, %33, %34, %35, %36, %37, %38, %39, %40, %41, %42, %43, %44, %45, %46, %47, %48, %49, %50, %51, %52, %53, %54, %55, %56, %57, %58, %59, %60, %61, %62, %63, %64, %65, %66, %67, %68, %69, %70, %71, %72, %73, %74, %75, %76, %77, %78, %79, %80, %81, %82, %83, %84, %85, %86, %87, %88, %89, %90, %91, %92, %93, %94, %95, %96, %97}, "
    "a, b, 1, 1, 1, 0, 1;\n"
    "mad.lo.u32 t, %102, 2, t;\nmad.lo.u32 %98, %102, 128, %98;\n"
    "mov.b64 a, {t, %100};\nmov.b64 b, {%98, %101};\n"
    "wgmma.mma_async.sync.aligned.m64n192k16.f32.bf16.bf16 "
    "{%2, %3, %4, %5, %6, %7, %8, %9, %10, %11, %12, %13, %14, %15, %16, %17, %18, %19, %20, %21, %22, %23, %24, %25, %26, %27, %28, %29, %30, %31, %32, %33, %34, %35, %36, %37, %38, %39, %40, %41, %42, %43, %44, %45, %46, %47, %48, %49, %50, %51, %52, %53, %54, %55, %56, %57, %58, %59, %60, %61, %62, %63, %64, %65, %66, %67, %68, %69, %70, %71, %72, %73, %74, %75, %76, %77, %78, %79, %80, %81, %82, %83, %84, %85, %86, %87, %88, %89, %90, %91, %92, %93, %94, %95, %96, %97}, "
    "a, b, 1, 1, 1, 0, 1;\n"
    "mov.b64 s, {%104, %104};\nmbarrier.test_wait.shared::cta.b64 p, [%103], s;\nmov.b64 s, {%106, %106};\nmbarrier.test_wait.shared::cta.b64 q, [%105], s;\n"
    "mad.lo.u32 t, %102, 2, t;\nmad.lo.u32 %98, %102, 128, %98;\n"
    "mov.b64 a, {t, %100};\nmov.b64 b, {%98, %101};\n"
    "wgmma.mma_async.sync.aligned.m64n192k16.f32.bf16.bf16 "
    "{%2, %3, %4, %5, %6, %7, %8, %9, %10, %11, %12, %13, %14, %15, %16, %17, %18, %19, %20, %21, %22, %23, %24, %25, %26, %27, %28, %29, %30, %31, %32, %33, %34, %35, %36, %37, %38, %39, %40, %41, %42, %43, %44, %45, %46, %47, %48, %49, %50, %51, %52, %53, %54, %55, %56, %57, %58, %59, %60, %61, %62, %63, %64, %65, %66, %67, %68, %69, %70, %71, %72, %73, %74, %75, %76, %77, %78, %79, %80, %81, %82, %83, %84, %85, %86, %87, %88, %89, %90, %91, %92, %93, %94, %95, %96, %97}, "
    "a, b, 1, 1, 1, 0, 1;\n"
    "wgmma.commit_group.sync.aligned;\nselp.u32 %0, 1, 0, p;\nselp.u32 %1, 1, 0, q;\n}"
    : "=r"(ok.x), "=r"(ok.y), "+f"(d[0]), "+f"(d[1]), "+f"(d[2]), "+f"(d[3]), "+f"(d[4]), "+f"(d[5]), "+f"(d[6]), "+f"(d[7]), "+f"(d[8]), "+f"(d[9]), "+f"(d[10]), "+f"(d[11]), "+f"(d[12]), "+f"(d[13]), "+f"(d[14]), "+f"(d[15]), "+f"(d[16]), "+f"(d[17]), "+f"(d[18]), "+f"(d[19]), "+f"(d[20]), "+f"(d[21]), "+f"(d[22]), "+f"(d[23]), "+f"(d[24]), "+f"(d[25]), "+f"(d[26]), "+f"(d[27]), "+f"(d[28]), "+f"(d[29]), "+f"(d[30]), "+f"(d[31]), "+f"(d[32]), "+f"(d[33]), "+f"(d[34]), "+f"(d[35]), "+f"(d[36]), "+f"(d[37]), "+f"(d[38]), "+f"(d[39]), "+f"(d[40]), "+f"(d[41]), "+f"(d[42]), "+f"(d[43]), "+f"(d[44]), "+f"(d[45]), "+f"(d[46]), "+f"(d[47]), "+f"(d[48]), "+f"(d[49]), "+f"(d[50]), "+f"(d[51]), "+f"(d[52]), "+f"(d[53]), "+f"(d[54]), "+f"(d[55]), "+f"(d[56]), "+f"(d[57]), "+f"(d[58]), "+f"(d[59]), "+f"(d[60]), "+f"(d[61]), "+f"(d[62]), "+f"(d[63]), "+f"(d[64]), "+f"(d[65]), "+f"(d[66]), "+f"(d[67]), "+f"(d[68]), "+f"(d[69]), "+f"(d[70]), "+f"(d[71]), "+f"(d[72]), "+f"(d[73]), "+f"(d[74]), "+f"(d[75]), "+f"(d[76]), "+f"(d[77]), "+f"(d[78]), "+f"(d[79]), "+f"(d[80]), "+f"(d[81]), "+f"(d[82]), "+f"(d[83]), "+f"(d[84]), "+f"(d[85]), "+f"(d[86]), "+f"(d[87]), "+f"(d[88]), "+f"(d[89]), "+f"(d[90]), "+f"(d[91]), "+f"(d[92]), "+f"(d[93]), "+f"(d[94]), "+f"(d[95]), "+r"(db)
    : "r"(da), "r"(h0), "r"(h1), "r"(one), "r"(b0), "r"(p0), "r"(b1), "r"(p1) : "memory");
  return ok;
}
template <int S> __device__ __forceinline__ uint2 wgmma_first256(float (&d)[S], uint32_t da, uint32_t& db, uint32_t h0, uint32_t h1, uint32_t one, uint32_t b0, uint32_t p0, uint32_t b1, uint32_t p1) {
  uint2 ok;
  asm volatile("{\n.reg .b64 a, b, s;\n.reg .b32 t, u;\n.reg .pred p, q;\nwgmma.fence.sync.aligned;\n"
    "mov.b32 t, %131;\n"
    "mov.b64 a, {t, %132};\nmov.b64 b, {%130, %133};\n"
    "wgmma.mma_async.sync.aligned.m64n256k16.f32.bf16.bf16 "
    "{%2, %3, %4, %5, %6, %7, %8, %9, %10, %11, %12, %13, %14, %15, %16, %17, %18, %19, %20, %21, %22, %23, %24, %25, %26, %27, %28, %29, %30, %31, %32, %33, %34, %35, %36, %37, %38, %39, %40, %41, %42, %43, %44, %45, %46, %47, %48, %49, %50, %51, %52, %53, %54, %55, %56, %57, %58, %59, %60, %61, %62, %63, %64, %65, %66, %67, %68, %69, %70, %71, %72, %73, %74, %75, %76, %77, %78, %79, %80, %81, %82, %83, %84, %85, %86, %87, %88, %89, %90, %91, %92, %93, %94, %95, %96, %97, %98, %99, %100, %101, %102, %103, %104, %105, %106, %107, %108, %109, %110, %111, %112, %113, %114, %115, %116, %117, %118, %119, %120, %121, %122, %123, %124, %125, %126, %127, %128, %129}, "
    "a, b, 0, 1, 1, 0, 1;\n"
    "mad.lo.u32 t, %134, 2, t;\nmad.lo.u32 %130, %134, 128, %130;\n"
    "mov.b64 a, {t, %132};\nmov.b64 b, {%130, %133};\n"
    "wgmma.mma_async.sync.aligned.m64n256k16.f32.bf16.bf16 "
    "{%2, %3, %4, %5, %6, %7, %8, %9, %10, %11, %12, %13, %14, %15, %16, %17, %18, %19, %20, %21, %22, %23, %24, %25, %26, %27, %28, %29, %30, %31, %32, %33, %34, %35, %36, %37, %38, %39, %40, %41, %42, %43, %44, %45, %46, %47, %48, %49, %50, %51, %52, %53, %54, %55, %56, %57, %58, %59, %60, %61, %62, %63, %64, %65, %66, %67, %68, %69, %70, %71, %72, %73, %74, %75, %76, %77, %78, %79, %80, %81, %82, %83, %84, %85, %86, %87, %88, %89, %90, %91, %92, %93, %94, %95, %96, %97, %98, %99, %100, %101, %102, %103, %104, %105, %106, %107, %108, %109, %110, %111, %112, %113, %114, %115, %116, %117, %118, %119, %120, %121, %122, %123, %124, %125, %126, %127, %128, %129}, "
    "a, b, 1, 1, 1, 0, 1;\n"
    "mov.b64 s, {%136, %136};\nmbarrier.test_wait.shared::cta.b64 p, [%135], s;\nmov.b64 s, {%138, %138};\nmbarrier.test_wait.shared::cta.b64 q, [%137], s;\n"
    "mad.lo.u32 t, %134, 2, t;\nmad.lo.u32 %130, %134, 128, %130;\n"
    "mov.b64 a, {t, %132};\nmov.b64 b, {%130, %133};\n"
    "wgmma.mma_async.sync.aligned.m64n256k16.f32.bf16.bf16 "
    "{%2, %3, %4, %5, %6, %7, %8, %9, %10, %11, %12, %13, %14, %15, %16, %17, %18, %19, %20, %21, %22, %23, %24, %25, %26, %27, %28, %29, %30, %31, %32, %33, %34, %35, %36, %37, %38, %39, %40, %41, %42, %43, %44, %45, %46, %47, %48, %49, %50, %51, %52, %53, %54, %55, %56, %57, %58, %59, %60, %61, %62, %63, %64, %65, %66, %67, %68, %69, %70, %71, %72, %73, %74, %75, %76, %77, %78, %79, %80, %81, %82, %83, %84, %85, %86, %87, %88, %89, %90, %91, %92, %93, %94, %95, %96, %97, %98, %99, %100, %101, %102, %103, %104, %105, %106, %107, %108, %109, %110, %111, %112, %113, %114, %115, %116, %117, %118, %119, %120, %121, %122, %123, %124, %125, %126, %127, %128, %129}, "
    "a, b, 1, 1, 1, 0, 1;\n"
    "mad.lo.u32 t, %134, 2, t;\nmad.lo.u32 %130, %134, 128, %130;\n"
    "mov.b64 a, {t, %132};\nmov.b64 b, {%130, %133};\n"
    "wgmma.mma_async.sync.aligned.m64n256k16.f32.bf16.bf16 "
    "{%2, %3, %4, %5, %6, %7, %8, %9, %10, %11, %12, %13, %14, %15, %16, %17, %18, %19, %20, %21, %22, %23, %24, %25, %26, %27, %28, %29, %30, %31, %32, %33, %34, %35, %36, %37, %38, %39, %40, %41, %42, %43, %44, %45, %46, %47, %48, %49, %50, %51, %52, %53, %54, %55, %56, %57, %58, %59, %60, %61, %62, %63, %64, %65, %66, %67, %68, %69, %70, %71, %72, %73, %74, %75, %76, %77, %78, %79, %80, %81, %82, %83, %84, %85, %86, %87, %88, %89, %90, %91, %92, %93, %94, %95, %96, %97, %98, %99, %100, %101, %102, %103, %104, %105, %106, %107, %108, %109, %110, %111, %112, %113, %114, %115, %116, %117, %118, %119, %120, %121, %122, %123, %124, %125, %126, %127, %128, %129}, "
    "a, b, 1, 1, 1, 0, 1;\n"
    "wgmma.commit_group.sync.aligned;\nselp.u32 %0, 1, 0, p;\nselp.u32 %1, 1, 0, q;\n}"
    : "=r"(ok.x), "=r"(ok.y), "=f"(d[0]), "=f"(d[1]), "=f"(d[2]), "=f"(d[3]), "=f"(d[4]), "=f"(d[5]), "=f"(d[6]), "=f"(d[7]), "=f"(d[8]), "=f"(d[9]), "=f"(d[10]), "=f"(d[11]), "=f"(d[12]), "=f"(d[13]), "=f"(d[14]), "=f"(d[15]), "=f"(d[16]), "=f"(d[17]), "=f"(d[18]), "=f"(d[19]), "=f"(d[20]), "=f"(d[21]), "=f"(d[22]), "=f"(d[23]), "=f"(d[24]), "=f"(d[25]), "=f"(d[26]), "=f"(d[27]), "=f"(d[28]), "=f"(d[29]), "=f"(d[30]), "=f"(d[31]), "=f"(d[32]), "=f"(d[33]), "=f"(d[34]), "=f"(d[35]), "=f"(d[36]), "=f"(d[37]), "=f"(d[38]), "=f"(d[39]), "=f"(d[40]), "=f"(d[41]), "=f"(d[42]), "=f"(d[43]), "=f"(d[44]), "=f"(d[45]), "=f"(d[46]), "=f"(d[47]), "=f"(d[48]), "=f"(d[49]), "=f"(d[50]), "=f"(d[51]), "=f"(d[52]), "=f"(d[53]), "=f"(d[54]), "=f"(d[55]), "=f"(d[56]), "=f"(d[57]), "=f"(d[58]), "=f"(d[59]), "=f"(d[60]), "=f"(d[61]), "=f"(d[62]), "=f"(d[63]), "=f"(d[64]), "=f"(d[65]), "=f"(d[66]), "=f"(d[67]), "=f"(d[68]), "=f"(d[69]), "=f"(d[70]), "=f"(d[71]), "=f"(d[72]), "=f"(d[73]), "=f"(d[74]), "=f"(d[75]), "=f"(d[76]), "=f"(d[77]), "=f"(d[78]), "=f"(d[79]), "=f"(d[80]), "=f"(d[81]), "=f"(d[82]), "=f"(d[83]), "=f"(d[84]), "=f"(d[85]), "=f"(d[86]), "=f"(d[87]), "=f"(d[88]), "=f"(d[89]), "=f"(d[90]), "=f"(d[91]), "=f"(d[92]), "=f"(d[93]), "=f"(d[94]), "=f"(d[95]), "=f"(d[96]), "=f"(d[97]), "=f"(d[98]), "=f"(d[99]), "=f"(d[100]), "=f"(d[101]), "=f"(d[102]), "=f"(d[103]), "=f"(d[104]), "=f"(d[105]), "=f"(d[106]), "=f"(d[107]), "=f"(d[108]), "=f"(d[109]), "=f"(d[110]), "=f"(d[111]), "=f"(d[112]), "=f"(d[113]), "=f"(d[114]), "=f"(d[115]), "=f"(d[116]), "=f"(d[117]), "=f"(d[118]), "=f"(d[119]), "=f"(d[120]), "=f"(d[121]), "=f"(d[122]), "=f"(d[123]), "=f"(d[124]), "=f"(d[125]), "=f"(d[126]), "=f"(d[127]), "+r"(db)
    : "r"(da), "r"(h0), "r"(h1), "r"(one), "r"(b0), "r"(p0), "r"(b1), "r"(p1) : "memory");
  return ok;
}
template <int S> __device__ __forceinline__ uint2 wgmma_step256(float (&d)[S], uint32_t da, uint32_t& db, uint32_t h0, uint32_t h1, uint32_t one, uint32_t b0, uint32_t p0, uint32_t b1, uint32_t p1) {
  uint2 ok;
  asm volatile("{\n.reg .b64 a, b, s;\n.reg .b32 t, u;\n.reg .pred p, q;\nwgmma.fence.sync.aligned;\n"
    "mov.b32 t, %131;\n"
    "mov.b64 a, {t, %132};\nmov.b64 b, {%130, %133};\n"
    "wgmma.mma_async.sync.aligned.m64n256k16.f32.bf16.bf16 "
    "{%2, %3, %4, %5, %6, %7, %8, %9, %10, %11, %12, %13, %14, %15, %16, %17, %18, %19, %20, %21, %22, %23, %24, %25, %26, %27, %28, %29, %30, %31, %32, %33, %34, %35, %36, %37, %38, %39, %40, %41, %42, %43, %44, %45, %46, %47, %48, %49, %50, %51, %52, %53, %54, %55, %56, %57, %58, %59, %60, %61, %62, %63, %64, %65, %66, %67, %68, %69, %70, %71, %72, %73, %74, %75, %76, %77, %78, %79, %80, %81, %82, %83, %84, %85, %86, %87, %88, %89, %90, %91, %92, %93, %94, %95, %96, %97, %98, %99, %100, %101, %102, %103, %104, %105, %106, %107, %108, %109, %110, %111, %112, %113, %114, %115, %116, %117, %118, %119, %120, %121, %122, %123, %124, %125, %126, %127, %128, %129}, "
    "a, b, 1, 1, 1, 0, 1;\n"
    "mad.lo.u32 t, %134, 2, t;\nmad.lo.u32 %130, %134, 128, %130;\n"
    "mov.b64 a, {t, %132};\nmov.b64 b, {%130, %133};\n"
    "wgmma.mma_async.sync.aligned.m64n256k16.f32.bf16.bf16 "
    "{%2, %3, %4, %5, %6, %7, %8, %9, %10, %11, %12, %13, %14, %15, %16, %17, %18, %19, %20, %21, %22, %23, %24, %25, %26, %27, %28, %29, %30, %31, %32, %33, %34, %35, %36, %37, %38, %39, %40, %41, %42, %43, %44, %45, %46, %47, %48, %49, %50, %51, %52, %53, %54, %55, %56, %57, %58, %59, %60, %61, %62, %63, %64, %65, %66, %67, %68, %69, %70, %71, %72, %73, %74, %75, %76, %77, %78, %79, %80, %81, %82, %83, %84, %85, %86, %87, %88, %89, %90, %91, %92, %93, %94, %95, %96, %97, %98, %99, %100, %101, %102, %103, %104, %105, %106, %107, %108, %109, %110, %111, %112, %113, %114, %115, %116, %117, %118, %119, %120, %121, %122, %123, %124, %125, %126, %127, %128, %129}, "
    "a, b, 1, 1, 1, 0, 1;\n"
    "mov.b64 s, {%136, %136};\nmbarrier.test_wait.shared::cta.b64 p, [%135], s;\nmov.b64 s, {%138, %138};\nmbarrier.test_wait.shared::cta.b64 q, [%137], s;\n"
    "mad.lo.u32 t, %134, 2, t;\nmad.lo.u32 %130, %134, 128, %130;\n"
    "mov.b64 a, {t, %132};\nmov.b64 b, {%130, %133};\n"
    "wgmma.mma_async.sync.aligned.m64n256k16.f32.bf16.bf16 "
    "{%2, %3, %4, %5, %6, %7, %8, %9, %10, %11, %12, %13, %14, %15, %16, %17, %18, %19, %20, %21, %22, %23, %24, %25, %26, %27, %28, %29, %30, %31, %32, %33, %34, %35, %36, %37, %38, %39, %40, %41, %42, %43, %44, %45, %46, %47, %48, %49, %50, %51, %52, %53, %54, %55, %56, %57, %58, %59, %60, %61, %62, %63, %64, %65, %66, %67, %68, %69, %70, %71, %72, %73, %74, %75, %76, %77, %78, %79, %80, %81, %82, %83, %84, %85, %86, %87, %88, %89, %90, %91, %92, %93, %94, %95, %96, %97, %98, %99, %100, %101, %102, %103, %104, %105, %106, %107, %108, %109, %110, %111, %112, %113, %114, %115, %116, %117, %118, %119, %120, %121, %122, %123, %124, %125, %126, %127, %128, %129}, "
    "a, b, 1, 1, 1, 0, 1;\n"
    "mad.lo.u32 t, %134, 2, t;\nmad.lo.u32 %130, %134, 128, %130;\n"
    "mov.b64 a, {t, %132};\nmov.b64 b, {%130, %133};\n"
    "wgmma.mma_async.sync.aligned.m64n256k16.f32.bf16.bf16 "
    "{%2, %3, %4, %5, %6, %7, %8, %9, %10, %11, %12, %13, %14, %15, %16, %17, %18, %19, %20, %21, %22, %23, %24, %25, %26, %27, %28, %29, %30, %31, %32, %33, %34, %35, %36, %37, %38, %39, %40, %41, %42, %43, %44, %45, %46, %47, %48, %49, %50, %51, %52, %53, %54, %55, %56, %57, %58, %59, %60, %61, %62, %63, %64, %65, %66, %67, %68, %69, %70, %71, %72, %73, %74, %75, %76, %77, %78, %79, %80, %81, %82, %83, %84, %85, %86, %87, %88, %89, %90, %91, %92, %93, %94, %95, %96, %97, %98, %99, %100, %101, %102, %103, %104, %105, %106, %107, %108, %109, %110, %111, %112, %113, %114, %115, %116, %117, %118, %119, %120, %121, %122, %123, %124, %125, %126, %127, %128, %129}, "
    "a, b, 1, 1, 1, 0, 1;\n"
    "wgmma.commit_group.sync.aligned;\nselp.u32 %0, 1, 0, p;\nselp.u32 %1, 1, 0, q;\n}"
    : "=r"(ok.x), "=r"(ok.y), "+f"(d[0]), "+f"(d[1]), "+f"(d[2]), "+f"(d[3]), "+f"(d[4]), "+f"(d[5]), "+f"(d[6]), "+f"(d[7]), "+f"(d[8]), "+f"(d[9]), "+f"(d[10]), "+f"(d[11]), "+f"(d[12]), "+f"(d[13]), "+f"(d[14]), "+f"(d[15]), "+f"(d[16]), "+f"(d[17]), "+f"(d[18]), "+f"(d[19]), "+f"(d[20]), "+f"(d[21]), "+f"(d[22]), "+f"(d[23]), "+f"(d[24]), "+f"(d[25]), "+f"(d[26]), "+f"(d[27]), "+f"(d[28]), "+f"(d[29]), "+f"(d[30]), "+f"(d[31]), "+f"(d[32]), "+f"(d[33]), "+f"(d[34]), "+f"(d[35]), "+f"(d[36]), "+f"(d[37]), "+f"(d[38]), "+f"(d[39]), "+f"(d[40]), "+f"(d[41]), "+f"(d[42]), "+f"(d[43]), "+f"(d[44]), "+f"(d[45]), "+f"(d[46]), "+f"(d[47]), "+f"(d[48]), "+f"(d[49]), "+f"(d[50]), "+f"(d[51]), "+f"(d[52]), "+f"(d[53]), "+f"(d[54]), "+f"(d[55]), "+f"(d[56]), "+f"(d[57]), "+f"(d[58]), "+f"(d[59]), "+f"(d[60]), "+f"(d[61]), "+f"(d[62]), "+f"(d[63]), "+f"(d[64]), "+f"(d[65]), "+f"(d[66]), "+f"(d[67]), "+f"(d[68]), "+f"(d[69]), "+f"(d[70]), "+f"(d[71]), "+f"(d[72]), "+f"(d[73]), "+f"(d[74]), "+f"(d[75]), "+f"(d[76]), "+f"(d[77]), "+f"(d[78]), "+f"(d[79]), "+f"(d[80]), "+f"(d[81]), "+f"(d[82]), "+f"(d[83]), "+f"(d[84]), "+f"(d[85]), "+f"(d[86]), "+f"(d[87]), "+f"(d[88]), "+f"(d[89]), "+f"(d[90]), "+f"(d[91]), "+f"(d[92]), "+f"(d[93]), "+f"(d[94]), "+f"(d[95]), "+f"(d[96]), "+f"(d[97]), "+f"(d[98]), "+f"(d[99]), "+f"(d[100]), "+f"(d[101]), "+f"(d[102]), "+f"(d[103]), "+f"(d[104]), "+f"(d[105]), "+f"(d[106]), "+f"(d[107]), "+f"(d[108]), "+f"(d[109]), "+f"(d[110]), "+f"(d[111]), "+f"(d[112]), "+f"(d[113]), "+f"(d[114]), "+f"(d[115]), "+f"(d[116]), "+f"(d[117]), "+f"(d[118]), "+f"(d[119]), "+f"(d[120]), "+f"(d[121]), "+f"(d[122]), "+f"(d[123]), "+f"(d[124]), "+f"(d[125]), "+f"(d[126]), "+f"(d[127]), "+r"(db)
    : "r"(da), "r"(h0), "r"(h1), "r"(one), "r"(b0), "r"(p0), "r"(b1), "r"(p1) : "memory");
  return ok;
}
template <int S> __device__ __forceinline__ void wgmma_aug192(float (&d)[S], uint32_t a0, uint32_t a1, uint32_t db, uint32_t h1) {
  asm volatile("{\n.reg .b64 b;\n.reg .b32 z;\nmov.b32 z, 0;\n"
    "mov.b64 b, {%98, %99};\nwgmma.fence.sync.aligned;\n"
    "wgmma.mma_async.sync.aligned.m64n192k16.f32.bf16.bf16 "
    "{%0, %1, %2, %3, %4, %5, %6, %7, %8, %9, %10, %11, %12, %13, %14, %15, %16, %17, %18, %19, %20, %21, %22, %23, %24, %25, %26, %27, %28, %29, %30, %31, %32, %33, %34, %35, %36, %37, %38, %39, %40, %41, %42, %43, %44, %45, %46, %47, %48, %49, %50, %51, %52, %53, %54, %55, %56, %57, %58, %59, %60, %61, %62, %63, %64, %65, %66, %67, %68, %69, %70, %71, %72, %73, %74, %75, %76, %77, %78, %79, %80, %81, %82, %83, %84, %85, %86, %87, %88, %89, %90, %91, %92, %93, %94, %95}, "
    "{%96, %97, z, z}, b, 1, 1, 1, 1;\n"
    "wgmma.commit_group.sync.aligned;\n}"
    : "+f"(d[0]), "+f"(d[1]), "+f"(d[2]), "+f"(d[3]), "+f"(d[4]), "+f"(d[5]), "+f"(d[6]), "+f"(d[7]), "+f"(d[8]), "+f"(d[9]), "+f"(d[10]), "+f"(d[11]), "+f"(d[12]), "+f"(d[13]), "+f"(d[14]), "+f"(d[15]), "+f"(d[16]), "+f"(d[17]), "+f"(d[18]), "+f"(d[19]), "+f"(d[20]), "+f"(d[21]), "+f"(d[22]), "+f"(d[23]), "+f"(d[24]), "+f"(d[25]), "+f"(d[26]), "+f"(d[27]), "+f"(d[28]), "+f"(d[29]), "+f"(d[30]), "+f"(d[31]), "+f"(d[32]), "+f"(d[33]), "+f"(d[34]), "+f"(d[35]), "+f"(d[36]), "+f"(d[37]), "+f"(d[38]), "+f"(d[39]), "+f"(d[40]), "+f"(d[41]), "+f"(d[42]), "+f"(d[43]), "+f"(d[44]), "+f"(d[45]), "+f"(d[46]), "+f"(d[47]), "+f"(d[48]), "+f"(d[49]), "+f"(d[50]), "+f"(d[51]), "+f"(d[52]), "+f"(d[53]), "+f"(d[54]), "+f"(d[55]), "+f"(d[56]), "+f"(d[57]), "+f"(d[58]), "+f"(d[59]), "+f"(d[60]), "+f"(d[61]), "+f"(d[62]), "+f"(d[63]), "+f"(d[64]), "+f"(d[65]), "+f"(d[66]), "+f"(d[67]), "+f"(d[68]), "+f"(d[69]), "+f"(d[70]), "+f"(d[71]), "+f"(d[72]), "+f"(d[73]), "+f"(d[74]), "+f"(d[75]), "+f"(d[76]), "+f"(d[77]), "+f"(d[78]), "+f"(d[79]), "+f"(d[80]), "+f"(d[81]), "+f"(d[82]), "+f"(d[83]), "+f"(d[84]), "+f"(d[85]), "+f"(d[86]), "+f"(d[87]), "+f"(d[88]), "+f"(d[89]), "+f"(d[90]), "+f"(d[91]), "+f"(d[92]), "+f"(d[93]), "+f"(d[94]), "+f"(d[95])
    : "r"(a0), "r"(a1), "r"(db), "r"(h1) : "memory");
}
template <int S> __device__ __forceinline__ void wgmma_aug256(float (&d)[S], uint32_t a0, uint32_t a1, uint32_t db, uint32_t h1) {
  asm volatile("{\n.reg .b64 b;\n.reg .b32 z;\nmov.b32 z, 0;\n"
    "mov.b64 b, {%130, %131};\nwgmma.fence.sync.aligned;\n"
    "wgmma.mma_async.sync.aligned.m64n256k16.f32.bf16.bf16 "
    "{%0, %1, %2, %3, %4, %5, %6, %7, %8, %9, %10, %11, %12, %13, %14, %15, %16, %17, %18, %19, %20, %21, %22, %23, %24, %25, %26, %27, %28, %29, %30, %31, %32, %33, %34, %35, %36, %37, %38, %39, %40, %41, %42, %43, %44, %45, %46, %47, %48, %49, %50, %51, %52, %53, %54, %55, %56, %57, %58, %59, %60, %61, %62, %63, %64, %65, %66, %67, %68, %69, %70, %71, %72, %73, %74, %75, %76, %77, %78, %79, %80, %81, %82, %83, %84, %85, %86, %87, %88, %89, %90, %91, %92, %93, %94, %95, %96, %97, %98, %99, %100, %101, %102, %103, %104, %105, %106, %107, %108, %109, %110, %111, %112, %113, %114, %115, %116, %117, %118, %119, %120, %121, %122, %123, %124, %125, %126, %127}, "
    "{%128, %129, z, z}, b, 1, 1, 1, 1;\n"
    "wgmma.commit_group.sync.aligned;\n}"
    : "+f"(d[0]), "+f"(d[1]), "+f"(d[2]), "+f"(d[3]), "+f"(d[4]), "+f"(d[5]), "+f"(d[6]), "+f"(d[7]), "+f"(d[8]), "+f"(d[9]), "+f"(d[10]), "+f"(d[11]), "+f"(d[12]), "+f"(d[13]), "+f"(d[14]), "+f"(d[15]), "+f"(d[16]), "+f"(d[17]), "+f"(d[18]), "+f"(d[19]), "+f"(d[20]), "+f"(d[21]), "+f"(d[22]), "+f"(d[23]), "+f"(d[24]), "+f"(d[25]), "+f"(d[26]), "+f"(d[27]), "+f"(d[28]), "+f"(d[29]), "+f"(d[30]), "+f"(d[31]), "+f"(d[32]), "+f"(d[33]), "+f"(d[34]), "+f"(d[35]), "+f"(d[36]), "+f"(d[37]), "+f"(d[38]), "+f"(d[39]), "+f"(d[40]), "+f"(d[41]), "+f"(d[42]), "+f"(d[43]), "+f"(d[44]), "+f"(d[45]), "+f"(d[46]), "+f"(d[47]), "+f"(d[48]), "+f"(d[49]), "+f"(d[50]), "+f"(d[51]), "+f"(d[52]), "+f"(d[53]), "+f"(d[54]), "+f"(d[55]), "+f"(d[56]), "+f"(d[57]), "+f"(d[58]), "+f"(d[59]), "+f"(d[60]), "+f"(d[61]), "+f"(d[62]), "+f"(d[63]), "+f"(d[64]), "+f"(d[65]), "+f"(d[66]), "+f"(d[67]), "+f"(d[68]), "+f"(d[69]), "+f"(d[70]), "+f"(d[71]), "+f"(d[72]), "+f"(d[73]), "+f"(d[74]), "+f"(d[75]), "+f"(d[76]), "+f"(d[77]), "+f"(d[78]), "+f"(d[79]), "+f"(d[80]), "+f"(d[81]), "+f"(d[82]), "+f"(d[83]), "+f"(d[84]), "+f"(d[85]), "+f"(d[86]), "+f"(d[87]), "+f"(d[88]), "+f"(d[89]), "+f"(d[90]), "+f"(d[91]), "+f"(d[92]), "+f"(d[93]), "+f"(d[94]), "+f"(d[95]), "+f"(d[96]), "+f"(d[97]), "+f"(d[98]), "+f"(d[99]), "+f"(d[100]), "+f"(d[101]), "+f"(d[102]), "+f"(d[103]), "+f"(d[104]), "+f"(d[105]), "+f"(d[106]), "+f"(d[107]), "+f"(d[108]), "+f"(d[109]), "+f"(d[110]), "+f"(d[111]), "+f"(d[112]), "+f"(d[113]), "+f"(d[114]), "+f"(d[115]), "+f"(d[116]), "+f"(d[117]), "+f"(d[118]), "+f"(d[119]), "+f"(d[120]), "+f"(d[121]), "+f"(d[122]), "+f"(d[123]), "+f"(d[124]), "+f"(d[125]), "+f"(d[126]), "+f"(d[127])
    : "r"(a0), "r"(a1), "r"(db), "r"(h1) : "memory");
}

__device__ __forceinline__ uint32_t clock32() { uint32_t c; asm volatile("mov.u32 %0, %%clock;" : "=r"(c)); return c; }
__device__ __forceinline__ void spin_until(uint32_t c) {
  asm volatile("{\n.reg .pred p;\n.reg .s32 t;\nLAB_WAIT:\nmov.u32 t, %%clock;\nsub.s32 t, t, %0;\nsetp.lt.s32 p, t, 0;\n@p bra.uni LAB_WAIT;\n}" ::"r"(c) : "memory");
}
struct Nop { __device__ __forceinline__ void operator()(int) const {} };
template <int V> struct IC { static constexpr int v = V; };
struct Pipe {
  uint32_t db, g8, a8, pa, tph, aend, curB, curA, prevB, prevA, bo, so, sph, h0, h1, one;
  uint2 nx;
  int w; bool l0;
  __device__ __forceinline__ int lane() const { return LSO ? (so >> 5) & 31 : threadIdx.x & 31; }
  __device__ __forceinline__ void adv_a() { a8 += 8; pa += PA1; if (a8 == aend) a8 -= NA * 8; }
  __device__ __forceinline__ uint32_t take() { const uint32_t a = SB + OFF_A + a8 * 1024; adv_a(); return a; }
  __device__ __forceinline__ uint32_t ahead(int d) const { uint32_t ls = a8 + d * 8; if (ls >= aend) ls -= NA * 8; return SB + OFF_A + ls * 1024; }
  __device__ __forceinline__ uint32_t wait_ahead(int d) {
    uint32_t ls = a8 + d * 8;
    if (ls >= aend) ls -= NA * 8;
    mbar_spin31(SB + BAR_FULLA + ls, pa + d * PA1);
    return SB + OFF_A + ls * 1024;
  }
  template <int N, bool FIRST, int S> __device__ __forceinline__ uint2 iss(float (&acc)[S], bool skip) {
    const uint32_t da = DA0 + a8 * 64;
    if (!FIRST) { if (N != 192) db &= ~0x2000u; else if (db == DB0 + 15 * 512) db = DB0; }
    prevB = curB; prevA = curA;
    curB = g8 & 56; curA = a8;
    g8 += G1;
    a8 += skip ? 16 : 8; pa += skip ? 2 * PA1 : PA1;
    if (a8 >= aend) a8 -= NA * 8;
    const uint32_t fb = SB + BAR_FULLB + (g8 & 56), fa = SB + BAR_FULLA + a8;
    uint2 ok;
    if constexpr (N == 128) ok = FIRST ? wgmma_first128(acc, da, db, h0, h1, one, fb, g8, fa, pa) : wgmma_step128(acc, da, db, h0, h1, one, fb, g8, fa, pa);
    if constexpr (N == 192) ok = FIRST ? wgmma_first192(acc, da, db, h0, h1, one, fb, g8, fa, pa) : wgmma_step192(acc, da, db, h0, h1, one, fb, g8, fa, pa);
    if constexpr (N == 256) ok = FIRST ? wgmma_first256(acc, da, db, h0, h1, one, fb, g8, fa, pa) : wgmma_step256(acc, da, db, h0, h1, one, fb, g8, fa, pa);
    db += N * 8 - 384;
    return ok;
  }
  __device__ __forceinline__ void ensure(uint2 ok) {
    asm volatile(
        "{\n.reg .pred p, q;\n.reg .b64 s, t;\nmov.b64 s, {%1, %1};\nmov.b64 t, {%3, %3};\nsetp.ne.u32 p, %4, 0;\nsetp.ne.u32 q, %5, 0;\n@!p bra.uni LAB_WAIT;\n@q bra.uni DONE;\n"
        "LAB_WAIT:\nmbarrier.try_wait.shared::cta.b64 p, [%0], s;\nmbarrier.try_wait.shared::cta.b64 q, [%2], t;\n"
        "and.pred p, p, q;\n@!p bra.uni LAB_WAIT;\nDONE:\n}" ::"r"(SB + BAR_FULLB + (g8 & 56)), "r"(g8), "r"(SB + BAR_FULLA + a8), "r"(pa), "r"(ok.x), "r"(ok.y) : "memory");
  }
  template <class Hook> __device__ __forceinline__ void validate(bool check, const CUtensorMap* tm16, int c0, int c1, int wp, int j, Hook hook) {
    const uint32_t rows = SB + OFF_A + a8 * 1024 + wp * 2048, ad = a8 * 1024 + so;
    uint32_t v0 = 0, v1 = 0;
    asm volatile("{\n.reg .pred p;\nsetp.ne.u32 p, %3, 0;\n@p ld.shared.b32 %0, [%2];\n@p ld.shared.b32 %1, [%2 + 1024];\n}" : "+r"(v0), "+r"(v1) : "r"(ad), "r"((uint32_t)check));
    hook();
    while (__any_sync(~0u, max(v0, v1) == 0xffffffffu)) {
      const uint32_t bar = SB + BAR_SPEC + (w * 4 + wp) * 8;
      e_load<2048>(rows, tm16, c0 + sched_k(c_sched.v[j][(g8 >> 3) & 511]), c1 + wp * 16, bar);
      mbar_spin(bar, sph);
      sph ^= 1;
      v0 = lds32(ad); v1 = lds32(ad + 1024);
    }
  }
  __device__ __forceinline__ void fence() const { asm volatile("{\n.reg .pred p;\nsetp.eq.u32 p, %0, 2;\nLAB:\n@p pmevent 6;\n@p bra.uni LAB;\n}" ::"r"(one) : "memory"); }
  __device__ __forceinline__ void drain() {
    wg_wait<0>();
    arrive_2(SB + BAR_EMPTYB + curB, SB + BAR_EMPTYA + curA, l0);
    curB = BAR_DUMMY - BAR_EMPTYB; curA = BAR_DUMMY - BAR_EMPTYA;
  }
  __device__ __forceinline__ void signal_server(uint32_t odd) { __syncwarp(); arrive_n(SB + BAR_SRV + w * 16 + odd * 8, l0); }
  __device__ __forceinline__ void signal_loader() { __syncwarp(); arrive_n(SB + BAR_STG + w * 8, l0); }
  template <int N, bool HOLD = false, int S, class Pre = Nop> __device__ __forceinline__ void begin(float (&acc)[S], uint32_t p0, int proft, Pre pre = Pre()) {
    db = DB0 + p0 * 512;
    const uint32_t c1 = HOLD ? clock32() : 0;
    ensure(nx);
    if (HOLD) spin_until(c1 + lds32(SB + OFF_HOLD + w * 4));
    pre(0);
    PROF_T(w, proft, 0);
    ensure(iss<N, true>(acc, false));
  }
  template <int N, bool ENSURE = true, int S, class Hook> __device__ __forceinline__ void run(float (&acc)[S], int i0, int i1, uint32_t skips, int pause, Hook hook) {
    int i = i0;
    const int ev = w ? pause : -1;
#pragma unroll 1
    while (true) {
      const uint2 ok = iss<N, false>(acc, (skips >> i) & 1);
      wg_wait<1>();
      arrive_2(SB + BAR_EMPTYB + prevB, SB + BAR_EMPTYA + prevA, l0);
      if (pause >= 0 && i + 1 == i1) { nx = ok; break; }
      if constexpr (ENSURE) { ensure(ok); hook(i); } else hook(i, ok);
      i++;
      if (pause < 0 && i == i1) break;
      if (pause > 0 && i == ev) { drain(); mbar_spin(SB + BAR_LEAD, tph); }
    }
  }
  template <int N, bool AUG, int S> __device__ __forceinline__ void end(float (&acc)[S], int ns, uint32_t pos, uint32_t au0, uint32_t au1, int proft) {
    uint32_t augB = 0;
    arrive_n(SB + BAR_LEAD + w * (BAR_DUMMY - BAR_LEAD), l0);
    if constexpr (AUG) {
      asm volatile("{\n.reg .pred p;\n.reg .b64 s;\nmov.b64 s, {%1, %1};\nsetp.ne.u32 p, %2, 0;\n@p bra.uni DONE;\nLAB_WAIT:\nmbarrier.try_wait.shared::cta.b64 p, [%0], s;\n@!p bra.uni LAB_WAIT;\nDONE:\n}"
                     ::"r"(SB + BAR_FULLB + (g8 & 56)), "r"(g8), "r"(nx.x) : "memory");
      const uint32_t dc = (((SB + OFF_B) >> 4) | (64u << 16)) + pos * 512;
      if constexpr (N == 192) wgmma_aug192(acc, au0, au1, dc, h1); else wgmma_aug256(acc, au0, au1, dc, h1);
      augB = g8 & 56; g8 += G1;
    }
    tph ^= 1;
    if (ns > 0) wait_ahead(ns - 1);
    nx = make_uint2(mbar_test(SB + BAR_FULLB + (g8 & 56), g8 >> 31), AUG ? mbar_test(SB + BAR_FULLA + a8, pa >> 31) : 1);
    wg_wait<0>();
    arrive_2(SB + BAR_EMPTYB + curB, SB + BAR_EMPTYA + curA, l0);
    if (AUG) arrive_n(SB + BAR_EMPTYB + augB, l0);
    PROF_T(w, proft, 1);
  }
};

__device__ __forceinline__ uint32_t box_addr(uint32_t buf, uint32_t bo, int u) { return (buf + bo) ^ (u * 32); }

__device__ __forceinline__ float bf_round(float x) { return __bfloat162float(__float2bfloat16_rn(x)); }
__device__ __forceinline__ void own_rstd(int w, int wp, int lane, float (&rstd)[2]) {
#pragma unroll
  for (int hh = 0; hh < 2; hh++) rstd[hh] = __uint_as_float(lds32(SB + OFF_RSTD + (w * 72 + 8 + wp * 16 + (lane >> 2) + hh * 8) * 4));
}
__device__ __forceinline__ void stats_fetch(int w, int wp, int lane, uint32_t (&au)[2]) {
  const int g = lane >> 2, q4 = lane & 3;
  float rstd[2];
  own_rstd(w, wp, lane, rstd);
#pragma unroll
  for (int hh = 0; hh < 2; hh++) {
    const float m = __uint_as_float(lds32(SB + OFF_MEAN + (w * 64 + wp * 16 + g + hh * 8) * 4));
    const float v = q4 == 3 ? rcp(rstd[hh]) : -m;
    const float v1 = bf_round(v), v2 = bf_round(v - v1);
    const float p = q4 == 1 ? v2 : (q4 == 2 ? v - v1 - v2 : v1);
    au[hh] = pack_bf16(p, q4 == 3 ? v2 : p);
  }
}

struct Attn {
  uint32_t lo[24], hi[24], ha[16], hslot;
  float c[8][4], rstd[2];
  float2 rk[3];
  const uint4* hsrc;
  __device__ __forceinline__ void pull(int lane) {
    asm volatile("{\n.reg .b64 a;\n.reg .b32 t;\nand.b32 t, %19, 3;\nmad.wide.u32 a, t, 8, %18;\nld.relaxed.gpu.global.v2.f32 {%16,%17}, [a + 2048];\nmad.wide.u32 a, %19, 16, %18;\n"
                 "ld.relaxed.gpu.global.v4.b32 {%0,%1,%2,%3}, [a];\nld.relaxed.gpu.global.v4.b32 {%4,%5,%6,%7}, [a + 512];\n"
                 "ld.relaxed.gpu.global.v4.b32 {%8,%9,%10,%11}, [a + 1024];\nld.relaxed.gpu.global.v4.b32 {%12,%13,%14,%15}, [a + 1536];\n}"
                 : "=&r"(ha[0]), "=&r"(ha[1]), "=&r"(ha[2]), "=&r"(ha[3]), "=&r"(ha[4]), "=&r"(ha[5]), "=&r"(ha[6]), "=&r"(ha[7]), "=&r"(ha[8]), "=&r"(ha[9]), "=&r"(ha[10]),
                   "=&r"(ha[11]), "=&r"(ha[12]), "=&r"(ha[13]), "=&r"(ha[14]), "=&r"(ha[15]), "=&f"(rk[0].x), "=&f"(rk[0].y) : "l"(hsrc), "r"(lane) : "memory");
  }
  __device__ __forceinline__ bool missing() const {
    return __any_sync(~0u, min(min(min(ha[0], ha[4]), min(ha[8], ha[12])), min(__float_as_uint(rk[0].x), __float_as_uint(rk[0].y))) == 0);
  }
  __device__ __forceinline__ void A(const float (&acc)[96], Pipe& M, int w, int wp, int r, uint4* halo_out) {
    const int lane = M.lane();
    auto cvt = [&](uint32_t& d, int u) { asm volatile("cvt.rn.bf16x2.f32 %0, %1, %2;" : "=r"(d) : "f"(acc[u + 1]), "f"(acc[u])); };
    auto rest = [&] {
#pragma unroll
      for (int nb = 23; nb >= 0; nb--) {
        cvt(lo[nb], 4 * nb);
        if (nb < 8) cvt(hi[nb], 4 * nb + 2);
        if (nb >= 16) lo[nb] = movm(lo[nb]);
      }
    };
#pragma unroll
    for (int nb = 8; nb < 24; nb++) hi[nb] = pack_bf16(acc[4 * nb + 2], acc[4 * nb + 3]);
    hslot = M.ahead(3);
    const uint32_t hbuf = hslot + wp * 2048 + lane * 16;
#pragma unroll
    for (int nb = 16; nb < 24; nb++) hi[nb] = movm(hi[nb]);
    if (wp == 3) {
      if (r < 15) {
#pragma unroll
        for (int p = 0; p < 4; p++) halo_out[p * 32 + lane] = make_uint4(hi[8 + 4 * p] ? hi[8 + 4 * p] : 0x8000u, hi[9 + 4 * p], hi[10 + 4 * p], hi[11 + 4 * p]);
        const uint32_t rh = lds32(SB + OFF_RSTD + (w * 72 + 64 + (lane & 7)) * 4);
        if (lane < 8) reinterpret_cast<uint32_t*>(halo_out + 128)[lane] = rh ? rh : 0x80000000u;
      }
    } else {
#pragma unroll
      for (int p = 0; p < 4; p++)
        asm volatile("st.shared.v4.b32 [%0], {%1,%2,%3,%4};" ::"r"(hbuf + 2048 + p * 512), "r"(hi[8 + 4 * p]), "r"(hi[9 + 4 * p]), "r"(hi[10 + 4 * p]), "r"(hi[11 + 4 * p]) : "memory");
    }
    __syncwarp();
    arrive_n(SB + BAR_HALO + w * 8, M.l0);
    rest();
    hsrc = halo_out - 16 * 136;
#pragma unroll
    for (int u = 0; u < 16; u++) ha[u] = 0;
    rk[0] = make_float2(1.f, 1.f);
  }
  __device__ __forceinline__ void B(int w, int wp, int r, int lane, uint32_t hph) {
    own_rstd(w, wp, lane, rstd);
    if (wp == 0) {
#pragma unroll
      for (int u = 1; u < 3; u++) rk[u] = lds64(SB + OFF_RSTD + (w * 72 + u * 8 + 2 * (lane & 3)) * 4);
      while (r > 0 && missing()) {
        pull(lane);
      }
      return;
    }
    mbar_spin(SB + BAR_HALO + w * 8, hph);
#pragma unroll
    for (int p = 0; p < 4; p++)
      asm volatile("ld.shared.v4.b32 {%0,%1,%2,%3}, [%4];" : "=r"(ha[4 * p]), "=r"(ha[4 * p + 1]), "=r"(ha[4 * p + 2]), "=r"(ha[4 * p + 3]) : "r"(hslot + wp * 2048 + lane * 16 + p * 512) : "memory");
#pragma unroll
    for (int u = 0; u < 3; u++) rk[u] = lds64(SB + OFF_RSTD + (w * 72 + wp * 16 + u * 8 + 2 * (lane & 3)) * 4);
  }
  template <class F> __device__ __forceinline__ void C(int wp, int r, int lane, uint32_t zero, F last) {
    const int g = lane >> 2, q = lane & 3;
    const bool nohalo = (wp == 0) && (r == 0);
    const bool up0 = 2 * q > g, up1 = 2 * q + 1 > g;
    const float sc = 0.17677669529663687f * 1.4426950408889634f;
    const float kx0 = up0 ? rk[0].x : rk[1].x, kx1 = up1 ? rk[0].y : rk[1].y;
    const float ky0 = up0 ? rk[1].x : rk[2].x, ky1 = up1 ? rk[1].y : rk[2].y;
    const float fx = rstd[0] * sc, fy = rstd[1] * sc;
    float sm[2][4] = {}, s0[2][4] = {}, s1[2][4] = {};
#pragma unroll
    for (int ks = 0; ks < 2; ks++)
#pragma unroll
      for (int h = 0; h < 2; h++) {
        const int a = 4 * h + 2 * ks;
        mma16(s0[h], lo[a], hi[a], lo[a + 1], hi[a + 1], lo[8 + a], lo[9 + a]);
        mma16(s1[h], lo[a], hi[a], lo[a + 1], hi[a + 1], hi[8 + a], hi[9 + a]);
      }
#pragma unroll
    for (int u = 0; u < 4; u++) { const int a = 4 * (u & 1) + (u & 2); mma16(sm[u & 1], lo[a], hi[a], lo[a + 1], hi[a + 1], ha[a], ha[a + 1]); }
    uint32_t pf[2][4];
    const uint32_t um = (up0 ? 0xffffu : 0u) | (up1 ? 0xffff0000u : 0u);
#pragma unroll
    for (int h = 0; h < 2; h++) {
      if (nohalo) { sm[h][0] = -INFINITY; sm[h][1] = -INFINITY; }
      float x0 = (up0 ? sm[h][0] : s0[h][0]) * (kx0 * fx), x1 = (up1 ? sm[h][1] : s0[h][1]) * (kx1 * fx);
      float y0 = (up0 ? s0[h][2] : s1[h][2]) * (ky0 * fy), y1 = (up1 ? s0[h][3] : s1[h][3]) * (ky1 * fy);
      float mx = fmaxf(x0, x1), my = fmaxf(y0, y1);
      mx = fmaxf(mx, __shfl_xor_sync(~0u, mx, 1)); my = fmaxf(my, __shfl_xor_sync(~0u, my, 1));
      mx = fmaxf(mx, __shfl_xor_sync(~0u, mx, 2)); my = fmaxf(my, __shfl_xor_sync(~0u, my, 2));
      x0 = ex2(x0 - mx); x1 = ex2(x1 - mx); y0 = ex2(y0 - my); y1 = ex2(y1 - my);
      float sx = x0 + x1, sy = y0 + y1;
      x0 *= kx0; x1 *= kx1; y0 *= ky0; y1 *= ky1;
      sx += __shfl_xor_sync(~0u, sx, 1); sy += __shfl_xor_sync(~0u, sy, 1);
      sx += __shfl_xor_sync(~0u, sx, 2); sy += __shfl_xor_sync(~0u, sy, 2);
      sx = rcp(sx); sy = rcp(sy);
      x0 *= sx; x1 *= sx; y0 *= sy; y1 *= sy;
      const uint32_t px = pack_bf16(x0, x1), py = pack_bf16(y0, y1);
      pf[h][0] = px & um; pf[h][1] = px & ~um; pf[h][2] = py & um; pf[h][3] = py & ~um;
    }
#pragma unroll
    for (int u = 0; u < 4; u++) {
#pragma unroll
      for (int e = 0; e < 4; e++) { c[2 * u][e] = 0.f; c[2 * u + 1][e] = 0.f; }
      mma8(c[2 * u], ha[8 + 2 * u], ha[9 + 2 * u], pf[u >> 1][0]);
      mma8(c[2 * u + 1], lo[16 + 2 * u], lo[17 + 2 * u], pf[u >> 1][2]);
    }
#pragma unroll
    for (int u = 0; u < 4; u++) {
      mma8(c[2 * u], lo[16 + 2 * u], lo[17 + 2 * u], pf[u >> 1][1]);
      mma8(c[2 * u + 1], hi[16 + 2 * u], hi[17 + 2 * u], pf[u >> 1][3]);
    }
    uint32_t dep = 0;
    last();
#pragma unroll
    for (int u = 0; u < (EFIRST == 3 ? 0 : 8); u++) dep |= __float_as_uint(c[u][0]);
    asm volatile("bar.sync %0, 256;" ::"r"(3 + (dep & zero)) : "memory");
  }
  __device__ __forceinline__ void E(Pipe& M, bool urgent) {
#pragma unroll
    for (int u = 0; u < 4; u++)
      asm volatile("stmatrix.sync.aligned.m8n8.x4.trans.shared.b16 [%0], {%1, %2, %3, %4};" ::"r"(box_addr(hslot, M.bo, u)),
                   "r"(pack_bf16(c[2 * u][0], c[2 * u][1])), "r"(pack_bf16(c[2 * u + 1][0], c[2 * u + 1][1])),
                   "r"(pack_bf16(c[2 * u][2], c[2 * u][3])), "r"(pack_bf16(c[2 * u + 1][2], c[2 * u + 1][3])) : "memory");
    __syncwarp();
    arrive_n(SB + (urgent ? BAR_STG + M.w * 8 : BAR_SRV + M.w * 16 + 8), M.l0);
  }
};

__device__ __forceinline__ void epi_res(const float (&acc)[64], const float (&pre)[64], float sc0, float sc1, uint32_t (&xr)[32], Pipe& M, int wp) {
  Pipe T = M;
  const uint32_t buf0 = T.take(), buf1 = T.take();
#pragma unroll
  for (int u = 0; u < 8; u++) {
#pragma unroll
    for (int nb = 2 * u; nb < 2 * u + 2; nb++) {
      xr[2 * nb] = pack_bf16(fmaf(acc[4 * nb], sc0, pre[2 * nb]), fmaf(acc[4 * nb + 1], sc0, pre[32 + 2 * nb]));
      xr[2 * nb + 1] = pack_bf16(fmaf(acc[4 * nb + 2], sc1, pre[2 * nb + 1]), fmaf(acc[4 * nb + 3], sc1, pre[33 + 2 * nb]));
    }
    stsm4(box_addr(u < 4 ? buf0 : buf1, M.bo, u & 3), xr[4 * u], xr[4 * u + 1], xr[4 * u + 2], xr[4 * u + 3]);
    if (u == 3) { M.signal_loader(); M.fence(); }
  }
  __syncwarp();
  arrive_n(SB + BAR_STG2 + M.w * 8, M.l0);
  fence_async_smem();
  wg_bar(M.w);
}
__device__ __forceinline__ void presum(float (&pre)[64], const uint32_t (&xr)[32], int lane, float usebias) {
  const uint32_t bias = SB + OFF_VEC + (lane & 3) * 8;
#pragma unroll
  for (int nb = 0; nb < 16; nb++) {
    const float2 b = lds64(bias + nb * 32);
#pragma unroll
    for (int u = 2 * nb; u < 2 * nb + 2; u++) {
      pre[32 + u] = fmaf(b.y, usebias, bf_hi(xr[u])); pre[u] = fmaf(b.x, usebias, bf_lo(xr[u]));
      asm volatile("" : "+f"(pre[u]), "+f"(pre[32 + u]));
    }
  }
}
template <int U0, int U1, int S, int Q> __device__ __forceinline__ void pack_relu(uint32_t (&o)[Q], const float (&acc)[S]) {
#pragma unroll
  for (int u = U0; u < U1; u++) asm volatile("cvt.rn.relu.bf16x2.f32 %0, %1, %2;" : "=r"(o[u]) : "f"(acc[2 * u + 1]), "f"(acc[2 * u]));
}
__device__ __forceinline__ uint32_t sq_bf16x2(uint32_t a) { uint32_t d; asm("mul.rn.bf16x2 %0, %1, %1;" : "=r"(d) : "r"(a)); return d; }
template <int Q> __device__ __forceinline__ void ffn_stage(const uint32_t (&o)[Q], int i, Pipe& M) {
  i -= M.w;
  if (i == 1 || i == 4 || i == 7 || (Q == 64 && i == 10)) {
    const uint32_t buf = M.wait_ahead(2 - M.w);
#pragma unroll
    for (int b = 0; b < Q / 16; b++)
      if (i == 3 * b + 1) {
#pragma unroll
        for (int u = 4 * b; u < 4 * b + 4; u++)
          stsm4(box_addr(buf, M.bo, u & 3), sq_bf16x2(o[4 * u]), sq_bf16x2(o[4 * u + 1]), sq_bf16x2(o[4 * u + 2]), sq_bf16x2(o[4 * u + 3]));
      }
    M.signal_server((i & 1) ^ (Q == 64));
  }
}

__device__ __forceinline__ void wait_flags(const uint8_t* f, uint32_t tag, int lane) {
  const uint32_t t4 = (tag & 0xff) * 0x01010101u;
  const uint32_t* fp = reinterpret_cast<const uint32_t*>(f) + (lane & (FG / 4 - 1));
  while (__any_sync(~0u, __vsub4(ld_relaxed(fp), t4) & 0x80808080u)) {}
  asm volatile("fence.acquire.gpu;\nfence.proxy.async.global;" ::: "memory");
}
__device__ __forceinline__ uint32_t get_epoch() { mbar_spin(SB + BAR_EPOCH, 0); return __shfl_sync(~0u, lds32(SB + OFF_HOLD + 8), 0); }
__device__ __forceinline__ void aloader(const Params& P, const Ptrs& Q, int bid, int r, int j, int lane, int w, uint32_t e, uint32_t epoch) {
  const uint32_t abase = SB + OFF_A + w * NA * 8192, fbase = SB + BAR_FULLA + w * NA * 8, ebase = SB + BAR_EMPTYA + w * NA * 8;
  uint32_t slot = NPRO, ph = 1, nst = 0, npace = 0;
  int t = -1, kind = -1, a0 = 0, a1 = 0;
  const CUtensorMap* tmA = nullptr;
  uint64_t pol = 0;
  uint4* hin = Q.s->halo[0][0] + (r * 16 + j * 2 + w - 16) * 136;
  uint32_t* const pace = Q.s->pace[0] + (bid & -PG) * 4;
  const uint8_t* const flags = Q.s->flags[r / (FG / 8)][w];
  auto adv = [&] { if (++slot == NA) { slot = 0; ph ^= 1; } };
#pragma unroll 1
  for (int g = NPRO; g <= NSTEP; g++) {
    const uint32_t cur = e;
    e = c_sched.v[j][g + 1];
    if (!(cur & E_RARE)) {
      if (cur & E_HAND) { mbar_spin(ebase + slot * 8, ph); e_arrive(fbase + slot * 8, 1); adv(); }
    } else {
      if (cur & F_NEW) {
        t++; kind = kind == 5 ? 0 : kind + 1;
        const bool narrow = kind == 2 || kind == 5;
        static_assert(TM_XIN == 0 && TM_X == 1 && TM_XA == 2 && TM_O == 3 && TM_H == 4, "map order");
        tmA = &P.tm[t < 2 ? 0 : (0x422311 >> (4 * kind)) & 15];
        pol = ((AEF >> t) & 1) ? 0x12F0000000000000ull : 0x1000000000000000ull;
        a0 = narrow ? 0 : w * 1024; a1 = narrow ? r * 128 + w * 64 : r * 64;
      }
      const bool xo = cur & E_XPUB0;
      uint32_t s = slot;
      if (cur & (E_HAND | E_ATTN | E_XPUB0)) {
        if (cur & E_KEEP) e_arrive(ebase + slot * 8, 4);
#pragma unroll 1
        for (int u = xo ? 0 : 1; u < 2; u++) { mbar_wait(ebase + slot * 8, ph); e_arrive(fbase + slot * 8, 1); adv(); }
      }
      uint32_t hold = 0;
      int lag = 0;
      if ((xo && t < 12) || (cur & F_GATH)) {
        uint32_t v;
        uint32_t v1;
        do asm volatile("ld.relaxed.gpu.global.v2.u32 {%0, %1}, [%2];" : "=r"(v), "=r"(v1) : "l"(pace + npace + (lane & (PG - 1)) * 2) : "memory");
        while (__any_sync(~0u, ((v ^ (epoch * 16 + t - 1)) | (v ^ v1)) & 31));
        v += v1;
        npace ^= PG * 2;
        lag = min((int)(v - __shfl_sync(~0u, v, bid & (PG - 1))), 8000) * LAGM >> 5;
        hold = __reduce_max_sync(~0u, lag);
        asm volatile("st.shared.b32 [%0], %1;" ::"r"(SB + OFF_HOLD + w * 4), "r"(hold) : "memory");
      }
      if (cur & (E_ATTN | E_XPUB0)) {
        const uint32_t s2 = s == NA - 1 ? 0 : s + 1;
        mbar_wait(SB + BAR_STG + w * 8, nst & 1);
        nst++;
        LT(0);
        const uint32_t c1 = clock32();
        e_store(tmA, a0 + sched_k(cur), a1, abase + s * 8192);
        if (xo) {
          mbar_spin(SB + BAR_STG2 + w * 8, ~t & 1);
          e_store(tmA, a0 + sched_k(cur) + 64, a1, abase + s2 * 8192);
          if (t == 12) break;
        } else e_arrive(SB + BAR_OWN + w * 8, 1);
        LT(1);
        spin_until(c1 + hold + (xo ? SDELAY : SDELAYO));
        LT(2);
        LT(5);
      }
      if (cur & E_SIG) {
        e_arrive(SB + BAR_SRV + w * 16, 4);
      }
      if (cur & E_REL) bulk_wait_all();
      if ((cur & E_REL) && (kind == 1 || kind == 2) && r > 0) {
        uint4* hz = hin + lane;
        hin += 256 * 136;
#pragma unroll
        for (int p = 0; p < 4; p++) hz[p * 32] = make_uint4(0, 0, 0, 0);
        if (lane < 2) hz[128] = make_uint4(0, 0, 0, 0);
      }
      if (cur & E_WAIT) {
        wait_flags(flags + ((cur & E_PART1) ? FG : 0), epoch * 16 + t, lane);
      }
    }
    if (!(cur & (F_AUG | F_NOA))) {
      mbar_wait(ebase + slot * 8, ph);
      e_load(abase + slot * 8192, tmA, a0 + sched_k(cur), a1, fbase + slot * 8, pol);
      adv();
      if (cur & F_STAMP) {
        uint32_t stamp;
        asm volatile("mov.u32 %0, %%globaltimer_lo;" : "=r"(stamp));
        asm volatile("st.relaxed.gpu.global.u32 [%0], %1;" ::"l"(pace + npace + (bid & (PG - 1)) * 2 + w), "r"((stamp & ~31u) | ((epoch * 16 + t) & 31)) : "memory");
      }
    }
  }
  bulk_wait_all();
}

__device__ __forceinline__ void bloader(const Params& P, const Ptrs& Q, bool aux, int j, int lane, uint32_t e, uint32_t epoch) {
  const uint32_t* const sched = c_sched.v[aux ? 8 : j];
  int kind = -1, c2 = 0, c3 = 0, na = 0;
  const CUtensorMap* tmB = nullptr;
  uint32_t sph = 0, efm = aux ? 0 : BEF * 2;
  uint64_t pol = 0;
#pragma unroll 1
  for (int g = aux ? 8 + (j & 1) : NPRO; g < (aux ? NSTEP_AUX : NSTEP); g += 1 + aux) {
    const uint32_t cur = e;
    e = sched[g + 1 + aux];
    if (cur & F_NEW) {
      kind = kind == 5 ? 0 : kind + ((cur >> 29) & 3);
      static_assert(TM_WQKV == 5 && TM_WO == 6 && TM_W1A == 7 && TM_W1B == 8 && TM_W2 == 9, "map order");
      tmB = &P.tm[(0x978655 >> (4 * kind)) & 15];
      efm >>= 1;
      pol = (efm & 1) ? 0x12F0000000000000ull : 0x1000000000000000ull;
      na = (0x243233 >> (4 * kind)) & 15;
      c2 = ((0x277200 >> (4 * kind)) & 15) * j + (kind == 4 ? 3 : 0);
      c3 = kind <= 1 ? kind * 8 + j : 0;
    }
    const int need = g - (int)((cur >> 5) & 15);
    const uint32_t dst = SB + OFF_B + (cur & 31) * 8192, bar = SB + BAR_FULLB + (g & 7) * 8;
    mbar_wait(SB + BAR_EMPTYB + (need & 7) * 8, (need >> 3) & 1);
    if (!(cur & F_AUG)) {
      asm volatile("{\n.reg .pred p;\nelect.sync _|p, 0xffffffff;\n@p mbarrier.arrive.expect_tx.shared::cta.b64 _, [%2], %7;\n"
                   "@p cp.async.bulk.tensor.4d.shared::cluster.global.mbarrier::complete_tx::bytes.L2::cache_hint [%0], [%1, {%3, %4, %5, %6}], [%2], %8;\n}"
                   ::"r"(dst), "l"(tmB), "r"(bar), "r"(0), "r"(sched_k(cur)), "r"(c2), "r"(c3), "r"(na * 8192), "l"(pol) : "memory");
    } else {
      const bool chk = g < NSTEP / 2;
      const uint32_t b2 = chk ? SB + BAR_AUG : bar, ad = dst + lane * 16 + (lane >> 3) * 4;
      while (true) {
        asm volatile("{\n.reg .pred p;\nelect.sync _|p, 0xffffffff;\n@p mbarrier.arrive.expect_tx.shared::cta.b64 _, [%2], 4096;\n"
                     "@p cp.async.bulk.shared::cluster.global.mbarrier::complete_tx::bytes [%0], [%1], 4096, [%2];\n}"
                     ::"r"(dst), "l"(Q.s->aug[epoch & 1][(kind - (kind >= 3)) * 8 + j]), "r"(b2) : "memory");
        if (!chk) break;
        mbar_spin(b2, sph);
        sph ^= 1;
        uint32_t mn = ~0u;
#pragma unroll
        for (int u = 0; u < 8; u++) mn = min(mn, lds32(ad + u * 512));
        if (!__any_sync(~0u, mn == 0)) { e_arrive(bar, 1); break; }
      }
      __syncwarp();
    }
  }
}

constexpr uint32_t job_slots(int layer) {
  const int pos[10] = {11, 26, 63, 73, 77, 81, 92, 96, 100, 104};
  uint32_t v = 0;
  for (int m = 0; m < 10; m++) v |= (uint32_t)((layer * 148 + pos[m]) % NA) << (3 * m);
  return v;
}
constexpr uint32_t JOB_SLOTS0 = job_slots(0), JOB_SLOTS1 = job_slots(1);
__device__ __forceinline__ void server(const Params& P, const Ptrs& Q, int bid, int r, int j, int lane, uint32_t epoch) {
  const uint32_t c0 = clock32();
  if (PFT) {
    spin_until(c0 + PFT);
    if (lane < 16) asm volatile("cp.async.bulk.prefetch.L2.global [%0], 2048;" ::"l"(Q.x + (r * 128 + j * 16 + lane) * 1024) : "memory");
  }
  if (CPF) spin_until(c0 + CPF);
  epoch += __shfl_sync(~0u, c_sched.v[j][lane < 18 ? lane * 16 : 0] >> 31, 0);
  {
    const uint2 b = reinterpret_cast<const uint2*>(Q.b2 + j * 128)[lane];
    sts128(SB + OFF_VEC + lane * 16, b.x << 16, b.x & 0xffff0000u, b.y << 16, b.y & 0xffff0000u);
  }
  int hl = 0;
  uint32_t fph = 0, pend = SB + BAR_DUMMY3;
#pragma unroll 1
  for (int n = 0; n < 20; n++) {
    const int layer = n >= 10, m = n - 10 * layer;
    const bool stat = m == 0 || m == 2;
    const uint32_t slot = ((layer ? JOB_SLOTS1 : JOB_SLOTS0) >> (m * 3)) & 7;
    auto fetch = [&](int w) {
      asm volatile("{\n.reg .pred p;\nelect.sync _|p, 0xffffffff;\n@p mbarrier.arrive.expect_tx.shared::cta.b64 _, [%2], 4096;\n"
                   "@p cp.async.bulk.shared::cluster.global.mbarrier::complete_tx::bytes [%0], [%1], 4096, [%2];\n}"
                   ::"r"(SB + OFF_A + (w * NA + slot) * 8192), "l"(&Q.s->stats[hl][r * 32 + w * 16][0][0]), "r"(SB + BAR_SPEC + 64 + w * 8) : "memory");
    };
#pragma unroll 1
    for (int w = 0; w < 2; w++) {
      mbar_spin(SB + BAR_SRV + w * 16 + (n & 1) * 8, (n >> 1) & 1);
      if (stat) fetch(w);
      else {
        e_store(&P.tm[m == 1 ? TM_O : TM_H], m == 1 ? j * 64 : 448 * j + (m - 3) * 64, r * 128 + w * 64, SB + OFF_A + (w * NA + slot) * 8192);
        bulk_wait_read<1>();
        e_arrive(pend, 4);
        pend = SB + BAR_EMPTYA + (w * NA + slot) * 8;
      }
    }
    if (stat) {
#pragma unroll 1
      for (int w = 0; w < 2; w++) {
        const uint32_t src = SB + OFF_A + (w * NA + slot) * 8192 + (lane >> 1) * 256 + ((lane >> 1) & 7) * 32 + (lane & 1) * 16;
        float ms[2], md[2], mq[2], m0[2];
        while (true) {
          mbar_spin(SB + BAR_SPEC + 64 + w * 8, (fph >> w) & 1);
          fph ^= 1u << w;
          uint32_t bad = 0;
          ms[0] = ms[1] = md[0] = md[1] = mq[0] = mq[1] = m0[0] = m0[1] = 0.f;
#pragma unroll 1
          for (int p = 0; p < 8; p += 2) {
            const float4 v2[2] = {lds128(src ^ (p * 32)), lds128(src ^ (p * 32) ^ 32)};
            if (p == 0) { m0[0] = v2[0].x; m0[1] = v2[0].z; }
#pragma unroll
            for (int z = 0; z < 2; z++) {
              const float4 v = v2[z];
              const float a = v.x - m0[0], b = v.z - m0[1];
              bad |= __float_as_uint(v.y) ^ epoch;
              ms[0] += a; md[0] = fmaf(a, a, md[0]); mq[0] += __uint_as_float(__float_as_uint(v.y) & ~63u);
              ms[1] += b; md[1] = fmaf(b, b, md[1]); mq[1] += v.w;
            }
          }
          if (!__any_sync(~0u, bad & 63)) break;
          fetch(w);
          __syncwarp();
        }
        e_arrive(SB + BAR_EMPTYA + (w * NA + slot) * 8, 4);
        const int row = (lane >> 3) * 16 + (lane & 7);
#pragma unroll
        for (int z = 0; z < 2; z++) {
          const float d = ms[z] * 0.125f;
          asm volatile("st.shared.f32 [%0], %1;" ::"r"(SB + OFF_MEAN + (w * 64 + row + z * 8) * 4), "f"(m0[z] + d) : "memory");
          const float rs = rsq(fmaf(mq[z], 1.f / 1024.f, fmaxf(fmaf(md[z], 0.125f, -d * d), 0.f)) + 1e-5f);
          asm volatile("st.shared.f32 [%0], %1;" ::"r"(SB + OFF_RSTD + (w * 72 + 8 + row + z * 8) * 4), "f"(rs) : "memory");
        }
        e_arrive(SB + BAR_STAT + w * 8, 8);
      }
    }
    if (stat && n != 12) {
#pragma unroll 1
      for (int u = 0; u < (m ? 2 : 3); u++) {
        const uint32_t pitch = u == 2 ? 448 : 128;
        uint4* p = reinterpret_cast<uint4*>(u == 2 ? Q.s->h : (m ? Q.out : Q.s->x)) + (u == 2 ? 64 + j * 8 : j * 16 + u * 8) + ((r * 128 + (lane >> 3)) * pitch + (lane & 7));
#pragma unroll 1
        for (int k = 0; k < 32 / FUN; k++) {
#pragma unroll
          for (int z = 0; z < FUN; z++) {
            *p = make_uint4(~0u, ~0u, ~0u, ~0u);
            p += 4 * pitch;
            asm volatile("" : "+l"(p));
          }
        }
      }
      __syncwarp();
    }
    if ((0x222 >> m) & 1) {
      bulk_wait_all();
      e_arrive(pend, 4);
      pend = SB + BAR_DUMMY3;
      if (lane < 2) st_release8(&Q.s->flags[r / (FG / 8)][lane][(r & (FG / 8 - 1)) * 8 + j + (m == 9 ? FG : 0)], epoch * 16 + layer * 6 + (m == 1 ? 2 : 5));
      __syncwarp();
    }
    hl += stat;
  }
}

__device__ __forceinline__ void aux_math(const Ptrs& Q, int bid, int jj, int warp, int lane) {
  const int g = lane >> 2, q = lane & 3, c0 = (warp & 3) * 2;
  uint32_t st = warp >> 2, bf[16][4] = {};
  const uint32_t ad0 = SB + ((lane >> 4) * 8 + (lane & 7)) * 128 + (((c0 + ((lane >> 3) & 1)) ^ (lane & 7)) << 4);
#pragma unroll 1
  for (int t = 0; t < 4; t++) {
    float acc[4][4] = {};
    uint32_t bias[8];
#pragma unroll
    for (int a = 0; a < 8; a++) bias[a] = t >= 2 ? reinterpret_cast<const uint32_t*>(Q.b1 + 448 * jj + (t - 2) * 192 + c0 * 8)[(a >> 1) * 32 + (a & 1) * 4 + q] : 0u;
#pragma unroll 1
    for (int i = 0; i < 16; i++, st += 2) {
      const uint32_t ad = ad0 + (c_sched.v[8][st] & 31) * 8192;
      mbar_spin(SB + BAR_FULLB + (st & 7) * 8, (st >> 3) & 1);
#pragma unroll
      for (int u = 0; u < 16; u++)
        asm volatile("{\n.reg .pred p;\nsetp.ne.u32 p, %5, 0;\n@p ldmatrix.sync.aligned.m8n8.x4.trans.shared.b16 {%0,%1,%2,%3}, [%4];\n}"
                     : "+r"(bf[u][0]), "+r"(bf[u][1]), "+r"(bf[u][2]), "+r"(bf[u][3])
                     : "r"(ad + (u & 3) * 8192 + (u >> 2) * 2048), "r"((u & 3) != 3 || t == 3 ? 1 : 0) : "memory");
      __syncwarp();
      e_arrive(SB + BAR_EMPTYB + (st & 7) * 8, 2);
#pragma unroll
      for (int u = 0; u < 16; u++) mma16(acc[u & 3], bf[u][0], bf[u][1], bf[u][2], bf[u][3], 0x3F803F80u, 0x3F803F80u);
    }
    const uint32_t epoch = lds32(SB + OFF_HOLD + 8);
    const uint32_t o = (t * 8 + jj) * 1024 + g * 32 + ((c0 ^ g) << 2) + q + (epoch & 1) * 32768;
    uint32_t *const p0 = Q.s->aug[0][0] + o, *const p1 = Q.s->aug[0][0] + (o ^ 4);
#pragma unroll
    for (int a = 0; a < 8; a++) {
      const float u = acc[a >> 1][(a & 1) * 2];
      uint32_t h = movm(pack_bf16(u, u - bf_round(u)));
      if (g >= 6) h = bias[a];
      ((a & 1) ? p1 : p0)[(a >> 1) * 256] = h ? h : 0x8000u;
    }
    uint4* const z = reinterpret_cast<uint4*>(Q.s->aug[~epoch & 1][t * 8 + jj]) + (threadIdx.x & 127);
    z[0] = z[128] = make_uint4(0, 0, 0, 0);
  }
}

template <bool BYSM> __global__ void __launch_bounds__(NTHREADS, 1) mega_kernel(const __grid_constant__ Ptrs Q, const __grid_constant__ Params P) {
  extern __shared__ __align__(1024) uint8_t smem_raw[];
  constexpr uint32_t sb = SB;
  const uint32_t centry = clock32();
  const int warp = __shfl_sync(~0u, threadIdx.x >> 5, 0), lane = threadIdx.x & 31;
  const int bid = BYSM ? work_id() : blockIdx.x;
  const bool aux = bid >= NMAIN;
  const int r = Q44 ? ((bid >> 5) << 2) | (bid & 3) : ((bid >> 4) << 1) | (bid & 1), j = (aux ? bid * 2 : bid >> (1 + Q44)) & 7;
  PRO(0);
  {
    const uint32_t b = sb + OFF_BAR + warp * 48, cnt = warp < 6 ? 1 : (warp < 10 ? 4 : 8);
    asm volatile("{\n.reg .pred p;\nelect.sync _|p, 0xffffffff;\n@p mbarrier.init.shared::cta.b64 [%0], %1;\n@p mbarrier.init.shared::cta.b64 [%0 + 8], %1;\n"
                 "@p mbarrier.init.shared::cta.b64 [%0 + 16], %1;\n@p mbarrier.init.shared::cta.b64 [%0 + 24], %1;\n"
                 "@p mbarrier.init.shared::cta.b64 [%0 + 32], %1;\n@p mbarrier.init.shared::cta.b64 [%0 + 40], %1;\nfence.mbarrier_init.release.cluster;\n}"
                 ::"r"(b), "r"(cnt) : "memory");
  }
  __syncthreads();
  {
    static_assert(NPRO == 4, "prologue stages");
    const int st = ((11 - warp) * (aux ? 32 : 11)) >> 5, op = aux ? (st < 8) * 2 : 11 - warp - 3 * st, sd = aux ? st >> STGX : (op == 2 ? st : st & 2);
    const uint32_t bar0 = sb + OFF_BAR + (op * 6 + st) * 8;
    const int kc = aux ? (st >> 1) * 64 : (((st & 2 ? ROUND1 : ROUND0) >> (4 * j)) & 15) * 128 + (st & 1) * 64;
    spin_until(centry + (sd ? STG0 + sd * STG1 : 0));
    if (op == 2) {
      asm volatile("{\n.reg .pred p;\nelect.sync _|p, 0xffffffff;\n@p mbarrier.arrive.expect_tx.shared::cta.b64 _, [%2], 24576;\n"
                   "@p cp.async.bulk.tensor.4d.shared::cluster.global.mbarrier::complete_tx::bytes [%0], [%1, {%3, %4, %3, %5}], [%2];\n}"
                   ::"r"(sb + OFF_B + (aux ? (st & 1) * 114688 + (st >> 1) * 24576 : (st + pos0(0) / 3 - (st + pos0(0) / 3 >= 5 ? 5 : 0)) * 24576)), "l"(&P.tm[TM_WQKV]), "r"(bar0), "r"(0), "r"(kc), "r"(j + (st & aux)) : "memory");
    } else if (!aux) e_load(sb + OFF_A + (op * 6 + st) * 8192, &P.tm[TM_XIN], op * 1024 + kc, r * 64, bar0);
    PRO(1);
    asm volatile("prefetch.tensormap [%0];" ::"l"(&P.tm[warp]) : "memory");
  }
  if (warp >= 8) {
    asm volatile("setmaxnreg.dec.sync.aligned.u32 24;");
    if (warp == 11) {
      if (smem_u32(smem_raw) != SB) __trap();
      const uint32_t epoch = __shfl_sync(~0u, ld_relaxed(&Q.s->epoch[bid]) + 1, 0);
      Q.s->epoch[bid] = epoch;
      asm volatile("st.shared.b32 [%0], %1;" ::"r"(sb + OFF_HOLD + 8), "r"(epoch) : "memory");
      e_arrive(sb + BAR_EPOCH, 1);
      PRO(2);
      if (!aux) server(P, Q, bid, r, j, lane, epoch);
    } else {
      const uint32_t e = c_sched.v[aux ? 8 : j][aux ? warp : NPRO];
      spin_until(centry + STGL + (aux ? STGLX : (warp > 8 ? STGLW : 0)) + (e >> 31));
      PRO(2);
      const uint32_t epoch = get_epoch();
      PRO(3);
      if (warp <= 8 + aux) bloader(P, Q, aux, j + warp - 8, lane, e, epoch);
      else if (!aux) aloader(P, Q, bid, r, j, lane, warp - 9, e, epoch);
    }
  } else if (aux) aux_math(Q, bid, j + (warp >> 2), warp, lane);
  else {
    asm volatile("setmaxnreg.inc.sync.aligned.u32 240;");
    const int w = warp >> 2, wp = warp & 3;
    {
      uint32_t xr[32];
#pragma unroll
      for (int u = 0; u < 32; u++) if (NOI) asm volatile("" : "=r"(xr[u])); else xr[u] = 0;
      Pipe M;
      M.db = 0; M.g8 = 0; M.a8 = w * NA * 8; M.pa = 0; M.tph = 0; M.aend = (w + 1) * NA * 8;
      M.h0 = gridDim.y * 0x40000040u; M.h1 = gridDim.z * 0x40000040u; M.one = gridDim.z;
      M.curB = M.curA = M.prevB = M.prevA = M.sph = 0; M.nx = make_uint2(0, 0); M.w = w; M.l0 = lane == 0;
      M.bo = (wp * 16 + (lane & 15)) * 128 + (((lane >> 4) ^ (lane & 7)) << 4);
      M.so = __shfl_sync(~0u, SB + OFF_A + wp * 2048 + lane * 32 + (lane >> 2) * 4, lane);
      M.bo = __shfl_sync(~0u, M.bo, lane);
      auto nop = [](int) {};
      const uint32_t zero = gridDim.y - 1;
      PROF_T(w, 0, 3);
      if (STARTC) spin_until(centry + STARTC);
#pragma unroll 1
      for (int hl = 0; hl < 4; hl++) {
        const int t0 = hl * 3;
        const bool ffn = hl & 1;
        float acc[96], acn[64];
        uint32_t au[2] = {0u, 0u};
        {
          const int d = hl ? 0 : ((OWNP * 2u) >> (4 * j)) & 15;
          auto own = [&](auto h, uint32_t dep = 0) {
#pragma unroll
            for (int u = 4 * h.v; u < 4 * h.v + 4; u++)
              asm volatile("ldmatrix.sync.aligned.m8n8.x4.shared.b16 {%0,%1,%2,%3}, [%4];" : "=r"(xr[4 * u]), "=r"(xr[4 * u + 1]), "=r"(xr[4 * u + 2]), "=r"(xr[4 * u + 3])
                           : "r"(box_addr(sb + OFF_A + M.a8 * 1024, M.bo + dep, u & 3)) : "memory");
          };
          M.begin<192>(acc, ffn ? pos0(3) : pos0(0), t0, [&](int) { if (hl + d == 0) own(IC<0>{}); });
          if (hl + d == 0) own(IC<1>{}, (xr[0] | xr[4] | xr[8] | xr[12]) & zero);
          float ss[2] = {0.f, 0.f}, sq[2] = {0.f, 0.f};
          auto part = [&](auto c0, auto n) {
#pragma unroll
            for (int v = 0; v < 4 * n.v; v++) {
              const int u = c0.v + v / n.v * 4 + v % n.v;
              float a, b;
              asm volatile("shl.b32 %0, %2, 16;\nand.b32 %1, %2, 0xffff0000;" : "=f"(a), "=f"(b) : "r"(xr[u]));
              ss[u & 1] += a + b; sq[u & 1] = fmaf(a, a, fmaf(b, b, sq[u & 1]));
            }
          };
          const uint64_t plan = hl ? (ffn ? PLAN1 : PLAN2) : (w ? (d & 4 ? (d & 2 ? PB6 : PB4) : (d ? PB2 : PB0)) : (d & 4 ? (d & 2 ? PA6 : PA4) : (d ? PA2 : PA0)));
          auto todo = [&](int i) { uint64_t v; asm volatile("shr.u64 %0, %1, %2;" : "=l"(v) : "l"(plan), "r"((i + 1 - d) * 8)); return (uint32_t)v; };
          uint32_t m = todo(1);
          M.run<192, false>(acc, 1, 16, 1u << 10, 16 - (ffn ? LEAD3 : LEAD0), [&](int i, uint2 ok) {
           CT(0);
           if (m & 127) {
             if (m & 1) part(IC<0>{}, IC<2>{});
             if (m & 2) part(IC<2>{}, IC<2>{});
             if (m & 4) part(IC<16>{}, IC<1>{});
             if (m & 8) part(IC<17>{}, IC<1>{});
             if (m & 16) part(IC<18>{}, IC<1>{});
             if (m & 32) part(IC<19>{}, IC<1>{});
             if (m & 64) {
               const uint32_t epoch = lds32(sb + OFF_HOLD + 8);
#pragma unroll
               for (int o = 1; o < 4; o *= 2)
#pragma unroll
                 for (int z = 0; z < 2; z++) { ss[z] += __shfl_xor_sync(~0u, ss[z], o); sq[z] += __shfl_xor_sync(~0u, sq[z], o); }
               const float m0 = ss[0] * (1.f / 128.f), m1 = ss[1] * (1.f / 128.f);
               const int rowpair = r * 64 + w * 32 + wp * 8 + (M.lane() >> 2);
               if ((M.lane() & 3) == 0)
                 st_pkt(&Q.s->stats[hl][rowpair >> 1][j][rowpair & 1], __float_as_uint(m0), (__float_as_uint(fmaxf(fmaf(-ss[0], m0, sq[0]), 0.f)) & ~63u) | (epoch & 63),
                        __float_as_uint(m1), __float_as_uint(fmaxf(fmaf(-ss[1], m1, sq[1]), 0.f)));
             }
           }
           CT(1);
           M.ensure(ok);
           CT(3);
           M.validate(hl != 0, &P.tm[ffn ? TM_XA16 : TM_X16], w * 1024, r * 64, wp, j, [&] {
            if (m & 128) { if (m & 1) own(IC<1>{}); else own(IC<0>{}); }
            m = todo(i + 1);
            if (i == STATI) { mbar_spin(sb + BAR_STAT + w * 8, hl & 1); stats_fetch(w, wp, M.lane(), au); }
           });
           CT(4);
          });
          M.end<192, true>(acc, ffn ? 0 : 4, ffn ? posa(3) : posa(0), au[0], au[1], t0);
          PROF_T(w, t0, 2);
        }
        if (!ffn) {
          Attn T;
#pragma unroll 1
          for (int wave = 0; wave < 2; wave++) {
            AP(9);
            uint4* const hp = Q.s->halo[0][0] + (uint32_t)(((hl + wave) * 256 + r * 16 + j * 2 + w) * 136);
            T.A(acc, M, w, wp, r, hp);
            AP(0);
            if (wave == 0) {
              M.begin<192, PACE2 & 1>(acc, pos0(1), t0 + 1);
              M.run<192>(acc, 1, NH1, 4, -1, [&](int i) { if (((HPM >> i) & 1) && wp == 0 && r > 0 && T.missing()) T.pull(M.lane()); });
              T.B(w, wp, r, M.lane(), 0);
              M.drain();
            } else {
              M.begin<128, (PACE2 >> 1) & 1>(acn, pos0(2), t0 + 2);
              if (wp == 0 && r > 0) T.pull(M.lane());
              M.run<128>(acn, 1, NH2, 4, -1, nop);
              T.B(w, wp, r, M.lane(), 1);
              M.drain();
#pragma unroll
              for (int z = 0; z < 64; z++) asm volatile("mov.b32 %0, %1;" : "=f"(acc[z]) : "f"(acn[z]));
            }
            AP(2);
            T.C(wp, r, M.lane(), zero, [&] { if (EFIRST == 3 || (EFIRST == 2 && wave)) T.E(M, wave); });
            AP(3);
            if (wave == 1) break;
            M.run<192>(acc, NH1, 16, 1u << 7, 16 - LEAD1, [&](int i) { if (EFIRST < 3 && i == NH1) T.E(M, false); });
            M.end<192, true>(acc, 4, posa(1), au[0], au[1], t0 + 1);
            PROF_T(w, t0 + 1, 2);
          }
#pragma unroll
          for (int z = 0; z < 64; z++) asm volatile("mov.b32 %0, %1;" : "=f"(acn[z]) : "f"(acc[z]));
          if (EFIRST == 1) T.E(M, true);
          else if (!EFIRST) {
            M.ensure(M.iss<128, false>(acn, false));
            T.E(M, true);
          }
        } else {
          uint32_t pk[48], pk2[64];
          pack_relu<0, 48>(pk, acc);
          {
            float acc2[128];
            M.begin<256, (PACE2 >> 3) & 1>(acc2, pos0(4), t0 + 1);
            M.run<256>(acc2, 1, 16, 0x248, 16 - LEAD4, [&](int i) { ffn_stage(pk, i, M); });
            M.end<256, true>(acc2, 0, posa(4), au[0], au[1], t0 + 1);
            pack_relu<0, 64>(pk2, acc2);
            PROF_T(w, t0 + 1, 2);
          }
          M.begin<128, (PACE2 >> 4) & 1>(acn, pos0(5), t0 + 2);
          M.run<128>(acn, 1, 13, 0x1248, -1, [&](int i) { ffn_stage(pk2, i, M); });
        }
        {
          const int ks = ffn ? 56 : 16, pause = ks - (ffn ? LEAD5 : LEAD2), vfrom = ffn ? 99 : 7;
          const int imid = w ? pause : (ffn ? 20 : IPRE);
          auto check = [&](int i) {
            if (i >= vfrom) {
              if (i == 7) mbar_spin(sb + BAR_OWN + w * 8, hl >> 1);
              M.validate(true, &P.tm[TM_O16], 0, r * 128 + w * 64, wp, j, [] {});
            }
          };
          M.run<128>(acn, ffn ? 13 : NH2 + !EFIRST, imid, 0, -1, check);
          if (w) M.drain();
          float pre[64], rstd[2];
          presum(pre, xr, M.lane(), ffn ? 1.f : 0.f);
          own_rstd(w, wp, M.lane(), rstd);
          if (w) mbar_spin(SB + BAR_LEAD, M.tph);
          M.run<128>(acn, imid, ks, 0, 0, check);
          M.end<128, false>(acn, 2, 0, 0, 0, t0 + 2);
          epi_res(acn, pre, ffn ? rstd[0] * rstd[0] : 1.f, ffn ? rstd[1] * rstd[1] : 1.f, xr, M, wp);
          PROF_T(w, t0 + 2, 2);
        }
      }
    }
  }
}

typedef CUresult (*EncFn)(CUtensorMap*, CUtensorMapDataType, cuuint32_t, void*, const cuuint64_t*, const cuuint64_t*, const cuuint32_t*,
                          const cuuint32_t*, CUtensorMapInterleave, CUtensorMapSwizzle, CUtensorMapL2promotion, CUtensorMapFloatOOBfill);

void enc2(EncFn enc, CUtensorMap* tm, const void* p, uint64_t cols, uint64_t rows, uint32_t boxrows = 64, CUtensorMapL2promotion promo = APROMO) {
  cuuint64_t gd[2] = {cols, rows}, gs[1] = {cols * 2};
  cuuint32_t box[2] = {64, boxrows}, es[2] = {1, 1};
  enc(tm, CU_TENSOR_MAP_DATA_TYPE_BFLOAT16, 2, const_cast<void*>(p), gd, gs, box, es, CU_TENSOR_MAP_INTERLEAVE_NONE, CU_TENSOR_MAP_SWIZZLE_128B,
      promo, CU_TENSOR_MAP_FLOAT_OOB_FILL_NONE);
}
void enc4(EncFn enc, CUtensorMap* tm, const void* p, uint64_t K, uint64_t N, uint64_t d2, uint64_t s2, uint64_t d3, uint64_t s3, uint32_t na) {
  cuuint64_t gd[4] = {64, K, d2, d3}, gs[3] = {N * 2, s2, s3};
  cuuint32_t box[4] = {64, 64, na, 1}, es[4] = {1, 1, 1, 1};
  enc(tm, CU_TENSOR_MAP_DATA_TYPE_BFLOAT16, 4, const_cast<void*>(p), gd, gs, box, es, CU_TENSOR_MAP_INTERLEAVE_NONE, CU_TENSOR_MAP_SWIZZLE_128B,
      WPROMO, CU_TENSOR_MAP_FLOAT_OOB_FILL_NONE);
}

}

extern "C" void kernel_launch(void* const* d_in, const int* in_sizes, int n_in, void* d_out, int out_size) {
  static EncFn enc = nullptr;
  static Scratch* ps = nullptr;
  static void (*kernel)(Ptrs, Params) = mega_kernel<true>;
  if (!enc) {
    cudaDriverEntryPointQueryResult qr;
    cudaGetDriverEntryPoint("cuTensorMapEncodeTiled", (void**)&enc, cudaEnableDefault, &qr);
    int dev = 0, nsm = 0;
    cudaGetDevice(&dev);
    cudaDeviceGetAttribute(&nsm, cudaDevAttrMultiProcessorCount, dev);
    if (nsm != NMAIN + NAUX) kernel = mega_kernel<false>;
    cudaFuncSetAttribute(kernel, cudaFuncAttributeMaxDynamicSharedMemorySize, SMEM_BYTES);
    cudaGetSymbolAddress((void**)&ps, g_s);
  }
  Params P;
  Ptrs Q;
  Q.s = ps;
  void *p_h = ps->h, *p_x = ps->x;
  enc2(enc, &P.tm[TM_XIN], d_in[0], 2048, 1024, 64, XPROMO);
  enc2(enc, &P.tm[TM_X], d_out, 2048, 1024);
  enc2(enc, &P.tm[TM_XA], p_x, 2048, 1024);
  enc2(enc, &P.tm[TM_O], p_h, 3584, 2048);
  enc2(enc, &P.tm[TM_H], p_h, 3584, 2048);
  enc2(enc, &P.tm[TM_X16], d_out, 2048, 1024, 16);
  enc2(enc, &P.tm[TM_XA16], p_x, 2048, 1024, 16);
  enc2(enc, &P.tm[TM_O16], p_h, 3584, 2048, 16);
  enc4(enc, &P.tm[TM_WQKV], d_in[1], 1024, 3072, 3, 2048, 16, 128, 3);
  enc4(enc, &P.tm[TM_WO], d_in[2], 1024, 1024, 16, 128, 1, 128, 2);
  enc4(enc, &P.tm[TM_W1A], d_in[4], 1024, 3584, 56, 128, 1, 128, 4);
  enc4(enc, &P.tm[TM_W1B], d_in[4], 1024, 3584, 56, 128, 1, 128, 3);
  enc4(enc, &P.tm[TM_W2], d_in[6], 3584, 1024, 16, 128, 1, 128, 2);
  Q.out = (__nv_bfloat16*)d_out;
  Q.b1 = (const __nv_bfloat16*)d_in[5];
  Q.x = (const __nv_bfloat16*)d_in[0];
  Q.b2 = (const __nv_bfloat16*)d_in[7];
  kernel<<<NMAIN + NAUX, NTHREADS, SMEM_BYTES, cudaStreamPerThread>>>(Q, P);
}
```
